```python
import torch

def _softmax(x, axis=-1):
    return torch.softmax(x, dim=axis)
def _gelu(x):
    return torch.nn.functional.gelu(x, approximate="tanh")
def _silu(x):
    return torch.nn.functional.silu(x)
def _sigmoid(x):
    return torch.sigmoid(x)
def _layernorm(x, axis=-1, eps=1e-5):
    m = x.mean(dim=axis, keepdim=True)
    v = x.var(dim=axis, keepdim=True, unbiased=False)
    return (x - m) / torch.sqrt(v + eps)
def _scatter_add(tgt, idx, src, axis=0):
    return tgt.clone().index_add_(axis, idx, src)
def _segment_sum(src, seg, n):
    out = torch.zeros((n,) + src.shape[1:], dtype=src.dtype)
    return out.index_add_(0, seg, src)
def _pad(x, pw):
    flat = tuple(v for pair in reversed(pw) for v in pair)
    return torch.nn.functional.pad(x, flat)

kernel_name = 'interleave_layers__sliding_block_cached__moe_arch_mod__decode'

def setup_inputs():

    _w = (lambda a: (lambda t: t.to(torch.bfloat16) if t.is_floating_point() else t)(torch.as_tensor(a)))
    def _A_setup():
        B, Sq, D = 4, 1, 640
        Hq, Hkv, Sk, Dh = 32, 32, 4096, 192
        assert Hq % Hkv == 0, (Hq, Hkv)
        return {
            "x": _w((lambda *s: torch.randn(*s, dtype=torch.bfloat16) * 0.05)(B, Sq, D)),
            "k_cache": _w((lambda *s: torch.randn(*s, dtype=torch.bfloat16) * 1.6)(B, Hkv, Sk, Dh)),
            "v_cache": _w((lambda *s: torch.randn(*s, dtype=torch.bfloat16) * 1.6)(B, Hkv, Sk, Dh)),
            "wq": _w((lambda *s: torch.randn(*s, dtype=torch.bfloat16) * 1.6)(D, Hq * Dh) * (D ** -0.5)),
            "wo": _w((lambda *s: torch.randn(*s, dtype=torch.bfloat16) * 1.6)(Hq * Dh, D) * ((Hq * Dh) ** -0.5)),
        }
    _A_in = _A_setup()

    def _B_setup():
        B, S, D, F, C = 4, 1, 640, 1536, 1
        return {
            "x": _w((lambda *s: torch.randn(*s, dtype=torch.bfloat16) * 0.05)(B, S, D)),
            "w_r": _w((lambda *s: torch.randn(*s, dtype=torch.bfloat16) * 0.05)(D)),
            "w_gate": _w((lambda *s: torch.randn(*s, dtype=torch.bfloat16) * 0.05)(D, F)),
            "w_up": _w((lambda *s: torch.randn(*s, dtype=torch.bfloat16) * 0.05)(D, F)),
            "w_down": _w((lambda *s: torch.randn(*s, dtype=torch.bfloat16) * 0.05)(F, D)),
        }
    _B_in = _B_setup()

    return {
        "A_x": _A_in["x"],
        "A_k_cache": _A_in["k_cache"],
        "A_v_cache": _A_in["v_cache"],
        "A_wq": _A_in["wq"],
        "A_wo": _A_in["wo"],
        "B_x": _B_in["x"],
        "B_w_r": _B_in["w_r"],
        "B_w_gate": _B_in["w_gate"],
        "B_w_up": _B_in["w_up"],
        "B_w_down": _B_in["w_down"],
    }

def reference(A_x, A_k_cache, A_v_cache, A_wq, A_wo, B_x, B_w_r, B_w_gate, B_w_up, B_w_down):
    def _A_ref(x, k_cache, v_cache, wq, wo):
        B, Sq, D = x.shape
        Hq, Dh = 32, 192
        Hkv, Sk = k_cache.shape[1], k_cache.shape[2]
        W = min(4096, max(256, Sk // 4))
        rep = Hq // Hkv
        q = (lambda x, *d: x.permute(*d))((x @ wq).reshape(B, Sq, Hq, Dh), 0, 2, 1, 3)
        k = (lambda x, n, axis: torch.repeat_interleave(x, n, dim=axis))(k_cache[:, :, Sk - W:, :], rep, axis=1)
        v = (lambda x, n, axis: torch.repeat_interleave(x, n, dim=axis))(v_cache[:, :, Sk - W:, :], rep, axis=1)
        scores = torch.einsum("bhqd,bhkd->bhqk", q, k) * (Dh ** -0.5)
        p = _softmax(scores, axis=-1)
        o = torch.einsum("bhqk,bhkd->bhqd", p, v)
        return (lambda x, *d: x.permute(*d))(o, 0, 2, 1, 3).reshape(B, Sq, Hq * Dh) @ wo

    def _B_ref(x, w_r, w_gate, w_up, w_down):
        B, S, D = x.shape
        C = 1
        r = x @ w_r
        idx = torch.argsort(-r, axis=-1)[:, :C]
        idx_e = (lambda x, n, axis: torch.repeat_interleave(x, n, dim=axis))(idx.reshape(B, C, 1), D, axis=2)
        x_sel = (lambda x, i, axis: torch.take_along_dim(x, i, dim=axis))(x, idx_e, axis=1)
        g = _silu(x_sel @ w_gate)
        u = x_sel @ w_up
        y = (g * u) @ w_down
        r_sel = _sigmoid((lambda x, i, axis: torch.take_along_dim(x, i, dim=axis))(r, idx, axis=1))
        y = y * r_sel.reshape(B, C, 1)
        b_off = (torch.arange(B) * S).reshape(B, 1)
        flat_idx = (idx + b_off).reshape(B * C)
        zero = (x * 0.0).reshape(B * S, D)
        upd = _scatter_add(zero, flat_idx, y.reshape(B * C, D), axis=0)
        return x + upd.reshape(B, S, D)

    x = A_x
    x = x + _A_ref(_layernorm(x, axis=-1), A_k_cache, A_v_cache, A_wq, A_wo)
    x = x + _B_ref(_layernorm(x, axis=-1), B_w_r, B_w_gate, B_w_up, B_w_down)
    x = x + _A_ref(_layernorm(x, axis=-1), A_k_cache, A_v_cache, A_wq, A_wo)
    x = x + _B_ref(_layernorm(x, axis=-1), B_w_r, B_w_gate, B_w_up, B_w_down)
    return x
```

```cpp
#include <cuda_runtime.h>
#include <cuda_bf16.h>
#include <cuda.h>
#include <stdint.h>

namespace {

constexpr int NB = 4, DM = 640, NHEAD = 32, DH = 192, SK = 4096, WIN = 1024, FF = 1536;
constexpr int NCTA = 128;
constexpr int TILE = 12288, PAIR = 2 * TILE;

#define CFG_TICK0 488
#define CFG_TICK 515
#define CFG_WLAG 300
#define CFG_GSTEP 700
#define CFG_PFB 5120
#define CFG_VSTEP 350
#define CFG_START 0
#define CFG_TIMED 8
#define CFG_WIN2 4
#define CFG_WIN 3
#define CFG_RSTEP 620
#define CFG_RLAG 0
#define CFG_RSTEP3 450
#define CFG_DLY_A 400
#define CFG_DLY_B 800
#define CFG_DLY_AL 100
#define CFG_DLY_BL 300
#define CFG_DLY_P 100
#define CFG_DLY_Q 100
#define CFG_QKWAIT 1
#define CFG_ZTILE 6
#define CFG_DLY_F 300
#define CFG_LMAX 500
#define CFG_REG_CHAIN 216
#define CFG_REG_ATT 48
#define CFG_REG_HELP 32
constexpr int KB_KV0 = 165;
__host__ __device__ constexpr int kb_ns(int kb) { return kb * CFG_TICK0 / 12; }
constexpr int PF_NS = CFG_TICK0 * CFG_PFB / TILE;
__host__ __device__ constexpr int tile_ns(int j) {
    return kb_ns(KB_KV0) + 2 * PF_NS + j * CFG_TICK0 + (j > 16 ? (j - 16) * (CFG_TICK - CFG_TICK0) : 0) - (j == 63 ? PF_NS : 0);
}

__device__ __forceinline__ uint32_t slots(int k) { return k & 2 ? (k & 1 ? 0x04321658u : 0x65837104u) : (k & 1 ? 0x10482765u : 0x76543210u); }
__device__ __forceinline__ int pass_nibble(int k, int u) { return k > 0 ? 4 + (u & 1) : u; }
__device__ __forceinline__ uint32_t slot_at(uint32_t tab, int u) { return (tab >> (4 * u)) & 15; }

constexpr int NROUND = 11;
constexpr uint32_t ORD_BATCH = 0x3b9910, ORD_LAST = 0x6da, ORD_NO_HEAD = 0x248, ORD_NO_TAIL = 0x092;

constexpr uint32_t SB = 1024;
constexpr uint32_t SM_BAR = SB + 9 * PAIR;
constexpr int B_F1 = 0;
constexpr int B_RR = 24;
constexpr int B_RK = 32;
constexpr int B_RV = 36;
constexpr int B_Z = 37;
constexpr int B_EP = 38;
constexpr int B_W = 39;
constexpr int B_WC = 42;
constexpr int B_FIN = 45;
constexpr int B_F3 = 46;
constexpr int B_QS = 47;
constexpr int B_PS = 48;
constexpr int B_RP = 49;
constexpr int B_FL = 50;
constexpr int NBAR = 51;
__host__ __device__ constexpr uint32_t bar_at(int i) { return SM_BAR + 8 * i; }
constexpr uint32_t SM_EPOCH = SM_BAR + 416;
constexpr uint32_t SM_PROG = SM_EPOCH + 4;
constexpr uint32_t SM_MAX = SM_EPOCH + 16;
constexpr uint32_t SM_FIN = SM_MAX + 16;
constexpr uint32_t SM_Q = SM_FIN + 32;
constexpr uint32_t PSTR = 144;
constexpr uint32_t SM_P = SM_Q + 5 * 384;
constexpr uint32_t SM_X = SM_P + 8 * PSTR;
constexpr uint32_t SM_CSG = SM_X + 40;
constexpr uint32_t SM_CSQ = SM_CSG + 32 * 48;
constexpr uint32_t SM_ONES = SM_X + 8 * 384;
constexpr uint32_t SM_PG = SM_ONES + 48;
constexpr uint32_t SM_PO = SM_PG + 1024;
constexpr uint32_t SM_PQ = SM_PO;
constexpr int SMEM_BYTES = SM_PO + 3072 - SB;
static_assert(SMEM_BYTES <= 232448 && SM_Q % 16 == 0 && SM_P % 16 == 0 && SM_X % 16 == 0 && SM_PO % 16 == 0, "smem");
constexpr uint32_t ST_WQ = SB, ST_WD = SB + 3 * PAIR, ST_WO = SB + 4 * PAIR, ST_WG = SB + 7 * PAIR, ST_X = ST_WG + 40960;

__device__ unsigned g_epoch;
__device__ unsigned g_init;
__device__ uint2 g_q[5][NHEAD][96];
__device__ uint4 g_o[2][NHEAD][8][4][4];
__device__ float4 g_acc[NB][3][64][2][8];
constexpr uint32_t ACC_TYPE = 64 * 256, ACC_SET = 3 * ACC_TYPE;
constexpr uint32_t FULL_A = 0x42040000u, FULL_B = 0x42800000u;

struct Params {
    const unsigned short* x;
    const char* kc;
    const char* vc;
    const char* wq;
    const char* wo;
    const unsigned short* wr;
    const char* wg;
    const char* wu;
    const char* wd;
    unsigned short* out;
};

__device__ __forceinline__ uint32_t smem_u32(const void* p) { return (uint32_t)__cvta_generic_to_shared(p); }
__device__ __forceinline__ void mbar_init(uint32_t a, uint32_t c) { asm volatile("mbarrier.init.shared::cta.b64 [%0], %1;" ::"r"(a), "r"(c) : "memory"); }
__device__ __forceinline__ void mbar_expect_tx(uint32_t a, uint32_t b) {
    asm volatile("mbarrier.arrive.expect_tx.shared::cta.b64 _, [%0], %1;" ::"r"(a), "r"(b) : "memory");
}
__device__ __forceinline__ void mbar_arrive(uint32_t a) { asm volatile("mbarrier.arrive.shared::cta.b64 _, [%0];" ::"r"(a) : "memory"); }
constexpr uint32_t SPIN_LIMIT = 1u << 22;
#define SPIN_DECL uint32_t spins = 0
#define SPIN_CHECK(info) { if (++spins > SPIN_LIMIT) __trap(); }
__device__ __forceinline__ void mbar_wait(uint32_t a, uint32_t parity) {
    uint32_t ok;
    SPIN_DECL;
    while (true) {
        asm volatile("{\n.reg .pred p;\nmbarrier.try_wait.parity.shared::cta.b64 p, [%1], %2;\nselp.u32 %0, 1, 0, p;\n}"
                     : "=r"(ok) : "r"(a), "r"(parity) : "memory");
        if (ok) break;
        SPIN_CHECK((a - SM_BAR) / 8 * 10 + parity);
    }
}
__device__ __forceinline__ uint32_t now_ns() { uint32_t t; asm volatile("mov.u32 %0, %%globaltimer_lo;" : "=r"(t) :: "memory"); return t; }
__device__ __forceinline__ uint32_t clk32() { uint32_t c; asm volatile("mov.u32 %0, %%clock;" : "=r"(c) :: "memory"); return c; }
__device__ __forceinline__ void wait_ns(uint32_t t) { while ((int)(now_ns() - t) < 0) {} }
__device__ __forceinline__ void wait_clk(uint32_t t) { while ((int)(clk32() - t) < 0) {} }
__device__ __forceinline__ bool elect_one() {
    uint32_t e;
    asm volatile("{\n.reg .pred p;\nelect.sync _|p, 0xffffffff;\nselp.u32 %0, 1, 0, p;\n}" : "=r"(e));
    return e;
}
constexpr uint64_t POL_FIRST = 0x12F0000000000000ull, POL_NORMAL = 0x1000000000000000ull;
__device__ __forceinline__ void tma_tile(uint32_t dst, const CUtensorMap* tm, int group, uint32_t bar, uint64_t pol) {
    asm volatile("cp.async.bulk.tensor.4d.shared::cluster.global.mbarrier::complete_tx::bytes.L2::cache_hint"
                 " [%0], [%1, {%3, %3, %3, %4}], [%2], %5;"
                 ::"r"(dst), "l"(tm), "r"(bar), "r"(0), "r"(group), "l"(pol) : "memory");
}
__device__ __forceinline__ void tma2d(uint32_t dst, const CUtensorMap* tm, int x, int y, uint32_t bar) {
    asm volatile("cp.async.bulk.tensor.2d.shared::cluster.global.mbarrier::complete_tx::bytes [%0], [%1, {%3, %4}], [%2];"
                 ::"r"(dst), "l"(tm), "r"(bar), "r"(x), "r"(y) : "memory");
}
__device__ __forceinline__ void bulk_load(uint32_t dst, const void* src, uint32_t bytes, uint32_t bar) {
    asm volatile("cp.async.bulk.shared::cluster.global.mbarrier::complete_tx::bytes [%0], [%1], %2, [%3];"
                 ::"r"(dst), "l"(src), "r"(bytes), "r"(bar) : "memory");
}
__device__ __forceinline__ void l2_prefetch(const void* p, uint32_t bytes) {
    asm volatile("cp.async.bulk.prefetch.L2.global [%0], %1;" ::"l"(p), "r"(bytes) : "memory");
}
__device__ __forceinline__ void mma16816(float (&c)[4], uint32_t a0, uint32_t a1, uint32_t a2, uint32_t a3, uint32_t b0, uint32_t b1) {
    asm volatile("mma.sync.aligned.m16n8k16.row.col.f32.bf16.bf16.f32 {%0,%1,%2,%3}, {%4,%5,%6,%7}, {%8,%9}, {%0,%1,%2,%3};"
                 : "+f"(c[0]), "+f"(c[1]), "+f"(c[2]), "+f"(c[3]) : "r"(a0), "r"(a1), "r"(a2), "r"(a3), "r"(b0), "r"(b1));
}
__device__ __forceinline__ void mma1688(float (&c)[4], uint32_t a0, uint32_t a1, uint32_t b0) {
    asm volatile("mma.sync.aligned.m16n8k8.row.col.f32.bf16.bf16.f32 {%0,%1,%2,%3}, {%4,%5}, {%6}, {%0,%1,%2,%3};"
                 : "+f"(c[0]), "+f"(c[1]), "+f"(c[2]), "+f"(c[3]) : "r"(a0), "r"(a1), "r"(b0));
}
__device__ __forceinline__ void ldsm4t(uint32_t (&r)[4], uint32_t a, uint32_t& zero) {
    asm volatile("ldmatrix.sync.aligned.m8n8.x4.trans.shared.b16 {%0,%1,%2,%3}, [%4];"
                 : "=r"(r[0]), "=r"(r[1]), "=r"(r[2]), "=r"(r[3]) : "r"(a + zero) : "memory");
    zero &= r[3];
}
__device__ __forceinline__ uint4 ld_pkt(const void* p) {
    uint4 v;
    asm volatile("{\n.reg .b128 t;\nld.relaxed.gpu.global.b128 t, [%4];\nmov.b128 {%0,%1,%2,%3}, t;\n}"
                 : "=r"(v.x), "=r"(v.y), "=r"(v.z), "=r"(v.w) : "l"(p) : "memory");
    return v;
}
__device__ __forceinline__ void st_pkt(const void* p, uint32_t a, uint32_t b, uint32_t c, uint32_t d) {
    asm volatile("{\n.reg .b128 t;\nmov.b128 t, {%1,%2,%3,%4};\nst.relaxed.gpu.global.b128 [%0], t;\n}"
                 ::"l"(p), "r"(a), "r"(b), "r"(c), "r"(d) : "memory");
}
__device__ __forceinline__ uint2 ld_pkt8(const void* p) {
    uint2 v;
    asm volatile("{\n.reg .b64 t;\nld.relaxed.gpu.global.b64 t, [%2];\nmov.b64 {%0,%1}, t;\n}" : "=r"(v.x), "=r"(v.y) : "l"(p) : "memory");
    return v;
}
__device__ __forceinline__ void red_cell(const char* p, float a, float b, float c) {
    asm volatile("red.relaxed.gpu.global.add.v4.f32 [%0], {%1,%2,%3,%4};" ::"l"(p), "f"(a), "f"(b), "f"(c), "f"(1.0f) : "memory");
}
__device__ __forceinline__ uint32_t cell_count(const char* p) {
    uint32_t c;
    asm volatile("ld.relaxed.gpu.global.u32 %0, [%1+12];" : "=r"(c) : "l"(p) : "memory");
    return c;
}
#define PRED(n) "{\n.reg .pred p;\nsetp.ne.u32 p, %" #n ", 0;\n"
__device__ __forceinline__ void red_cell_if(bool on, const char* p, float a, float b, float c) {
    asm volatile(PRED(5) "@p red.relaxed.gpu.global.add.v4.f32 [%0], {%1,%2,%3,%4};\n}"
                 ::"l"(p), "f"(a), "f"(b), "f"(c), "f"(1.0f), "r"((uint32_t)on) : "memory");
}
__device__ __forceinline__ void st_pkt8_if(bool on, const void* p, uint32_t a, uint32_t b) {
    asm volatile(PRED(3) ".reg .b64 t;\nmov.b64 t, {%1,%2};\n@p st.relaxed.gpu.global.b64 [%0], t;\n}" ::"l"(p), "r"(a), "r"(b), "r"((uint32_t)on) : "memory");
}
__device__ __forceinline__ void st_pkt_if(bool on, const void* p, uint32_t a, uint32_t b, uint32_t c, uint32_t d) {
    asm volatile(PRED(5) ".reg .b128 t;\nmov.b128 t, {%1,%2,%3,%4};\n@p st.relaxed.gpu.global.b128 [%0], t;\n}"
                 ::"l"(p), "r"(a), "r"(b), "r"(c), "r"(d), "r"((uint32_t)on) : "memory");
}
__device__ __forceinline__ void mbar_arrive_if(bool on, uint32_t a) {
    asm volatile(PRED(1) "@p mbarrier.arrive.shared::cta.b64 _, [%0];\n}" ::"r"(a), "r"((uint32_t)on) : "memory");
}
__device__ __forceinline__ void sts16_if(bool on, uint32_t a, uint32_t v) {
    asm volatile(PRED(2) "@p st.shared.u16 [%0], %1;\n}" ::"r"(a), "h"((unsigned short)v), "r"((uint32_t)on) : "memory");
}
__device__ __forceinline__ void sts32_if(bool on, uint32_t a, uint32_t v) {
    asm volatile(PRED(2) "@p st.shared.u32 [%0], %1;\n}" ::"r"(a), "r"(v), "r"((uint32_t)on) : "memory");
}
__device__ __forceinline__ void sts128_if(bool on, uint32_t a, uint32_t x, uint32_t y, uint32_t z, uint32_t w) {
    asm volatile(PRED(5) "@p st.shared.v4.u32 [%0], {%1,%2,%3,%4};\n}" ::"r"(a), "r"(x), "r"(y), "r"(z), "r"(w), "r"((uint32_t)on) : "memory");
}
__device__ __forceinline__ void prefetch_if(bool on, const void* p) {
    asm volatile(PRED(1) "@p prefetch.global.L2 [%0];\n}" ::"l"(p), "r"((uint32_t)on) : "memory");
}
__device__ __forceinline__ float fast_rcp(float x) { float r; asm("rcp.approx.ftz.f32 %0, %1;" : "=f"(r) : "f"(x)); return r; }
__device__ __forceinline__ float fast_sqrt(float x) { float r; asm("sqrt.approx.ftz.f32 %0, %1;" : "=f"(r) : "f"(x)); return r; }
__device__ __forceinline__ float fast_ex2(float x) { float r; asm("ex2.approx.ftz.f32 %0, %1;" : "=f"(r) : "f"(x)); return r; }
__device__ __forceinline__ uint32_t pack2(float lo, float hi) {
    uint32_t r;
    asm("cvt.rn.bf16x2.f32 %0, %1, %2;" : "=r"(r) : "f"(hi), "f"(lo));
    return r;
}
__device__ __forceinline__ float bfr(float x) { return __uint_as_float(pack2(0.f, x)); }
__device__ __forceinline__ uint32_t badd2(uint32_t a, uint32_t b) { uint32_t r; asm("add.rn.bf16x2 %0, %1, %2;" : "=r"(r) : "r"(a), "r"(b)); return r; }
__device__ __forceinline__ uint32_t bsub2(uint32_t a, uint32_t b) { uint32_t r; asm("sub.rn.bf16x2 %0, %1, %2;" : "=r"(r) : "r"(a), "r"(b)); return r; }
__device__ __forceinline__ uint32_t bmul2(uint32_t a, uint32_t b) { uint32_t r; asm("mul.rn.bf16x2 %0, %1, %2;" : "=r"(r) : "r"(a), "r"(b)); return r; }
__device__ __forceinline__ float bf_lo(uint32_t w) { return __uint_as_float(w << 16); }
__device__ __forceinline__ float bf_hi(uint32_t w) { return __uint_as_float(w & 0xffff0000u); }
__device__ __forceinline__ float F(uint32_t t) { return __uint_as_float(t); }
__device__ __forceinline__ uint32_t lds16(uint32_t a) { unsigned short h; asm volatile("ld.shared.u16 %0, [%1];" : "=h"(h) : "r"(a) : "memory"); return h; }
__device__ __forceinline__ uint32_t lds32(uint32_t a) { uint32_t v; asm volatile("ld.shared.u32 %0, [%1];" : "=r"(v) : "r"(a) : "memory"); return v; }
__device__ __forceinline__ uint2 lds64(uint32_t a) {
    uint2 v; asm volatile("ld.shared.v2.u32 {%0,%1}, [%2];" : "=r"(v.x), "=r"(v.y) : "r"(a) : "memory"); return v;
}
__device__ __forceinline__ uint4 lds128(uint32_t a) {
    uint4 v; asm volatile("ld.shared.v4.u32 {%0,%1,%2,%3}, [%4];" : "=r"(v.x), "=r"(v.y), "=r"(v.z), "=r"(v.w) : "r"(a) : "memory"); return v;
}
__device__ __forceinline__ float sum8(const uint4& u, const uint4& v) {
    return ((F(u.x) + F(u.y)) + (F(u.z) + F(u.w))) + ((F(v.x) + F(v.y)) + (F(v.z) + F(v.w)));
}
__device__ __forceinline__ void sts16(uint32_t a, uint32_t v) { asm volatile("st.shared.u16 [%0], %1;" ::"r"(a), "h"((unsigned short)v) : "memory"); }
__device__ __forceinline__ void sts32(uint32_t a, uint32_t v) { asm volatile("st.shared.u32 [%0], %1;" ::"r"(a), "r"(v) : "memory"); }
__device__ __forceinline__ void stsf(uint32_t a, float v) { asm volatile("st.shared.f32 [%0], %1;" ::"r"(a), "f"(v) : "memory"); }
__device__ __forceinline__ void stsf2(uint32_t a, float x, float y) { asm volatile("st.shared.v2.f32 [%0], {%1,%2};" ::"r"(a), "f"(x), "f"(y) : "memory"); }
__device__ __forceinline__ void stsf4(uint32_t a, float x, float y, float z, float w) {
    asm volatile("st.shared.v4.f32 [%0], {%1,%2,%3,%4};" ::"r"(a), "f"(x), "f"(y), "f"(z), "f"(w) : "memory");
}
template <int ID, int N> __device__ __forceinline__ void bar_sync() { asm volatile("bar.sync %0, %1;" ::"n"(ID), "n"(N) : "memory"); }
template <int ID, int N> __device__ __forceinline__ void bar_arrive() { asm volatile("bar.arrive %0, %1;" ::"n"(ID), "n"(N) : "memory"); }
__device__ __forceinline__ void fence_async() { asm volatile("fence.proxy.async.shared::cta;" ::: "memory"); }
__device__ __forceinline__ float shx(float v, int m) { return __shfl_xor_sync(0xffffffffu, v, m); }
__device__ __forceinline__ float shi(float v, int l) { return __shfl_sync(0xffffffffu, v, l); }
__device__ __forceinline__ uint32_t shi(uint32_t v, int l) { return __shfl_sync(0xffffffffu, v, l); }
__device__ __forceinline__ uint32_t opaque(uint32_t x) { asm volatile("mov.u32 %0, %0;" : "+r"(x)); return x; }
__device__ __forceinline__ const char* opaque(const char* x) { asm volatile("mov.u64 %0, %0;" : "+l"(x)); return x; }
constexpr float LOG2E = 1.4426950408889634f;

#define TRACE(idx) do {} while (0)
#define TRACES(slot) do {} while (0)

__device__ __forceinline__ int kv_group(int k, int t) {
    const int cta = blockIdx.x;
    return ((k * NHEAD + (cta >> 2)) * SK + (SK - WIN) + (cta & 3) * 256 + t * 32) / 8;
}
__device__ __forceinline__ uint32_t phase_ns() { return (((blockIdx.x >> 2) * 13) & 31) * (CFG_TICK0 / 32); }

__device__ __forceinline__ void prefetch_role(const Params& p, const CUtensorMap* tmV, uint32_t t0) {
    const int cta = blockIdx.x;
    t0 += phase_ns();
#pragma unroll 1
    for (int i = 0; i < 5; i++) {
        wait_ns(t0 + i * CFG_TICK0);
        if (elect_one()) l2_prefetch(p.wq + (size_t)(128 * i + cta) * 12288, 12288);
    }
#pragma unroll 1
    for (int i = 0; i < 5; i++) {
        wait_ns(t0 + kb_ns(75) + i * kb_ns(6));
        if (elect_one()) { l2_prefetch(p.wg + (128 * i + cta) * 3072, 3072); l2_prefetch(p.wu + (128 * i + cta) * 3072, 3072); }
    }
#pragma unroll 1
    for (int i = 0; i < 6; i++) {
        wait_ns(t0 + kb_ns(105) + i * kb_ns(10));
        if (elect_one()) l2_prefetch(p.wo + (size_t)((cta >> 2) * DH + 32 * i + 8 * (cta & 3)) * 1280, 10240);
    }
    bar_sync<6, 64>();
#pragma unroll 1
    for (int i = 4; i < 4 * NB; i++) {
        const int k = i >> 2, t = 12 + (i & 3);
        mbar_wait(bar_at(B_RK + ((i >> 1) & 1)), (k - 1) & 1);
        SPIN_DECL;
        while ((int)lds32(SM_PROG) <= 16 * k + t) SPIN_CHECK(i);
        if (i < 4 * NB - 1) wait_ns(t0);
        t0 = now_ns() + CFG_VSTEP;
        if (elect_one()) {
            mbar_expect_tx(bar_at(B_F1 + t), TILE);
            tma_tile(SB + slot_at(slots(k), t >> 1) * PAIR + (t & 1) * TILE, tmV, kv_group(k, t & 7), bar_at(B_F1 + t), POL_FIRST);
        }
        TRACE(256 + 16 * k + t);
    }
}

struct WeightMaps { CUtensorMap q, o, g, u; };
__device__ __forceinline__ void load_role(const Params& p, const CUtensorMap* tmK, const CUtensorMap* tmV, uint32_t t0) {
    t0 += phase_ns();
    wait_ns(t0 + kb_ns(60));
    if (elect_one()) bulk_load(ST_WD, p.wd + blockIdx.x * 15360, 15360, bar_at(B_W));
    auto ahead = [&](int j) {
        if (CFG_PFB > 0) l2_prefetch((j & 8 ? p.vc : p.kc) + (size_t)kv_group(j >> 4, j & 7) * 3072 + (TILE - CFG_PFB), CFG_PFB);
    };
#pragma unroll 1
    for (int j = 0; j < 2; j++) {
        wait_ns(t0 + kb_ns(KB_KV0) + j * PF_NS);
        if (elect_one()) ahead(j);
    }
#pragma unroll 1
    for (int j = 0; j < 16 * NB; j++) {
        const int k = j >> 4, t = j & 15, u = t >> 1;
        if (j == 0 || j == 8 || j == 14) mbar_wait(bar_at(B_WC + j / 7), 0);
        if (k > 0 && t < 12) {
            if (t >= 4) mbar_wait(bar_at(B_RR + t - 4), k & 1);
            else if (t >= 2) mbar_wait(bar_at(B_RP), (k - 1) & 1);
            else if (k > 1) mbar_wait(bar_at(B_RK + 3), k & 1);
            else mbar_wait(bar_at(B_RR + t), 0);
        }
        const int jw = j - CFG_WIN;
        if (jw >= 0 && (jw < 16 || (jw & 15) < 12)) mbar_wait(bar_at(B_F1 + (jw & 15)), (jw >> 4) & 1);
        const int jv = j - CFG_WIN2;
        if (jv >= 16 && (jv & 15) >= 12) mbar_wait(bar_at(B_F1 + (jv & 15)), (jv >> 4) & 1);
        const uint32_t dst = SB + slot_at(slots(k), t < 8 ? pass_nibble(k, u) : u) * PAIR + (t & 1) * TILE;
        const int late = now_ns() - (t0 + tile_ns(j));
        if (late > CFG_LMAX) t0 += late - CFG_LMAX;
        wait_ns(t0 + tile_ns(j));
        if (elect_one()) {
            if (k > 0 && t >= 12) {
                l2_prefetch(p.vc + (size_t)kv_group(k, t & 7) * 3072, TILE - CFG_PFB);
            } else {
                mbar_expect_tx(bar_at(B_F1 + t), TILE);
                tma_tile(dst, t & 8 ? tmV : tmK, kv_group(k, t & 7), bar_at(B_F1 + t), t < 10 && j >= 8 && j < 56 ? POL_NORMAL : POL_FIRST);
            }
            if (j + 2 < 16 * NB) ahead(j + 2);
            sts32(SM_PROG, j + 1);
        }
        TRACE(128 + j);
    }
}

__device__ __forceinline__ void reload_role(const Params& p, const CUtensorMap* tmK, const CUtensorMap* tmV, const WeightMaps* tm, uint32_t t0) {
    const int cta = blockIdx.x;
    t0 += CFG_TICK0 + CFG_WLAG + phase_ns();
#pragma unroll 1
    for (int i = 0; i < 5; i++) {
        wait_ns(t0 + i * CFG_TICK0);
        if (elect_one()) tma2d(ST_WQ + i * 12288, &tm->q, 48 * cta, 128 * i, bar_at(B_W));
        if (i == 1) bar_sync<5, 480>();
    }
#pragma unroll 1
    for (int i = 0, o = 0; i < 10;) {
        const uint32_t now = now_ns() - t0;
        if (o < 6 && (int)now >= kb_ns(105) + o * kb_ns(10)) {
            if (elect_one()) tma2d(ST_WO + o * 10240, &tm->o, 160 * (cta & 3), (cta >> 2) * DH + 32 * o, bar_at(B_W + 1));
            o++;
        } else if ((int)now >= kb_ns(77) + i * CFG_GSTEP && (i < 9 || o == 6)) {
            if (elect_one()) tma2d(ST_WG + (i & 1) * 20480 + (i >> 1) * 4096, i & 1 ? &tm->u : &tm->g, (12 * cta) & ~7, 128 * (i >> 1), bar_at(B_W + 2));
            i++;
        }
    }
#pragma unroll 1
    for (int k = 0; k < NB - 1; k++) {
        mbar_wait(bar_at(B_RK + 2), k & 1);
        if (elect_one()) {
            const uint32_t dst = SB + slot_at(slots(k), 2) * PAIR;
            mbar_expect_tx(bar_at(B_FL), PAIR);
            tma_tile(dst, tmV, kv_group(k, 0), bar_at(B_FL), POL_FIRST);
            tma_tile(dst + TILE, tmV, kv_group(k, 1), bar_at(B_FL), POL_FIRST);
        }
        mbar_wait(bar_at(B_RV), k & 1);
        uint32_t due = now_ns() + (k == NB - 2 ? 0 : CFG_RLAG);
        if (elect_one()) mbar_expect_tx(bar_at(B_F3), 4 * PAIR);
#pragma unroll 1
        for (int t = 0; t < 8; t++) {
            wait_ns(due);
            due += k == NB - 2 ? CFG_RSTEP3 : CFG_RSTEP;
            if (elect_one())
                tma_tile(SB + slot_at(slots(k + 1), t >> 1) * PAIR + (t & 1) * TILE, tmK, kv_group(k + 1, t), bar_at(B_F3), POL_FIRST);
        }
        TRACE(121 + k);
    }
}

__device__ __forceinline__ void zero_role(const Params& p, int lane, unsigned ticket, uint32_t t0) {
    const int cta = blockIdx.x;
    const uint32_t epoch = __shfl_sync(0xffffffffu, ticket, 0) / NCTA + 1;
    if (lane == 0) { sts32(SM_EPOCH, epoch); mbar_arrive(bar_at(B_EP)); }
    const int cl = 2 * (cta & 15) + (lane & 1);
    const int col = 80 * (cta >> 4) + (cl & 2 ? 48 : 0) + (cl >> 2) + (cl & 1 ? 8 : 0);
    const char* own = reinterpret_cast<const char*>(g_acc) + (cta >> 4) * 2048 + (cl >> 2) * 256 + (cl & 3) * 16;
#pragma unroll 1
    for (int k = 0; k < NB + 2; k++) {
        if (k < NB) {
            wait_ns(t0 + tile_ns(16 * k + CFG_ZTILE));
            const int lg = lane >> 3, ty = (lane & 7) >> 1;
            const char* dst = own + (k - (lg >> 1)) * (int)ACC_SET + ty * ACC_TYPE + (lg ? 128 : 0);
            uint32_t v0 = 0, v1 = 0, v2 = 0, v3 = 0;
            if (lane < 2) {
                const unsigned short* xp = p.x + k * DM + col;
                v0 = __ldg(xp) << 16; v1 = __ldg(xp + 16) << 16; v2 = cl & 2 ? 0 : __ldg(xp + 32) << 16; v3 = 0x3f800000u;
            }
            if (ty < 3 && (lg == 0 || (lg == 1 && (ty == 0 || k == NB - 1)) || (lg == 2 && k > 0 && ty > 0))) st_pkt(dst, v0, v1, v2, v3);
            asm volatile("fence.acq_rel.gpu;" ::: "memory");
            __syncwarp();
            if (lane == 0) asm volatile("red.relaxed.gpu.global.add.u32 [%0], 1;" ::"l"(&g_init) : "memory");
            const uint32_t target = ((epoch - 1) * NB + k + 1) * NCTA;
            SPIN_DECL;
            while (true) {
                __nanosleep(400);
                uint32_t v;
                asm volatile("ld.acquire.gpu.global.u32 %0, [%1];" : "=r"(v) : "l"(&g_init) : "memory");
                if (__all_sync(0xffffffffu, (int)(v - target) >= 0)) break;
                SPIN_CHECK(v);
            }
        }
        uint4 r;
        if (k == 1) mbar_wait(bar_at(B_RK), 0);
        if (k > 1) {
            mbar_wait(bar_at(B_FIN), k & 1);
            r = lds128(SM_FIN + (lane & 1) * 16);
        }
        __syncwarp();
        if (lane == 0) mbar_arrive(bar_at(B_Z));
        if (k > 1) {
            const int b = k - 2;
            const char* src = own + b * ACC_SET + (1 + ((lane >> 1) & 1)) * ACC_TYPE + 128;
            unsigned short* o = p.out + b * DM + col;
            wait_clk(clk32() + CFG_DLY_F);
            uint4 v = {};
            SPIN_DECL;
            while (true) {
                v = ld_pkt(src);
                if (__all_sync(0xffffffffu, v.w == FULL_B)) break;
                SPIN_CHECK(k);
            }
            const float y0 = F(v.x) + shx(F(v.x), 2), y1 = F(v.y) + shx(F(v.y), 2), y2 = F(v.z) + shx(F(v.z), 2);
            const uint32_t x01 = badd2(r.x, badd2(r.y, bmul2(pack2(y0, y1), r.w)));
            const uint32_t x2 = badd2(r.z, badd2(r.z >> 16, bmul2(pack2(y2, 0.f), r.w)));
            if (lane < 2) {
                o[0] = x01; o[16] = x01 >> 16;
                if (!(cl & 2)) o[32] = x2;
            }
            TRACES((2 * b + 1) * 6 + 4);
        }
    }
}

__host__ __device__ constexpr uint32_t desc_lo(uint32_t addr) { return ((addr & 0x3FFFFu) >> 4) | (1u << 16); }
constexpr uint32_t DESC_HI_TILE = (3072u >> 4) | (1u << 30);
constexpr uint32_t DESC_HI_VEC = 1u;
template <int TA, int AOFF, int BOFF>
__device__ __forceinline__ void wgmma_n8(float (&d)[4], uint32_t alo, uint32_t blo, int accumulate) {
    asm volatile("{\n.reg .pred p;\n.reg .b32 a, b;\n.reg .b64 da, db;\nsetp.ne.b32 p, %6, 0;\n"
                 "add.u32 a, %4, %8;\nadd.u32 b, %5, %9;\nmov.b64 da, {a, %10};\nmov.b64 db, {b, %11};\n"
                 "wgmma.mma_async.sync.aligned.m64n8k16.f32.bf16.bf16 {%0,%1,%2,%3}, da, db, p, 1, 1, %7, 0;\n}"
                 : "+f"(d[0]), "+f"(d[1]), "+f"(d[2]), "+f"(d[3])
                 : "r"(alo), "r"(blo), "r"(accumulate), "n"(TA), "n"(AOFF >> 4), "n"(BOFF >> 4), "n"(DESC_HI_TILE), "n"(DESC_HI_VEC));
}
template <int KS>
__device__ __forceinline__ void qk_steps(float (&d)[4], uint32_t alo, uint32_t blo) {
    if constexpr (KS < 12) {
        wgmma_n8<0, (KS >> 2) * 1024 + (KS & 3) * 32, KS * 32>(d, alo, blo, KS > 0);
        qk_steps<KS + 1>(d, alo, blo);
    }
}
__device__ __forceinline__ void pv_steps(float (&e)[3][4], uint32_t alo, uint32_t blo, int acc) {
    wgmma_n8<1, 0, 0>(e[0], alo, blo, acc); wgmma_n8<1, 1024, 0>(e[1], alo, blo, acc); wgmma_n8<1, 2048, 0>(e[2], alo, blo, acc);
    wgmma_n8<1, 6144, 32>(e[0], alo, blo, 1); wgmma_n8<1, 7168, 32>(e[1], alo, blo, 1); wgmma_n8<1, 8192, 32>(e[2], alo, blo, 1);
}
__device__ __forceinline__ void wg_fence() { asm volatile("wgmma.fence.sync.aligned;" ::: "memory"); }
__device__ __forceinline__ void wg_commit() { asm volatile("wgmma.commit_group.sync.aligned;" ::: "memory"); }
template <int N> __device__ __forceinline__ void wg_wait() { asm volatile("wgmma.wait_group.sync.aligned %0;" ::"n"(N) : "memory"); }
__device__ __forceinline__ void qk_pair(float (&d)[4], uint32_t slot, uint32_t qslot) {
    wg_fence();
    qk_steps<0>(d, desc_lo(SB) + slot * (PAIR >> 4), desc_lo(SM_Q) + qslot * (384 >> 4));
    wg_commit();
}
__device__ __forceinline__ void acc_ready(float (&d)[4]) { asm volatile("" : "+f"(d[0]), "+f"(d[1]), "+f"(d[2]), "+f"(d[3]) :: "memory"); }
__device__ __forceinline__ uint32_t score_pair(float (&d)[4], int lane) {
    acc_ready(d);
    const float scale = 0.07216878364870322f;
    const uint32_t r = pack2(d[0], d[2]);
    return shi(pack2(bf_lo(r) * scale, bf_hi(r) * scale), lane & 28);
}

__device__ __forceinline__ void attention_role(const Params& p, int w, int lane) {
    const int cta = blockIdx.x, t4 = lane & 3, g = lane >> 2;
    mbar_wait(bar_at(B_EP), 0);
    const uint32_t tag0 = lds32(SM_EPOCH) * NB;
    auto get_q = [&](int slot, uint32_t tag) {
        if (w < 3) {
            const uint2* src = &g_q[slot][cta >> 2][w * 32 + lane];
            uint2 v;
            SPIN_DECL;
            while (true) {
                v = ld_pkt8(src);
                if (__all_sync(0xffffffffu, v.y == tag)) break;
                SPIN_CHECK(slot);
            }
            sts32(SM_Q + slot * 384 + (w * 32 + lane) * 4, v.x);
            fence_async();
        }
        bar_sync<4, 128>();
    };
    uint32_t m1 = 0;
    auto softmax = [&](uint32_t sc, int ps) -> uint32_t {
        const float s0 = bf_lo(sc), s1 = bf_hi(sc);
        int key = __float_as_int(fmaxf(s0, s1));
        key ^= (key >> 31) & 0x7fffffff;
        key = __reduce_max_sync(0xffffffffu, key);
        sts32_if(lane == 0, SM_MAX + w * 4, key);
        bar_sync<4, 128>();
        const uint4 mx = lds128(SM_MAX);
        key = max(max((int)mx.x, (int)mx.y), max((int)mx.z, (int)mx.w));
        key ^= (key >> 31) & 0x7fffffff;
        const float mb = __int_as_float(key) * LOG2E;
        const uint32_t pp = pack2(fast_ex2(fmaf(s0, LOG2E, -mb)), fast_ex2(fmaf(s1, LOG2E, -mb)));
        const uint32_t a = SM_P + (ps * 4 + t4) * PSTR + (16 * w + g) * 2;
        sts16(a, pp); sts16(a + 16, pp >> 16);
        fence_async();
        bar_sync<4, 128>();
        return key;
    };
    mbar_wait(bar_at(B_QS), 0);
#pragma unroll 1
    for (int b = 0; b < NB; b++) { TRACES(84 + b); get_q(b, tag0 + b); }
    TRACES(73);
#pragma unroll 1
    for (int it = 0; it <= NB; it++) {
        uint32_t m2 = 0;
#pragma unroll 1
        for (int ps = it == NB; ps <= (it > 0); ps++) {
            uint32_t sc = 0;
            const int k = it - ps;
            const uint32_t tab = slots(k);
            if (ps == 0) {
#pragma unroll 1
                for (int t = 0; t < 8; t++) {
                    mbar_wait(bar_at(B_F1 + t), k & 1);
                    float d[4];
                    const uint32_t alo = desc_lo(SB) + slot_at(tab, pass_nibble(k, t >> 1)) * (PAIR >> 4), blo = desc_lo(SM_Q) + k * (384 >> 4);
#pragma unroll 1
                    for (int c = 0; c < 3; c++) {
                        wg_fence();
                        wgmma_n8<0, 0, 0>(d, alo + c * 64, blo + c * 8, c > 0); wgmma_n8<0, 32, 32>(d, alo + c * 64, blo + c * 8, 1);
                        wgmma_n8<0, 64, 64>(d, alo + c * 64, blo + c * 8, 1); wgmma_n8<0, 96, 96>(d, alo + c * 64, blo + c * 8, 1);
                        wg_commit();
                        if (CFG_QKWAIT) wg_wait<0>();
                    }
                    wg_wait<0>();
                    if ((t & 1) == (w >> 1)) {
                        mbar_arrive_if(lane == 0, bar_at(B_RR + t));
                        const uint32_t s = score_pair(d, lane);
                        if (t4 == t >> 1) sc = s;
                    }
                }
            } else {
                TRACES(48 + k * 6);
                if (k > 0) mbar_wait(bar_at(B_F3), it & 1);
                mbar_wait(bar_at(B_QS), it & 1);
                wait_clk(clk32() + CFG_DLY_Q);
                get_q(4, tag0 + k);
                TRACES(49 + k * 6);
                float d[4][4];
#pragma unroll
                for (int u = 0; u < 4; u++) {
                    qk_pair(d[u], slot_at(tab, u), 4);
                    if (u == 2) { wg_wait<2>(); mbar_arrive_if(lane == 0, bar_at(B_RK)); }
                }
                sc = score_pair(d[0], lane);
                wg_wait<2>();
                mbar_arrive_if(lane == 0, bar_at(B_RK + 1));
                uint32_t s = score_pair(d[1], lane);
                if (t4 == 1) sc = s;
                wg_wait<1>();
                mbar_arrive_if(lane == 0, bar_at(B_RK + 2));
                s = score_pair(d[2], lane);
                if (t4 == 2) sc = s;
                wg_wait<0>();
                s = score_pair(d[3], lane);
                mbar_arrive_if(lane == 0, bar_at(B_RK + 3));
                if (t4 == 3) sc = s;
                TRACES(50 + k * 6);
            }
            m2 = softmax(sc, ps);
            if (ps == 0) m1 = m2;
        }
#pragma unroll 1
        for (int ps = it > 0; ps >= (it == NB); ps--) {
            const int k = it - ps;
            TRACES(ps ? 51 + k * 6 : 95);
            const uint32_t tab = slots(k);
            const char* dst = opaque(reinterpret_cast<const char*>(&g_o[ps][cta >> 2][2 * w + (g >> 2)][cta & 3][g & 3]));
            st_pkt_if(t4 == 0, dst, 0, 0, 0, tag0 + k + 128);
            float e[3][4];
            uint4 u;
            float l, lx;
#pragma unroll
            for (int t = 0; t < 8; t++) {
                const int pr = ((t >> 1) + ps) & 3;
                const bool late = t >= 6 && ps && k < NB - 1;
                if (ps == 0) mbar_wait(bar_at(B_F1 + 8 + t), k & 1);
                if (t == 6 && late) mbar_wait(bar_at(B_FL), k & 1);
                wg_fence();
                pv_steps(e, desc_lo(SB + (t & 1) * TILE) + slot_at(tab, late ? 2 : 4 + pr) * (PAIR >> 4),
                         desc_lo(SM_P + (t & 1) * 64) + (4 * ps + pr) * (PSTR >> 4), t > 0);
                wg_commit();
                if (t == 2 && ps == 0) { wg_wait<1>(); mbar_arrive_if(lane == 0, bar_at(B_RP)); }
                if (t == 0) u = lds128(SM_P + (ps * 4 + (lane >> 3)) * PSTR + (lane & 7) * 16);
                if (t == 1) l = ((bf_lo(u.x) + bf_hi(u.x)) + (bf_lo(u.y) + bf_hi(u.y))) + ((bf_lo(u.z) + bf_hi(u.z)) + (bf_lo(u.w) + bf_hi(u.w)));
                if (t >= 2 && t <= 6) l += lx;
                if (t >= 1 && t <= 5) lx = shx(l, 32 >> t);
                if (t == 6) m2 = opaque((g < 4 ? (ps ? m2 : m1) : (__float_as_uint(l) + 0x80u) & 0xffffff00u) | ((tag0 + k) & 0xffu));
            }
            wg_wait<0>();
            acc_ready(e[0]); acc_ready(e[1]); acc_ready(e[2]);
            st_pkt_if(t4 == 0, dst, pack2(e[0][0], e[0][2]), pack2(e[1][0], e[1][2]), pack2(e[2][0], e[2][2]), m2);
            mbar_arrive_if(lane == 0, bar_at(ps ? B_RV : B_PS));
            TRACES((ps ? 52 : 53) + k * 6);
        }
    }
}

__device__ __forceinline__ void ln_finish(float s, float q, float& mean_b, float& rden) {
    const float mean = s * (1.f / DM);
    const float var = fmaxf(fmaf(q, 1.f / DM, -mean * mean), 0.f);
    mean_b = bfr(mean);
    rden = fast_rcp(bfr(fast_sqrt(bfr(bfr(var) + 1e-5f))));
}
__device__ __forceinline__ void ln_fast(float s, float q, float& mean, float& rstd) {
    mean = s * (1.f / DM);
    asm("rsqrt.approx.ftz.f32 %0, %1;" : "=f"(rstd) : "f"(fmaxf(fmaf(-mean, mean, fmaf(q, 1.f / DM, 1e-5f)), 1e-5f)));
}
__device__ __forceinline__ uint32_t ln_apply(uint32_t w, float mean_b, float rden) {
    const uint32_t d = bsub2(w, __byte_perm(__float_as_uint(mean_b), 0, 0x3232));
    return pack2(bf_lo(d) * rden, bf_hi(d) * rden);
}
__device__ __forceinline__ void spread(uint32_t (&b)[10], uint32_t x01, uint32_t x2, uint32_t wa, uint32_t ra, bool e2) {
    sts16(wa, x01); sts16(wa + 8, x01 >> 16);
    sts16_if(!e2, wa + 16, x2);
    __syncwarp();
    const uint4 u = lds128(ra), v = lds128(ra + 16);
    const uint2 z = lds64(ra + 32);
    b[0] = u.x; b[1] = u.y; b[2] = u.z; b[3] = u.w; b[4] = v.x; b[5] = v.y; b[6] = v.z; b[7] = v.w; b[8] = z.x; b[9] = z.y;
}
__device__ __forceinline__ float fold(float a, float b, bool sel, int m) { return (sel ? b : a) + shx(sel ? a : b, m); }

__device__ __forceinline__ void chain_role(const Params& p, int w, int lane, uint32_t t0) {
    const int cta = blockIdx.x, h = cta >> 2, s = cta & 3;
    const int g = lane >> 2, t4 = lane & 3;
    const bool e1 = t4 & 1, e2 = t4 & 2;
    uint32_t wq[5][3][4], wo[3][5][4], wg[5][4], wh[5][2], wd[4][4];
    const int col0 = 80 * w + (e2 ? 48 : 0) + g + (e1 ? 8 : 0);
    const uint32_t xw = opaque(SM_X + w * 384 + 48 * (g >> 1) + (e2 ? 24 : 0) + (e1 ? 4 : 0) + 2 * (g & 1));
    const uint32_t xr = opaque(g == 1 ? SM_ONES : SM_X + w * 384 + (g == 3 ? 192 : 0) + 48 * t4);
    TRACES(75);
    sts32_if(lane < 12, SM_ONES + lane * 4, 0x3f803f80u);
    uint32_t zero = lane >> 5;
    const int mi = lane >> 3, mr = lane & 7;
    mbar_wait(bar_at(B_W), 0);
    TRACES(74);
    sts16(xw + 192, lds16(ST_X + 5120 + col0 * 2)); sts16(xw + 200, lds16(ST_X + 5120 + col0 * 2 + 32));
    sts16_if(!e2, xw + 208, lds16(ST_X + 5120 + col0 * 2 + 64));
#pragma unroll
    for (int i = 0; i < 5; i++)
#pragma unroll
        for (int mt = 0; mt < 3; mt++) ldsm4t(wq[i][mt], ST_WQ + (80 * w + 16 * i + mr + 8 * (mi >> 1)) * 96 + 32 * mt + 16 * (mi & 1), zero);
    const bool odd = cta & 1;
    const uint32_t lo = ST_WD + (mr + (odd ? 4 : 0)) * 1280 + 160 * w, hi = ST_WD + ((mr & 3) + (odd ? 0 : 8)) * 1280 + 160 * w;
    ldsm4t(wd[0], lo + 16 * mi, zero);
    ldsm4t(wd[1], lo + 64 + 16 * mi, zero);
    ldsm4t(wd[2], hi + 64 * (mi >> 1) + 32 * (mr >> 2) + 16 * (mi & 1), zero);
    ldsm4t(wd[3], (mi < 2 ? lo : hi) + 128 + 16 * (mi & 1), zero);
    fence_async();
    __syncwarp();
    mbar_arrive_if(lane == 0, bar_at(B_WC));
    mbar_wait(bar_at(B_EP), 0);
    uint32_t x01 = 0, x2 = 0;
#pragma unroll 1
    for (int n = -5; n < NROUND; n++) {
        const bool last = (ORD_LAST >> (n & 15)) & 1, head = !((ORD_NO_HEAD >> (n & 15)) & 1);
        const int k = (ORD_BATCH >> (2 * (n & 15))) & 3;
        if (!last) bar_sync<2, 256>();
        TRACES(n <= 0 ? 83 + n : 95);
        const char* const slice = reinterpret_cast<const char*>(g_acc) + k * ACC_SET + (last ? 128 : 0) + w * 2048;
        const char* const cell = opaque(slice + g * 256 + t4 * 16);
        const char* const watch = slice + (cta & 7) * 256 + ((cta >> 3) & 3) * 16;
        if (n >= 0) {
          uint4 v;
          if (head) {
            if (!last || n == NROUND - 1) mbar_wait(bar_at(B_Z), (k + last) & 1);
            const uint4* src = &g_o[last][h][w & 6][g & 3][t4];
            const uint32_t tag = lds32(SM_EPOCH) * NB + k;
            mbar_wait(bar_at(last ? B_RV : B_PS), k & 1);
            wait_clk(clk32() + CFG_DLY_P);
            if (CFG_START && !last && k < NB - 1) wait_ns(t0 + tile_ns(16 * k + 15) + CFG_START);
            uint4 z;
            {
                SPIN_DECL;
                while (true) {
                    v = ld_pkt(src); z = ld_pkt(src + 16);
                    if (__all_sync(0xffffffffu, (((v.w ^ tag) | (z.w ^ tag)) & 0xffu) == 0)) break;
                    SPIN_CHECK(n);
                }
            }
            TRACES(tr + 0);
            float a[3][4] = {};
            const uint32_t bb[3][2] = {{v.x, v.y}, {z.x, z.y}, {v.z, z.z}};
            float sa, sb;
#pragma unroll
            for (int i = 0; i < 3; i++) {
                const uint32_t l0 = g < 4 ? bb[i][0] : 0, l1 = g < 4 ? bb[i][1] : 0, h0 = g < 4 ? 0 : bb[i][0], h1 = g < 4 ? 0 : bb[i][1];
#pragma unroll
                for (int mt = 0; mt < 5; mt++)
                    mma16816(a[mt % 3], wo[i][mt][0], wo[i][mt][1], wo[i][mt][2], wo[i][mt][3], mt < 3 ? l0 : h0, mt < 3 ? l1 : h1);
                if (i == 0) {
                    const float am = F(v.w & 0xffffff00u), al = F(z.w & 0xffffff00u);
                    const float m0 = shi(am, 0), m1 = shi(am, 4), m2 = shi(am, 8), m3 = shi(am, 12);
                    const float s0 = shi(al, 0), s1 = shi(al, 4), s2 = shi(al, 8), s3 = shi(al, 12);
                    const float mb = fmaxf(fmaxf(m0, m1), fmaxf(m2, m3)) * LOG2E;
                    const float w0 = fast_ex2(fmaf(m0, LOG2E, -mb)), w1 = fast_ex2(fmaf(m1, LOG2E, -mb));
                    const float w2 = fast_ex2(fmaf(m2, LOG2E, -mb)), w3 = fast_ex2(fmaf(m3, LOG2E, -mb));
                    const float rl = fast_rcp(fmaf(w0, s0, w1 * s1) + fmaf(w2, s2, w3 * s3));
                    sa = (e1 ? w2 : w0) * rl; sb = (e1 ? w3 : w1) * rl;
                }
            }
            float y[3];
#pragma unroll
            for (int j = 2; j < 5; j++) {
                const int mt = j % 3;
                y[mt] = fold(fmaf(a[mt][0], sa, a[mt][1] * sb), fmaf(a[mt][2], sa, a[mt][3] * sb), e1, 1);
            }
            const uint32_t pa = SM_PO + w * 512 + lane * 16;
            if (w < 2) {
                const char* dst = opaque(cell + s * 4096);
                bar_sync<1, 256>();
                const uint4 c1 = lds128(pa), c2 = lds128(pa + 1024), c3 = lds128(pa + 2048);
                red_cell(dst, (y[0] + F(c1.x)) + (F(c2.x) + F(c3.x)), (y[1] + F(c1.y)) + (F(c2.y) + F(c3.y)), (y[2] + F(c1.z)) + (F(c2.z) + F(c3.z)));
            } else {
                stsf4(pa - 1024, y[0], y[1], y[2], 0.f);
                bar_sync<1, 256>();
            }
            TRACES(tr + 1);
            if ((ORD_NO_TAIL >> n) & 1) continue;
            wait_clk(clk32() + (w < 2 ? 0 : 60) + (n < CFG_TIMED ? CFG_DLY_AL : CFG_DLY_A));
          }
            {
                SPIN_DECL;
                if (n < CFG_TIMED && head) while (__any_sync(0xffffffffu, cell_count(watch) != FULL_A)) SPIN_CHECK(n);
                while (true) {
                    v = ld_pkt(cell);
                    if (__all_sync(0xffffffffu, v.w == FULL_A)) break;
                    SPIN_CHECK(n);
                }
            }
            TRACES(tr + 2);
            x01 = pack2(F(v.x), F(v.y));
            x2 = pack2(F(v.z), 0.f);
        } else if (n == -1) {
            mbar_wait(bar_at(B_W + 1), 0);
            const uint32_t ln = opaque(lane);
            const int mi = ln >> 3, mr = ln & 7;
            uint32_t zero = ln >> 5;
            TRACES(76);
#pragma unroll
            for (int i = 0; i < 3; i++) {
                const int d = 16 * (w >> 1) + (mr >> 1) + 8 * (mr & 1) + (i < 2 ? 64 * (mi >> 1) + 4 * i : 128 + 4 * (mi >> 1));
#pragma unroll
                for (int mt = 0; mt < 5; mt++) ldsm4t(wo[i][mt], ST_WO + d * 320 + 160 * (w & 1) + 32 * mt + 16 * (mi & 1), zero);
            }
            fence_async();
            __syncwarp();
            mbar_arrive_if(lane == 0, bar_at(B_WC + 1));
            mbar_wait(bar_at(B_W + 2), 0);
            TRACES(77);
#pragma unroll
            for (int i = 0; i < 5; i++) {
                const uint32_t ga = ST_WG + (mi & 1) * 20480 + (80 * w + 16 * i + mr + 8 * (mi >> 1)) * 32;
                uint32_t r[4];
                ldsm4t(wg[i], ga + (odd ? 16 : 0), zero);
                ldsm4t(r, ga + (odd ? 0 : 16), zero);
#pragma unroll
                for (int kh = 0; kh < 2; kh++) {
                    const uint32_t moved = __shfl_xor_sync(0xffffffffu, odd ? r[2 * kh] : r[2 * kh + 1], 16);
                    wh[i][kh] = (g < 4) == odd ? moved : odd ? r[2 * kh + 1] : r[2 * kh];
                }
            }
            fence_async();
            __syncwarp();
            mbar_arrive_if(lane == 0, bar_at(B_WC + 2));
            TRACES(72);
            x01 = 0x3f803f80u; x2 = 0x3f80u;
        } else {
            const uint32_t xa = ST_X + (n + 5) * 1280, ln = opaque(lane);
            const int col0 = 80 * w + (ln & 2 ? 48 : 0) + (ln >> 2) + (ln & 1 ? 8 : 0);
            float sm = 0.f, sq = 0.f;
#pragma unroll
            for (int i = 0; i < 5; i++) {
                const uint2 c = lds64(xa + i * 256 + ln * 8);
                sm += (bf_lo(c.x) + bf_hi(c.x)) + (bf_lo(c.y) + bf_hi(c.y));
                sq = fmaf(bf_lo(c.x), bf_lo(c.x), fmaf(bf_hi(c.x), bf_hi(c.x), fmaf(bf_lo(c.y), bf_lo(c.y), fmaf(bf_hi(c.y), bf_hi(c.y), sq))));
            }
            x01 = lds16(xa + col0 * 2) | lds16(xa + col0 * 2 + 32) << 16;
            x2 = lds16(xa + col0 * 2 + 64);
#pragma unroll
            for (int o = 16; o; o >>= 1) { sm += shx(sm, o); sq += shx(sq, o); }
            float mean_b, rden;
            ln_finish(sm, sq, mean_b, rden);
            x01 = ln_apply(x01, mean_b, rden);
            x2 = ln_apply(x2, mean_b, rden);
        }
        if (n >= -1) {
            uint32_t b[10];
            spread(b, x01, x2, xw, xr, e2);
            float a[2][4] = {};
#pragma unroll
            for (int i = 0; i < 5; i++) {
                mma16816(a[0], wg[i][0], wg[i][1], wg[i][2], wg[i][3], b[2 * i], b[2 * i + 1]);
                mma16816(a[1], wh[i][0], b[2 * i], wh[i][1], b[2 * i + 1], b[2 * i], b[2 * i + 1]);
            }
            stsf(SM_PG + (w >> 2) * 512 + (g + 8 * t4) * 16 + (w & 3) * 4, e2 ? (e1 ? a[1][2] : a[1][0]) : (e1 ? a[0][2] : a[0][0]));
            const uint2 cs = lds64(SM_CSG + lane * 48);
            const char* dst = opaque(cell + (1 + (cta & 1)) * ACC_TYPE);
            bar_sync<2, 256>();
            const float S = sum8(lds128(SM_PG + lane * 16), lds128(SM_PG + 512 + lane * 16));
            const float sx = shi(S, 25), sq = shi(S, 24), Su = shi(S, lane + (lane < 16 ? 8 : 4));
            if (n < 0) {
                if (w == 0) stsf2(SM_CSG + lane * 48, S, Su);
            } else {
                float mean_b, rden;
                ln_fast(sx, sq, mean_b, rden);
                const float gv = bfr(fmaf(-mean_b, F(cs.x), S) * rden), uv = bfr(fmaf(-mean_b, F(cs.y), Su) * rden);
                const float sg = fast_rcp(1.f + fast_ex2(-LOG2E * gv));
                const uint32_t hb = pack2(bfr(gv * sg) * uv, 0.f);
                const uint32_t b0 = __byte_perm(shi(hb, 2 * t4), shi(hb, 2 * t4 + 1), 0x5410);
                const uint32_t b1 = __byte_perm(shi(hb, e1 ? 18 : 16), shi(hb, e1 ? 19 : 17), 0x5410);
                const bool up = g >= 4;
                const uint32_t l0 = up ? 0 : b0, h0 = up ? b0 : 0;
                float d[3][4] = {};
                mma1688(d[0], wd[0][0], wd[0][1], l0); mma1688(d[1], wd[0][2], wd[0][3], l0); mma1688(d[2], wd[1][0], wd[1][1], l0);
                mma1688(d[0], wd[1][2], wd[1][3], h0); mma1688(d[1], wd[3][0], wd[3][1], h0);
                mma1688(d[2], wd[2][2], wd[2][3], up || e2 ? 0 : b1); mma1688(d[0], wd[2][0], wd[2][1], up || e2 ? 0 : b1);
                mma1688(d[1], wd[2][0], wd[2][1], !up && e2 ? b1 : 0);
                mma1688(d[0], wd[2][2], wd[2][3], up && e2 ? b1 : 0); mma1688(d[1], wd[3][2], wd[3][3], up && !e2 ? b1 : 0);
                red_cell(dst, e1 ? d[0][2] : d[0][0], e1 ? d[1][2] : d[1][0], e1 ? d[2][2] : d[2][0]);
                const uint32_t tsend = clk32();
                TRACES(tr + 3);
                if (last && w != cta >> 4) continue;
                if (!last && w == 0) st_pkt8_if(lane < 24, &g_q[4][h][24 * s + lane], 0, 0);
                const float sgr = shi(sg, 27);
                const uint32_t sg2 = pack2(sgr, sgr);
                const uint32_t n01 = opaque(pack2((bf_lo(x01) - mean_b) * rden, (bf_hi(x01) - mean_b) * rden));
                const uint32_t n2 = opaque(pack2((bf_lo(x2) - mean_b) * rden, 0.f));
                if (last) {
                    sts128_if(lane >> 1 == (cta & 15), SM_FIN + (lane & 1) * 16, x01, n01, __byte_perm(x2, n2, 0x5410), sg2);
                    mbar_arrive_if(lane >> 1 == (cta & 15), bar_at(B_FIN));
                    __syncwarp();
                    continue;
                }
                prefetch_if(n > 0 && w * 16 + (lane >> 1) == cta, cell + 128 - (int)ACC_SET);
                wait_clk(tsend + (n < CFG_TIMED ? CFG_DLY_BL : CFG_DLY_B));
                uint4 v, z;
                {
                    SPIN_DECL;
                    if (n < CFG_TIMED)
                        while (__any_sync(0xffffffffu, cell_count(watch + (e1 ? 2 : 1) * ACC_TYPE) != FULL_B)) SPIN_CHECK(n);
                    while (true) {
                        v = ld_pkt(cell + ACC_TYPE); z = ld_pkt(cell + 2 * ACC_TYPE);
                        if (__all_sync(0xffffffffu, v.w == FULL_B && z.w == FULL_B)) break;
                        SPIN_CHECK(n);
                    }
                }
                x01 = badd2(x01, badd2(n01, bmul2(pack2(F(v.x) + F(z.x), F(v.y) + F(z.y)), sg2)));
                x2 = badd2(x2, badd2(n2, bmul2(pack2(F(v.z) + F(z.z), 0.f), sg2)));
                TRACES(tr + 4);
            }
        }
        {
            uint32_t b[10];
            spread(b, x01, x2, xw, xr, e2);
            float a[3][4] = {};
            const float f0 = bf_lo(x01), f1 = bf_hi(x01), f2 = e2 ? 0.f : bf_lo(x2);
            float st = fold(fmaf(f0, f0, fmaf(f1, f1, f2 * f2)), (f0 + f1) + f2, e1, 1);
#pragma unroll
            for (int i = 0; i < 5; i++) {
#pragma unroll
                for (int mt = 0; mt < 3; mt++) mma16816(a[mt], wq[i][mt][0], wq[i][mt][1], wq[i][mt][2], wq[i][mt][3], b[2 * i], b[2 * i + 1]);
                if (i < 4) st += shx(st, 2 << i);
            }
            const uint32_t pa = SM_PQ + (w >> 2) * 1024 + ((e2 ? 32 : 0) + (e1 ? 8 : 0) + g) * 16 + (w & 3) * 4;
            stsf(pa + 256, e2 ? st : e1 ? a[1][2] : a[1][0]);
            stsf(pa, e2 ? (e1 ? a[2][2] : a[2][0]) : (e1 ? a[0][2] : a[0][0]));
            if (w == 0) {
                const uint2 cs = lds64(SM_CSQ + lane * 48);
                const uint32_t qtag = lds32(SM_EPOCH) * NB + (n < 0 ? n + 5 : k);
                const char* dst = opaque(reinterpret_cast<const char*>(&g_q[n < 0 ? n + 5 : 4][h][24 * s + lane]));
                bar_sync<3, 256>();
                const uint32_t ra = SM_PQ + lane * 32;
                float S0 = sum8(lds128(ra), lds128(ra + 1024)), S1 = sum8(lds128(ra + 16), lds128(ra + 1040));
                if (n >= 0) {
                    float mean_b, rden;
                    ln_fast(shi(S0, 28), shi(S0, 24), mean_b, rden);
                    S0 = fmaf(-mean_b, F(cs.x), S0) * rden;
                    S1 = fmaf(-mean_b, F(cs.y), S1) * rden;
                }
                if (n == -1) stsf2(SM_CSQ + lane * 48, S0, S1);
                st_pkt8_if(lane < 24 && n != -1, dst, pack2(S0, S1), qtag);
                mbar_arrive_if(lane == 0 && (n == -2 || n >= 0), bar_at(B_QS));
                TRACES(n >= 0 ? tr + 5 : 95);
            } else bar_arrive<3, 256>();
            red_cell_if(n >= 0 && w * 16 + (lane >> 1) == cta, cell + 128, f0, f1, f2);
            __syncwarp();
        }
    }
}

template <int ID> __device__ __forceinline__ void role_exit() { asm volatile("exit; // %0" ::"n"(ID)); }
constexpr int NTHREADS = 512;
#define STR2(x) #x
#define STR(x) STR2(x)
__global__ void __launch_bounds__(NTHREADS, 1)
decode_kernel(const __grid_constant__ CUtensorMap tmK, const __grid_constant__ CUtensorMap tmV,
              const __grid_constant__ WeightMaps tmW, const Params p) {
    extern __shared__ __align__(1024) unsigned char smem[];
    const uint32_t t0 = now_ns();
    const int lane = threadIdx.x & 31;
    const int warp = __shfl_sync(0xffffffffu, threadIdx.x >> 5, 0);
    if (warp < 8) {
        asm volatile("setmaxnreg.inc.sync.aligned.u32 " STR(CFG_REG_CHAIN) ";");
        bar_sync<5, 480>();
        chain_role(p, warp, __shfl_sync(0xffffffffu, lane, lane), t0);
        role_exit<3>();
    } else if (warp < 12) {
        asm volatile("setmaxnreg.dec.sync.aligned.u32 " STR(CFG_REG_ATT) ";");
        if (elect_one()) {
#pragma unroll 1
            for (int i = warp - 8; i < NBAR; i += 4)
                if (i < B_W || i >= B_WC) mbar_init(bar_at(i), i == B_FIN ? 2 : i == B_PS || i == B_RP ? 4 : i >= B_F3 ? 1 : i >= B_WC ? 8 : i < B_RR || i > B_RV ? 1 : i < B_RK ? 2 : 4);
            asm volatile("fence.mbarrier_init.release.cluster;" ::: "memory");
            fence_async();
        }
        bar_sync<5, 480>();
        attention_role(p, warp - 8, lane);
        role_exit<2>();
    } else {
        asm volatile("setmaxnreg.dec.sync.aligned.u32 " STR(CFG_REG_HELP) ";");
        if (warp == 12) {
            TRACE(0);
            prefetch_role(p, &tmV, t0);
            role_exit<0>();
        } else {
            if (warp == 14) {
                if (smem_u32(smem) != SB) __trap();
                if (elect_one()) {
                    asm volatile("prefetch.tensormap [%0];" ::"l"(&tmW.q) : "memory");
                    mbar_init(bar_at(B_W), 1); mbar_init(bar_at(B_W + 1), 1); mbar_init(bar_at(B_W + 2), 1);
                    asm volatile("fence.mbarrier_init.release.cluster;" ::: "memory");
                    fence_async();
                    mbar_expect_tx(bar_at(B_W), 61440 + 15360 + 6400); mbar_expect_tx(bar_at(B_W + 1), 61440); mbar_expect_tx(bar_at(B_W + 2), 40960);
                    bulk_load(ST_X, p.x, 5120, bar_at(B_W));
                    bulk_load(ST_X + 5120, p.wr, 1280, bar_at(B_W));
                }
                reload_role(p, &tmK, &tmV, &tmW, t0);
            } else {
                unsigned ticket = 0;
                if (warp == 15 && lane == 0) asm volatile("atom.relaxed.gpu.global.add.u32 %0, [%1], 1;" : "=r"(ticket) : "l"(&g_epoch) : "memory");
                if (warp == 13 && elect_one()) {
                    asm volatile("prefetch.tensormap [%0];" ::"l"(&tmW.g) : "memory");
                    asm volatile("prefetch.tensormap [%0];" ::"l"(&tmW.u) : "memory");
                    asm volatile("prefetch.tensormap [%0];" ::"l"(&tmW.o) : "memory");
                    asm volatile("prefetch.tensormap [%0];" ::"l"(&tmK) : "memory");
                    asm volatile("prefetch.tensormap [%0];" ::"l"(&tmV) : "memory");
                }
                bar_sync<5, 480>();
                if (warp == 13) { sts32(SM_PROG, 0); bar_arrive<6, 64>(); load_role(p, &tmK, &tmV, t0); }
                else zero_role(p, lane, ticket, t0);
            }
            role_exit<1>();
        }
    }
}

typedef CUresult (*EncodeFn)(CUtensorMap*, CUtensorMapDataType, cuuint32_t, void*, const cuuint64_t*, const cuuint64_t*,
                             const cuuint32_t*, const cuuint32_t*, CUtensorMapInterleave, CUtensorMapSwizzle,
                             CUtensorMapL2promotion, CUtensorMapFloatOOBfill);

bool make_map(EncodeFn fn, CUtensorMap* m, const void* ptr, uint64_t cols, uint64_t rows, uint32_t bc, uint32_t br) {
    cuuint64_t dims[2] = {cols, rows};
    cuuint64_t strides[1] = {cols * 2};
    cuuint32_t box[2] = {bc, br};
    cuuint32_t es[2] = {1, 1};
    return fn(m, CU_TENSOR_MAP_DATA_TYPE_BFLOAT16, 2, const_cast<void*>(ptr), dims, strides, box, es, CU_TENSOR_MAP_INTERLEAVE_NONE,
              CU_TENSOR_MAP_SWIZZLE_NONE, CU_TENSOR_MAP_L2_PROMOTION_L2_128B, CU_TENSOR_MAP_FLOAT_OOB_FILL_NONE) == CUDA_SUCCESS;
}

bool make_kv_map(EncodeFn fn, CUtensorMap* m, const void* ptr) {
    cuuint64_t dims[4] = {64, 8, 3, (cuuint64_t)NB * NHEAD * SK / 8};
    cuuint64_t strides[3] = {DH * 2, 128, 8 * DH * 2};
    cuuint32_t box[4] = {64, 8, 3, 4};
    cuuint32_t es[4] = {1, 1, 1, 1};
    return fn(m, CU_TENSOR_MAP_DATA_TYPE_BFLOAT16, 4, const_cast<void*>(ptr), dims, strides, box, es, CU_TENSOR_MAP_INTERLEAVE_NONE,
              CU_TENSOR_MAP_SWIZZLE_128B, CU_TENSOR_MAP_L2_PROMOTION_L2_128B, CU_TENSOR_MAP_FLOAT_OOB_FILL_NONE) == CUDA_SUCCESS;
}

}

extern "C" void kernel_launch(void* const* d_in, const int* in_sizes, int n_in, void* d_out, int out_size) {
    (void)in_sizes; (void)n_in; (void)out_size;
    static EncodeFn fn = nullptr;
    if (!fn) {
        void* f = nullptr;
        cudaDriverEntryPointQueryResult qr;
        if (cudaGetDriverEntryPoint("cuTensorMapEncodeTiled", &f, cudaEnableDefault, &qr) != cudaSuccess || !f) return;
        fn = (EncodeFn)f;
        cudaFuncSetAttribute(decode_kernel, cudaFuncAttributeMaxDynamicSharedMemorySize, SMEM_BYTES);
    }
    CUtensorMap tmK, tmV;
    WeightMaps tmW;
    if (!make_kv_map(fn, &tmK, d_in[1]) || !make_kv_map(fn, &tmV, d_in[2])) return;
    if (!make_map(fn, &tmW.q, d_in[3], NHEAD * DH, DM, 48, 128) || !make_map(fn, &tmW.o, d_in[4], DM, NHEAD * DH, 160, 32)) return;
    if (!make_map(fn, &tmW.g, d_in[7], FF, DM, 16, 128) || !make_map(fn, &tmW.u, d_in[8], FF, DM, 16, 128)) return;
    Params p;
    p.x = (const unsigned short*)d_in[0];
    p.kc = (const char*)d_in[1];
    p.vc = (const char*)d_in[2];
    p.wq = (const char*)d_in[3];
    p.wo = (const char*)d_in[4];
    p.wr = (const unsigned short*)d_in[6];
    p.wg = (const char*)d_in[7];
    p.wu = (const char*)d_in[8];
    p.wd = (const char*)d_in[9];
    p.out = (unsigned short*)d_out;
    decode_kernel<<<NCTA, NTHREADS, SMEM_BYTES>>>(tmK, tmV, tmW, p);
}
```

```cpp
#include <cuda_runtime.h>
#include <cuda_bf16.h>
#include <cuda.h>
#include <stdint.h>

namespace {

constexpr int NB = 4, DM = 640, NHEAD = 32, DH = 192, SK = 4096, WIN = 1024, FF = 1536;
constexpr int NCTA = 128;
constexpr int TILE = 12288, PAIR = 2 * TILE;

#define CFG_TICK0 488
#define CFG_TICK 525
#define CFG_WLAG 300
#define CFG_GSTEP 700
#define CFG_PFB 3072
#define CFG_VSTEP 350
#define CFG_START 1
#define CFG_TIMED 8
#define CFG_WIN2 2
#define CFG_WIN 3
#define CFG_RSTEP 620
#define CFG_RLAG 0
#define CFG_RSTEP3 450
#define CFG_DLY_A 400
#define CFG_DLY_B 800
#define CFG_DLY_AL 100
#define CFG_DLY_BL 1300
#define CFG_DLY_P 100
#define CFG_DLY_Q 100
#define CFG_QKWAIT 1
#define CFG_SENT 1
#define CFG_ZTILE 6
#define CFG_DLY_F 300
#define CFG_LMAX 100
#define CFG_REG_CHAIN 216
#define CFG_REG_ATT 48
#define CFG_REG_HELP 32
constexpr int KB_KV0 = 165;
__host__ __device__ constexpr int kb_ns(int kb) { return kb * CFG_TICK0 / 12; }
constexpr int PF_NS = CFG_TICK0 * CFG_PFB / TILE;
__host__ __device__ constexpr int tile_ns(int j) {
    return kb_ns(KB_KV0) + 2 * PF_NS + j * CFG_TICK0 + (j > 16 ? (j - 16) * (CFG_TICK - CFG_TICK0) : 0) - (j == 63 ? PF_NS : 0);
}

__device__ __forceinline__ uint32_t slots(int k) { return k & 2 ? (k & 1 ? 0x04321658u : 0x65837104u) : (k & 1 ? 0x10482765u : 0x76543210u); }
__device__ __forceinline__ int pass_nibble(int k, int u) { return k > 0 ? 4 + (u & 1) : u; }
__device__ __forceinline__ uint32_t slot_at(uint32_t tab, int u) { return (tab >> (4 * u)) & 15; }

constexpr int NROUND = 11;
constexpr uint32_t ORD_BATCH = 0x3b9910, ORD_LAST = 0x6da, ORD_NO_HEAD = 0x248, ORD_NO_TAIL = 0x092;

constexpr uint32_t SB = 1024;
constexpr uint32_t SM_BAR = SB + 9 * PAIR;
constexpr int B_F1 = 0;
constexpr int B_RR = 24;
constexpr int B_RK = 32;
constexpr int B_RV = 36;
constexpr int B_Z = 37;
constexpr int B_EP = 38;
constexpr int B_W = 39;
constexpr int B_WC = 42;
constexpr int B_FIN = 45;
constexpr int B_F3 = 46;
constexpr int B_QS = 47;
constexpr int B_PS = 48;
constexpr int B_RP = 49;
constexpr int B_FL = 50;
constexpr int NBAR = 51;
__host__ __device__ constexpr uint32_t bar_at(int i) { return SM_BAR + 8 * i; }
constexpr uint32_t SM_EPOCH = SM_BAR + 416;
constexpr uint32_t SM_PROG = SM_EPOCH + 4;
constexpr uint32_t SM_MAX = SM_EPOCH + 16;
constexpr uint32_t SM_FIN = SM_MAX + 16;
constexpr uint32_t SM_Q = SM_FIN + 32;
constexpr uint32_t PSTR = 144;
constexpr uint32_t SM_P = SM_Q + 5 * 384;
constexpr uint32_t SM_X = SM_P + 8 * PSTR;
constexpr uint32_t SM_CSG = SM_X + 40;
constexpr uint32_t SM_CSQ = SM_CSG + 32 * 48;
constexpr uint32_t SM_ONES = SM_X + 8 * 384;
constexpr uint32_t SM_PG = SM_ONES + 48;
constexpr uint32_t SM_PO = SM_PG + 1024;
constexpr uint32_t SM_PQ = SM_PO;
constexpr int SMEM_BYTES = SM_PO + 3072 - SB;
static_assert(SMEM_BYTES <= 232448 && SM_Q % 16 == 0 && SM_P % 16 == 0 && SM_X % 16 == 0 && SM_PO % 16 == 0, "smem");
constexpr uint32_t ST_WQ = SB, ST_WD = SB + 3 * PAIR, ST_WO = SB + 4 * PAIR, ST_WG = SB + 7 * PAIR, ST_X = ST_WG + 40960;

__device__ unsigned g_epoch;
__device__ unsigned g_init;
__device__ uint2 g_q[5][NHEAD][96];
__device__ uint4 g_o[2][NHEAD][8][4][4];
__device__ float4 g_acc[NB][3][64][2][8];
constexpr uint32_t ACC_TYPE = 64 * 256, ACC_SET = 3 * ACC_TYPE;
constexpr uint32_t FULL_A = 0x42040000u, FULL_B = 0x42800000u;

struct Params {
    const unsigned short* x;
    const char* kc;
    const char* vc;
    const char* wq;
    const char* wo;
    const unsigned short* wr;
    const char* wg;
    const char* wu;
    const char* wd;
    unsigned short* out;
};

__device__ __forceinline__ uint32_t smem_u32(const void* p) { return (uint32_t)__cvta_generic_to_shared(p); }
__device__ __forceinline__ void mbar_init(uint32_t a, uint32_t c) { asm volatile("mbarrier.init.shared::cta.b64 [%0], %1;" ::"r"(a), "r"(c) : "memory"); }
__device__ __forceinline__ void mbar_expect_tx(uint32_t a, uint32_t b) {
    asm volatile("mbarrier.arrive.expect_tx.shared::cta.b64 _, [%0], %1;" ::"r"(a), "r"(b) : "memory");
}
__device__ __forceinline__ void mbar_arrive(uint32_t a) { asm volatile("mbarrier.arrive.shared::cta.b64 _, [%0];" ::"r"(a) : "memory"); }
constexpr uint32_t SPIN_LIMIT = 1u << 22;
#define SPIN_DECL uint32_t spins = 0
#define SPIN_CHECK(info) { if (++spins > SPIN_LIMIT) __trap(); }
__device__ __forceinline__ void mbar_wait(uint32_t a, uint32_t parity) {
    uint32_t ok;
    SPIN_DECL;
    while (true) {
        asm volatile("{\n.reg .pred p;\nmbarrier.try_wait.parity.shared::cta.b64 p, [%1], %2;\nselp.u32 %0, 1, 0, p;\n}"
                     : "=r"(ok) : "r"(a), "r"(parity) : "memory");
        if (ok) break;
        SPIN_CHECK((a - SM_BAR) / 8 * 10 + parity);
    }
}
__device__ __forceinline__ uint32_t now_ns() { uint32_t t; asm volatile("mov.u32 %0, %%globaltimer_lo;" : "=r"(t) :: "memory"); return t; }
__device__ __forceinline__ uint32_t clk32() { uint32_t c; asm volatile("mov.u32 %0, %%clock;" : "=r"(c) :: "memory"); return c; }
__device__ __forceinline__ void wait_ns(uint32_t t) { while ((int)(now_ns() - t) < 0) {} }
__device__ __forceinline__ void wait_clk(uint32_t t) { while ((int)(clk32() - t) < 0) {} }
__device__ __forceinline__ bool elect_one() {
    uint32_t e;
    asm volatile("{\n.reg .pred p;\nelect.sync _|p, 0xffffffff;\nselp.u32 %0, 1, 0, p;\n}" : "=r"(e));
    return e;
}
constexpr uint64_t POL_FIRST = 0x12F0000000000000ull, POL_NORMAL = 0x1000000000000000ull;
__device__ __forceinline__ void tma_tile(uint32_t dst, const CUtensorMap* tm, int group, uint32_t bar, uint64_t pol) {
    asm volatile("cp.async.bulk.tensor.4d.shared::cluster.global.mbarrier::complete_tx::bytes.L2::cache_hint"
                 " [%0], [%1, {%3, %3, %3, %4}], [%2], %5;"
                 ::"r"(dst), "l"(tm), "r"(bar), "r"(0), "r"(group), "l"(pol) : "memory");
}
__device__ __forceinline__ void tma2d(uint32_t dst, const CUtensorMap* tm, int x, int y, uint32_t bar) {
    asm volatile("cp.async.bulk.tensor.2d.shared::cluster.global.mbarrier::complete_tx::bytes [%0], [%1, {%3, %4}], [%2];"
                 ::"r"(dst), "l"(tm), "r"(bar), "r"(x), "r"(y) : "memory");
}
__device__ __forceinline__ void bulk_load(uint32_t dst, const void* src, uint32_t bytes, uint32_t bar) {
    asm volatile("cp.async.bulk.shared::cluster.global.mbarrier::complete_tx::bytes [%0], [%1], %2, [%3];"
                 ::"r"(dst), "l"(src), "r"(bytes), "r"(bar) : "memory");
}
__device__ __forceinline__ void l2_prefetch(const void* p, uint32_t bytes) {
    asm volatile("cp.async.bulk.prefetch.L2.global [%0], %1;" ::"l"(p), "r"(bytes) : "memory");
}
__device__ __forceinline__ void mma16816(float (&c)[4], uint32_t a0, uint32_t a1, uint32_t a2, uint32_t a3, uint32_t b0, uint32_t b1) {
    asm volatile("mma.sync.aligned.m16n8k16.row.col.f32.bf16.bf16.f32 {%0,%1,%2,%3}, {%4,%5,%6,%7}, {%8,%9}, {%0,%1,%2,%3};"
                 : "+f"(c[0]), "+f"(c[1]), "+f"(c[2]), "+f"(c[3]) : "r"(a0), "r"(a1), "r"(a2), "r"(a3), "r"(b0), "r"(b1));
}
__device__ __forceinline__ void mma1688(float (&c)[4], uint32_t a0, uint32_t a1, uint32_t b0) {
    asm volatile("mma.sync.aligned.m16n8k8.row.col.f32.bf16.bf16.f32 {%0,%1,%2,%3}, {%4,%5}, {%6}, {%0,%1,%2,%3};"
                 : "+f"(c[0]), "+f"(c[1]), "+f"(c[2]), "+f"(c[3]) : "r"(a0), "r"(a1), "r"(b0));
}
__device__ __forceinline__ void ldsm4t(uint32_t (&r)[4], uint32_t a, uint32_t& zero) {
    asm volatile("ldmatrix.sync.aligned.m8n8.x4.trans.shared.b16 {%0,%1,%2,%3}, [%4];"
                 : "=r"(r[0]), "=r"(r[1]), "=r"(r[2]), "=r"(r[3]) : "r"(a + zero) : "memory");
    zero &= r[3];
}
__device__ __forceinline__ uint4 ld_pkt(const void* p) {
    uint4 v;
    asm volatile("{\n.reg .b128 t;\nld.relaxed.gpu.global.b128 t, [%4];\nmov.b128 {%0,%1,%2,%3}, t;\n}"
                 : "=r"(v.x), "=r"(v.y), "=r"(v.z), "=r"(v.w) : "l"(p) : "memory");
    return v;
}
__device__ __forceinline__ void st_pkt(const void* p, uint32_t a, uint32_t b, uint32_t c, uint32_t d) {
    asm volatile("{\n.reg .b128 t;\nmov.b128 t, {%1,%2,%3,%4};\nst.relaxed.gpu.global.b128 [%0], t;\n}"
                 ::"l"(p), "r"(a), "r"(b), "r"(c), "r"(d) : "memory");
}
__device__ __forceinline__ uint2 ld_pkt8(const void* p) {
    uint2 v;
    asm volatile("{\n.reg .b64 t;\nld.relaxed.gpu.global.b64 t, [%2];\nmov.b64 {%0,%1}, t;\n}" : "=r"(v.x), "=r"(v.y) : "l"(p) : "memory");
    return v;
}
__device__ __forceinline__ void red_cell(const char* p, float a, float b, float c) {
    asm volatile("red.relaxed.gpu.global.add.v4.f32 [%0], {%1,%2,%3,%4};" ::"l"(p), "f"(a), "f"(b), "f"(c), "f"(1.0f) : "memory");
}
__device__ __forceinline__ uint32_t cell_count(const char* p) {
    uint32_t c;
    asm volatile("ld.relaxed.gpu.global.u32 %0, [%1+12];" : "=r"(c) : "l"(p) : "memory");
    return c;
}
#define PRED(n) "{\n.reg .pred p;\nsetp.ne.u32 p, %" #n ", 0;\n"
__device__ __forceinline__ void red_cell_if(bool on, const char* p, float a, float b, float c) {
    asm volatile(PRED(5) "@p red.relaxed.gpu.global.add.v4.f32 [%0], {%1,%2,%3,%4};\n}"
                 ::"l"(p), "f"(a), "f"(b), "f"(c), "f"(1.0f), "r"((uint32_t)on) : "memory");
}
__device__ __forceinline__ void st_pkt8_if(bool on, const void* p, uint32_t a, uint32_t b) {
    asm volatile(PRED(3) ".reg .b64 t;\nmov.b64 t, {%1,%2};\n@p st.relaxed.gpu.global.b64 [%0], t;\n}" ::"l"(p), "r"(a), "r"(b), "r"((uint32_t)on) : "memory");
}
__device__ __forceinline__ void st_pkt_if(bool on, const void* p, uint32_t a, uint32_t b, uint32_t c, uint32_t d) {
    asm volatile(PRED(5) ".reg .b128 t;\nmov.b128 t, {%1,%2,%3,%4};\n@p st.relaxed.gpu.global.b128 [%0], t;\n}"
                 ::"l"(p), "r"(a), "r"(b), "r"(c), "r"(d), "r"((uint32_t)on) : "memory");
}
__device__ __forceinline__ void mbar_arrive_if(bool on, uint32_t a) {
    asm volatile(PRED(1) "@p mbarrier.arrive.shared::cta.b64 _, [%0];\n}" ::"r"(a), "r"((uint32_t)on) : "memory");
}
__device__ __forceinline__ void sts16_if(bool on, uint32_t a, uint32_t v) {
    asm volatile(PRED(2) "@p st.shared.u16 [%0], %1;\n}" ::"r"(a), "h"((unsigned short)v), "r"((uint32_t)on) : "memory");
}
__device__ __forceinline__ void sts32_if(bool on, uint32_t a, uint32_t v) {
    asm volatile(PRED(2) "@p st.shared.u32 [%0], %1;\n}" ::"r"(a), "r"(v), "r"((uint32_t)on) : "memory");
}
__device__ __forceinline__ void sts128_if(bool on, uint32_t a, uint32_t x, uint32_t y, uint32_t z, uint32_t w) {
    asm volatile(PRED(5) "@p st.shared.v4.u32 [%0], {%1,%2,%3,%4};\n}" ::"r"(a), "r"(x), "r"(y), "r"(z), "r"(w), "r"((uint32_t)on) : "memory");
}
__device__ __forceinline__ void prefetch_if(bool on, const void* p) {
    asm volatile(PRED(1) "@p prefetch.global.L2 [%0];\n}" ::"l"(p), "r"((uint32_t)on) : "memory");
}
__device__ __forceinline__ float fast_rcp(float x) { float r; asm("rcp.approx.ftz.f32 %0, %1;" : "=f"(r) : "f"(x)); return r; }
__device__ __forceinline__ float fast_sqrt(float x) { float r; asm("sqrt.approx.ftz.f32 %0, %1;" : "=f"(r) : "f"(x)); return r; }
__device__ __forceinline__ float fast_ex2(float x) { float r; asm("ex2.approx.ftz.f32 %0, %1;" : "=f"(r) : "f"(x)); return r; }
__device__ __forceinline__ uint32_t pack2(float lo, float hi) {
    uint32_t r;
    asm("cvt.rn.bf16x2.f32 %0, %1, %2;" : "=r"(r) : "f"(hi), "f"(lo));
    return r;
}
__device__ __forceinline__ float bfr(float x) { return __uint_as_float(pack2(0.f, x)); }
__device__ __forceinline__ uint32_t badd2(uint32_t a, uint32_t b) { uint32_t r; asm("add.rn.bf16x2 %0, %1, %2;" : "=r"(r) : "r"(a), "r"(b)); return r; }
__device__ __forceinline__ uint32_t bsub2(uint32_t a, uint32_t b) { uint32_t r; asm("sub.rn.bf16x2 %0, %1, %2;" : "=r"(r) : "r"(a), "r"(b)); return r; }
__device__ __forceinline__ uint32_t bmul2(uint32_t a, uint32_t b) { uint32_t r; asm("mul.rn.bf16x2 %0, %1, %2;" : "=r"(r) : "r"(a), "r"(b)); return r; }
__device__ __forceinline__ float bf_lo(uint32_t w) { return __uint_as_float(w << 16); }
__device__ __forceinline__ float bf_hi(uint32_t w) { return __uint_as_float(w & 0xffff0000u); }
__device__ __forceinline__ float F(uint32_t t) { return __uint_as_float(t); }
__device__ __forceinline__ uint32_t lds16(uint32_t a) { unsigned short h; asm volatile("ld.shared.u16 %0, [%1];" : "=h"(h) : "r"(a) : "memory"); return h; }
__device__ __forceinline__ uint32_t lds32(uint32_t a) { uint32_t v; asm volatile("ld.shared.u32 %0, [%1];" : "=r"(v) : "r"(a) : "memory"); return v; }
__device__ __forceinline__ uint2 lds64(uint32_t a) {
    uint2 v; asm volatile("ld.shared.v2.u32 {%0,%1}, [%2];" : "=r"(v.x), "=r"(v.y) : "r"(a) : "memory"); return v;
}
__device__ __forceinline__ uint4 lds128(uint32_t a) {
    uint4 v; asm volatile("ld.shared.v4.u32 {%0,%1,%2,%3}, [%4];" : "=r"(v.x), "=r"(v.y), "=r"(v.z), "=r"(v.w) : "r"(a) : "memory"); return v;
}
__device__ __forceinline__ float sum8(const uint4& u, const uint4& v) {
    return ((F(u.x) + F(u.y)) + (F(u.z) + F(u.w))) + ((F(v.x) + F(v.y)) + (F(v.z) + F(v.w)));
}
__device__ __forceinline__ void sts16(uint32_t a, uint32_t v) { asm volatile("st.shared.u16 [%0], %1;" ::"r"(a), "h"((unsigned short)v) : "memory"); }
__device__ __forceinline__ void sts32(uint32_t a, uint32_t v) { asm volatile("st.shared.u32 [%0], %1;" ::"r"(a), "r"(v) : "memory"); }
__device__ __forceinline__ void stsf(uint32_t a, float v) { asm volatile("st.shared.f32 [%0], %1;" ::"r"(a), "f"(v) : "memory"); }
__device__ __forceinline__ void stsf2(uint32_t a, float x, float y) { asm volatile("st.shared.v2.f32 [%0], {%1,%2};" ::"r"(a), "f"(x), "f"(y) : "memory"); }
__device__ __forceinline__ void stsf4(uint32_t a, float x, float y, float z, float w) {
    asm volatile("st.shared.v4.f32 [%0], {%1,%2,%3,%4};" ::"r"(a), "f"(x), "f"(y), "f"(z), "f"(w) : "memory");
}
template <int ID, int N> __device__ __forceinline__ void bar_sync() { asm volatile("bar.sync %0, %1;" ::"n"(ID), "n"(N) : "memory"); }
template <int ID, int N> __device__ __forceinline__ void bar_arrive() { asm volatile("bar.arrive %0, %1;" ::"n"(ID), "n"(N) : "memory"); }
__device__ __forceinline__ void fence_async() { asm volatile("fence.proxy.async.shared::cta;" ::: "memory"); }
__device__ __forceinline__ float shx(float v, int m) { return __shfl_xor_sync(0xffffffffu, v, m); }
__device__ __forceinline__ float shi(float v, int l) { return __shfl_sync(0xffffffffu, v, l); }
__device__ __forceinline__ uint32_t shi(uint32_t v, int l) { return __shfl_sync(0xffffffffu, v, l); }
__device__ __forceinline__ uint32_t opaque(uint32_t x) { asm volatile("mov.u32 %0, %0;" : "+r"(x)); return x; }
__device__ __forceinline__ const char* opaque(const char* x) { asm volatile("mov.u64 %0, %0;" : "+l"(x)); return x; }
constexpr float LOG2E = 1.4426950408889634f;

#define TRACE(idx) do {} while (0)
#define TRACES(slot) do {} while (0)

__device__ __forceinline__ int kv_group(int k, int t) {
    const int cta = blockIdx.x;
    return ((k * NHEAD + (cta >> 2)) * SK + (SK - WIN) + (cta & 3) * 256 + t * 32) / 8;
}
__device__ __forceinline__ uint32_t phase_ns() { return (((blockIdx.x >> 2) * 13) & 31) * (CFG_TICK0 / 32); }

__device__ __forceinline__ void prefetch_role(const Params& p, const CUtensorMap* tmV, uint32_t t0) {
    const int cta = blockIdx.x;
    t0 += phase_ns();
#pragma unroll 1
    for (int i = 0; i < 5; i++) {
        wait_ns(t0 + i * CFG_TICK0);
        if (elect_one()) l2_prefetch(p.wq + (size_t)(128 * i + cta) * 12288, 12288);
    }
#pragma unroll 1
    for (int i = 0; i < 5; i++) {
        wait_ns(t0 + kb_ns(75) + i * kb_ns(6));
        if (elect_one()) { l2_prefetch(p.wg + (128 * i + cta) * 3072, 3072); l2_prefetch(p.wu + (128 * i + cta) * 3072, 3072); }
    }
#pragma unroll 1
    for (int i = 0; i < 6; i++) {
        wait_ns(t0 + kb_ns(105) + i * kb_ns(10));
        if (elect_one()) l2_prefetch(p.wo + (size_t)((cta >> 2) * DH + 32 * i + 8 * (cta & 3)) * 1280, 10240);
    }
    bar_sync<6, 64>();
#pragma unroll 1
    for (int i = 4; i < 4 * NB; i++) {
        const int k = i >> 2, t = 12 + (i & 3);
        mbar_wait(bar_at(B_RK + ((i >> 1) & 1)), (k - 1) & 1);
        SPIN_DECL;
        while ((int)lds32(SM_PROG) <= 16 * k + t) SPIN_CHECK(i);
        if (i < 4 * NB - 1) wait_ns(t0);
        t0 = now_ns() + CFG_VSTEP;
        if (elect_one()) {
            mbar_expect_tx(bar_at(B_F1 + t), TILE);
            tma_tile(SB + slot_at(slots(k), t >> 1) * PAIR + (t & 1) * TILE, tmV, kv_group(k, t & 7), bar_at(B_F1 + t), POL_FIRST);
        }
        TRACE(256 + 16 * k + t);
    }
}

struct WeightMaps { CUtensorMap q, o, g, u; };
__device__ __forceinline__ void load_role(const Params& p, const CUtensorMap* tmK, const CUtensorMap* tmV, uint32_t t0) {
    t0 += phase_ns();
    wait_ns(t0 + kb_ns(60));
    if (elect_one()) bulk_load(ST_WD, p.wd + blockIdx.x * 15360, 15360, bar_at(B_W));
    auto ahead = [&](int j) {
        if (CFG_PFB > 0) l2_prefetch((j & 8 ? p.vc : p.kc) + (size_t)kv_group(j >> 4, j & 7) * 3072 + (TILE - CFG_PFB), CFG_PFB);
    };
#pragma unroll 1
    for (int j = 0; j < 2; j++) {
        wait_ns(t0 + kb_ns(KB_KV0) + j * PF_NS);
        if (elect_one()) ahead(j);
    }
#pragma unroll 1
    for (int j = 0; j < 16 * NB; j++) {
        const int k = j >> 4, t = j & 15, u = t >> 1;
        if (j == 0 || j == 8 || j == 14) mbar_wait(bar_at(B_WC + j / 7), 0);
        if (k > 0 && t < 12) {
            if (t >= 4) mbar_wait(bar_at(B_RR + t - 4), k & 1);
            else if (t >= 2) mbar_wait(bar_at(B_RP), (k - 1) & 1);
            else if (k > 1) mbar_wait(bar_at(B_RK + 3), k & 1);
            else mbar_wait(bar_at(B_RR + t), 0);
        }
        const int jw = j - CFG_WIN;
        if (jw >= 0 && (jw < 16 || (jw & 15) < 12)) mbar_wait(bar_at(B_F1 + (jw & 15)), (jw >> 4) & 1);
        const int jv = j - CFG_WIN2;
        if (jv >= 16 && (jv & 15) >= 12) mbar_wait(bar_at(B_F1 + (jv & 15)), (jv >> 4) & 1);
        const uint32_t dst = SB + slot_at(slots(k), t < 8 ? pass_nibble(k, u) : u) * PAIR + (t & 1) * TILE;
        const int late = now_ns() - (t0 + tile_ns(j));
        if (late > CFG_LMAX) t0 += late - CFG_LMAX;
        wait_ns(t0 + tile_ns(j));
        if (elect_one()) {
            if (k > 0 && t >= 12) {
                l2_prefetch(p.vc + (size_t)kv_group(k, t & 7) * 3072, TILE - CFG_PFB);
            } else {
                mbar_expect_tx(bar_at(B_F1 + t), TILE);
                tma_tile(dst, t & 8 ? tmV : tmK, kv_group(k, t & 7), bar_at(B_F1 + t), t < 10 && j >= 8 && j < 56 ? POL_NORMAL : POL_FIRST);
            }
            if (j + 2 < 16 * NB) ahead(j + 2);
            sts32(SM_PROG, j + 1);
        }
        TRACE(128 + j);
    }
}

__device__ __forceinline__ void reload_role(const Params& p, const CUtensorMap* tmK, const CUtensorMap* tmV, const WeightMaps* tm, uint32_t t0) {
    const int cta = blockIdx.x;
    t0 += CFG_TICK0 + CFG_WLAG + phase_ns();
#pragma unroll 1
    for (int i = 0; i < 5; i++) {
        wait_ns(t0 + i * CFG_TICK0);
        if (elect_one()) tma2d(ST_WQ + i * 12288, &tm->q, 48 * cta, 128 * i, bar_at(B_W));
        if (i == 1) bar_sync<5, 480>();
    }
#pragma unroll 1
    for (int i = 0, o = 0; i < 10;) {
        const uint32_t now = now_ns() - t0;
        if (o < 6 && (int)now >= kb_ns(105) + o * kb_ns(10)) {
            if (elect_one()) tma2d(ST_WO + o * 10240, &tm->o, 160 * (cta & 3), (cta >> 2) * DH + 32 * o, bar_at(B_W + 1));
            o++;
        } else if ((int)now >= kb_ns(77) + i * CFG_GSTEP && (i < 9 || o == 6)) {
            if (elect_one()) tma2d(ST_WG + (i & 1) * 20480 + (i >> 1) * 4096, i & 1 ? &tm->u : &tm->g, (12 * cta) & ~7, 128 * (i >> 1), bar_at(B_W + 2));
            i++;
        }
    }
#pragma unroll 1
    for (int k = 0; k < NB - 1; k++) {
        mbar_wait(bar_at(B_RK + 2), k & 1);
        if (elect_one()) {
            const uint32_t dst = SB + slot_at(slots(k), 2) * PAIR;
            mbar_expect_tx(bar_at(B_FL), PAIR);
            tma_tile(dst, tmV, kv_group(k, 0), bar_at(B_FL), POL_FIRST);
            tma_tile(dst + TILE, tmV, kv_group(k, 1), bar_at(B_FL), POL_FIRST);
        }
        mbar_wait(bar_at(B_RV), k & 1);
        uint32_t due = now_ns() + (k == NB - 2 ? 0 : CFG_RLAG);
        if (elect_one()) mbar_expect_tx(bar_at(B_F3), 4 * PAIR);
#pragma unroll 1
        for (int t = 0; t < 8; t++) {
            wait_ns(due);
            due += k == NB - 2 ? CFG_RSTEP3 : CFG_RSTEP;
            if (elect_one())
                tma_tile(SB + slot_at(slots(k + 1), t >> 1) * PAIR + (t & 1) * TILE, tmK, kv_group(k + 1, t), bar_at(B_F3), POL_FIRST);
        }
        TRACE(121 + k);
    }
}

__device__ __forceinline__ void zero_role(const Params& p, int lane, unsigned ticket, uint32_t t0) {
    const int cta = blockIdx.x;
    const uint32_t epoch = __shfl_sync(0xffffffffu, ticket, 0) / NCTA + 1;
    if (lane == 0) { sts32(SM_EPOCH, epoch); mbar_arrive(bar_at(B_EP)); }
    const int cl = 2 * (cta & 15) + (lane & 1);
    const int col = 80 * (cta >> 4) + (cl & 2 ? 48 : 0) + (cl >> 2) + (cl & 1 ? 8 : 0);
    const char* own = reinterpret_cast<const char*>(g_acc) + (cta >> 4) * 2048 + (cl >> 2) * 256 + (cl & 3) * 16;
#pragma unroll 1
    for (int k = 0; k < NB + 2; k++) {
        if (k < NB) {
            wait_ns(t0 + tile_ns(16 * k + CFG_ZTILE));
            const int lg = lane >> 3, ty = (lane & 7) >> 1;
            const char* dst = own + (k - (lg >> 1)) * (int)ACC_SET + ty * ACC_TYPE + (lg ? 128 : 0);
            uint32_t v0 = 0, v1 = 0, v2 = 0, v3 = 0;
            if (lane < 2) {
                const unsigned short* xp = p.x + k * DM + col;
                v0 = __ldg(xp) << 16; v1 = __ldg(xp + 16) << 16; v2 = cl & 2 ? 0 : __ldg(xp + 32) << 16; v3 = 0x3f800000u;
            }
            if (ty < 3 && (lg == 0 || (lg == 1 && (ty == 0 || k == NB - 1)) || (lg == 2 && k > 0 && ty > 0))) st_pkt(dst, v0, v1, v2, v3);
            asm volatile("fence.acq_rel.gpu;" ::: "memory");
            __syncwarp();
            if (lane == 0) asm volatile("red.relaxed.gpu.global.add.u32 [%0], 1;" ::"l"(&g_init) : "memory");
            const uint32_t target = ((epoch - 1) * NB + k + 1) * NCTA;
            SPIN_DECL;
            while (true) {
                __nanosleep(400);
                uint32_t v;
                asm volatile("ld.acquire.gpu.global.u32 %0, [%1];" : "=r"(v) : "l"(&g_init) : "memory");
                if (__all_sync(0xffffffffu, (int)(v - target) >= 0)) break;
                SPIN_CHECK(v);
            }
        }
        uint4 r;
        if (k == 1) mbar_wait(bar_at(B_RK), 0);
        if (k > 1) {
            mbar_wait(bar_at(B_FIN), k & 1);
            r = lds128(SM_FIN + (lane & 1) * 16);
        }
        __syncwarp();
        if (lane == 0) mbar_arrive(bar_at(B_Z));
        if (k > 1) {
            const int b = k - 2;
            const char* src = own + b * ACC_SET + (1 + ((lane >> 1) & 1)) * ACC_TYPE + 128;
            unsigned short* o = p.out + b * DM + col;
            wait_clk(clk32() + CFG_DLY_F);
            uint4 v = {};
            SPIN_DECL;
            while (true) {
                v = ld_pkt(src);
                if (__all_sync(0xffffffffu, v.w == FULL_B)) break;
                SPIN_CHECK(k);
            }
            const float y0 = F(v.x) + shx(F(v.x), 2), y1 = F(v.y) + shx(F(v.y), 2), y2 = F(v.z) + shx(F(v.z), 2);
            const uint32_t x01 = badd2(r.x, badd2(r.y, bmul2(pack2(y0, y1), r.w)));
            const uint32_t x2 = badd2(r.z, badd2(r.z >> 16, bmul2(pack2(y2, 0.f), r.w)));
            if (lane < 2) {
                o[0] = x01; o[16] = x01 >> 16;
                if (!(cl & 2)) o[32] = x2;
            }
            TRACES((2 * b + 1) * 6 + 4);
        }
    }
}

__host__ __device__ constexpr uint32_t desc_lo(uint32_t addr) { return ((addr & 0x3FFFFu) >> 4) | (1u << 16); }
constexpr uint32_t DESC_HI_TILE = (3072u >> 4) | (1u << 30);
constexpr uint32_t DESC_HI_VEC = 1u;
template <int TA, int AOFF, int BOFF>
__device__ __forceinline__ void wgmma_n8(float (&d)[4], uint32_t alo, uint32_t blo, int accumulate) {
    asm volatile("{\n.reg .pred p;\n.reg .b32 a, b;\n.reg .b64 da, db;\nsetp.ne.b32 p, %6, 0;\n"
                 "add.u32 a, %4, %8;\nadd.u32 b, %5, %9;\nmov.b64 da, {a, %10};\nmov.b64 db, {b, %11};\n"
                 "wgmma.mma_async.sync.aligned.m64n8k16.f32.bf16.bf16 {%0,%1,%2,%3}, da, db, p, 1, 1, %7, 0;\n}"
                 : "+f"(d[0]), "+f"(d[1]), "+f"(d[2]), "+f"(d[3])
                 : "r"(alo), "r"(blo), "r"(accumulate), "n"(TA), "n"(AOFF >> 4), "n"(BOFF >> 4), "n"(DESC_HI_TILE), "n"(DESC_HI_VEC));
}
template <int KS>
__device__ __forceinline__ void qk_steps(float (&d)[4], uint32_t alo, uint32_t blo) {
    if constexpr (KS < 12) {
        wgmma_n8<0, (KS >> 2) * 1024 + (KS & 3) * 32, KS * 32>(d, alo, blo, KS > 0);
        qk_steps<KS + 1>(d, alo, blo);
    }
}
__device__ __forceinline__ void pv_steps(float (&e)[3][4], uint32_t alo, uint32_t blo, int acc) {
    wgmma_n8<1, 0, 0>(e[0], alo, blo, acc); wgmma_n8<1, 1024, 0>(e[1], alo, blo, acc); wgmma_n8<1, 2048, 0>(e[2], alo, blo, acc);
    wgmma_n8<1, 6144, 32>(e[0], alo, blo, 1); wgmma_n8<1, 7168, 32>(e[1], alo, blo, 1); wgmma_n8<1, 8192, 32>(e[2], alo, blo, 1);
}
__device__ __forceinline__ void wg_fence() { asm volatile("wgmma.fence.sync.aligned;" ::: "memory"); }
__device__ __forceinline__ void wg_commit() { asm volatile("wgmma.commit_group.sync.aligned;" ::: "memory"); }
template <int N> __device__ __forceinline__ void wg_wait() { asm volatile("wgmma.wait_group.sync.aligned %0;" ::"n"(N) : "memory"); }
__device__ __forceinline__ void qk_pair(float (&d)[4], uint32_t slot, uint32_t qslot) {
    wg_fence();
    qk_steps<0>(d, desc_lo(SB) + slot * (PAIR >> 4), desc_lo(SM_Q) + qslot * (384 >> 4));
    wg_commit();
}
__device__ __forceinline__ void acc_ready(float (&d)[4]) { asm volatile("" : "+f"(d[0]), "+f"(d[1]), "+f"(d[2]), "+f"(d[3]) :: "memory"); }
__device__ __forceinline__ uint32_t score_pair(float (&d)[4], int lane) {
    acc_ready(d);
    const float scale = 0.07216878364870322f;
    const uint32_t r = pack2(d[0], d[2]);
    return shi(pack2(bf_lo(r) * scale, bf_hi(r) * scale), lane & 28);
}

__device__ __forceinline__ void attention_role(const Params& p, int w, int lane) {
    const int cta = blockIdx.x, t4 = lane & 3, g = lane >> 2;
    mbar_wait(bar_at(B_EP), 0);
    const uint32_t tag0 = lds32(SM_EPOCH) * NB;
    auto get_q = [&](int slot, uint32_t tag) {
        if (w < 3) {
            const uint2* src = &g_q[slot][cta >> 2][w * 32 + lane];
            uint2 v;
            SPIN_DECL;
            while (true) {
                v = ld_pkt8(src);
                if (__all_sync(0xffffffffu, v.y == tag)) break;
                SPIN_CHECK(slot);
            }
            sts32(SM_Q + slot * 384 + (w * 32 + lane) * 4, v.x);
            fence_async();
        }
        bar_sync<4, 128>();
    };
    uint32_t m1 = 0;
    auto softmax = [&](uint32_t sc, int ps) -> uint32_t {
        const float s0 = bf_lo(sc), s1 = bf_hi(sc);
        int key = __float_as_int(fmaxf(s0, s1));
        key ^= (key >> 31) & 0x7fffffff;
        key = __reduce_max_sync(0xffffffffu, key);
        sts32_if(lane == 0, SM_MAX + w * 4, key);
        bar_sync<4, 128>();
        const uint4 mx = lds128(SM_MAX);
        key = max(max((int)mx.x, (int)mx.y), max((int)mx.z, (int)mx.w));
        key ^= (key >> 31) & 0x7fffffff;
        const float mb = __int_as_float(key) * LOG2E;
        const uint32_t pp = pack2(fast_ex2(fmaf(s0, LOG2E, -mb)), fast_ex2(fmaf(s1, LOG2E, -mb)));
        const uint32_t a = SM_P + (ps * 4 + t4) * PSTR + (16 * w + g) * 2;
        sts16(a, pp); sts16(a + 16, pp >> 16);
        fence_async();
        bar_sync<4, 128>();
        return key;
    };
    mbar_wait(bar_at(B_QS), 0);
#pragma unroll 1
    for (int b = 0; b < NB; b++) { TRACES(84 + b); get_q(b, tag0 + b); }
    TRACES(73);
#pragma unroll 1
    for (int it = 0; it <= NB; it++) {
        uint32_t m2 = 0;
#pragma unroll 1
        for (int ps = it == NB; ps <= (it > 0); ps++) {
            uint32_t sc = 0;
            const int k = it - ps;
            const uint32_t tab = slots(k);
            if (ps == 0) {
#pragma unroll 1
                for (int t = 0; t < 8; t++) {
                    mbar_wait(bar_at(B_F1 + t), k & 1);
                    float d[4];
                    const uint32_t alo = desc_lo(SB) + slot_at(tab, pass_nibble(k, t >> 1)) * (PAIR >> 4), blo = desc_lo(SM_Q) + k * (384 >> 4);
#pragma unroll 1
                    for (int c = 0; c < 3; c++) {
                        wg_fence();
                        wgmma_n8<0, 0, 0>(d, alo + c * 64, blo + c * 8, c > 0); wgmma_n8<0, 32, 32>(d, alo + c * 64, blo + c * 8, 1);
                        wgmma_n8<0, 64, 64>(d, alo + c * 64, blo + c * 8, 1); wgmma_n8<0, 96, 96>(d, alo + c * 64, blo + c * 8, 1);
                        wg_commit();
                        if (CFG_QKWAIT) wg_wait<0>();
                    }
                    wg_wait<0>();
                    if ((t & 1) == (w >> 1)) {
                        mbar_arrive_if(lane == 0, bar_at(B_RR + t));
                        const uint32_t s = score_pair(d, lane);
                        if (t4 == t >> 1) sc = s;
                    }
                }
            } else {
                TRACES(48 + k * 6);
                if (k > 0) mbar_wait(bar_at(B_F3), it & 1);
                mbar_wait(bar_at(B_QS), it & 1);
                wait_clk(clk32() + CFG_DLY_Q);
                get_q(4, tag0 + k);
                TRACES(49 + k * 6);
                float d[4][4];
#pragma unroll
                for (int u = 0; u < 4; u++) {
                    qk_pair(d[u], slot_at(tab, u), 4);
                    if (u == 2) { wg_wait<2>(); mbar_arrive_if(lane == 0, bar_at(B_RK)); }
                }
                sc = score_pair(d[0], lane);
                wg_wait<2>();
                mbar_arrive_if(lane == 0, bar_at(B_RK + 1));
                uint32_t s = score_pair(d[1], lane);
                if (t4 == 1) sc = s;
                wg_wait<1>();
                mbar_arrive_if(lane == 0, bar_at(B_RK + 2));
                s = score_pair(d[2], lane);
                if (t4 == 2) sc = s;
                wg_wait<0>();
                s = score_pair(d[3], lane);
                mbar_arrive_if(lane == 0, bar_at(B_RK + 3));
                if (t4 == 3) sc = s;
                TRACES(50 + k * 6);
            }
            m2 = softmax(sc, ps);
            if (ps == 0) m1 = m2;
        }
#pragma unroll 1
        for (int ps = it > 0; ps >= (it == NB); ps--) {
            const int k = it - ps;
            TRACES(ps ? 51 + k * 6 : 95);
            const uint32_t tab = slots(k);
            const char* dst = opaque(reinterpret_cast<const char*>(&g_o[ps][cta >> 2][2 * w + (g >> 2)][cta & 3][g & 3]));
            st_pkt_if(t4 == 0, dst, 0, 0, 0, tag0 + k + 128);
            float e[3][4];
            uint4 u;
            float l, lx;
#pragma unroll
            for (int t = 0; t < 8; t++) {
                const int pr = ((t >> 1) + ps) & 3;
                const bool late = t >= 6 && ps && k < NB - 1;
                if (ps == 0) mbar_wait(bar_at(B_F1 + 8 + t), k & 1);
                if (t == 6 && late) mbar_wait(bar_at(B_FL), k & 1);
                wg_fence();
                pv_steps(e, desc_lo(SB + (t & 1) * TILE) + slot_at(tab, late ? 2 : 4 + pr) * (PAIR >> 4),
                         desc_lo(SM_P + (t & 1) * 64) + (4 * ps + pr) * (PSTR >> 4), t > 0);
                wg_commit();
                if (t == 2 && ps == 0) { wg_wait<1>(); mbar_arrive_if(lane == 0, bar_at(B_RP)); }
                if (t == 0) u = lds128(SM_P + (ps * 4 + (lane >> 3)) * PSTR + (lane & 7) * 16);
                if (t == 1) l = ((bf_lo(u.x) + bf_hi(u.x)) + (bf_lo(u.y) + bf_hi(u.y))) + ((bf_lo(u.z) + bf_hi(u.z)) + (bf_lo(u.w) + bf_hi(u.w)));
                if (t >= 2 && t <= 6) l += lx;
                if (t >= 1 && t <= 5) lx = shx(l, 32 >> t);
                if (t == 6) m2 = opaque((g < 4 ? (ps ? m2 : m1) : (__float_as_uint(l) + 0x80u) & 0xffffff00u) | ((tag0 + k) & 0xffu));
            }
            wg_wait<0>();
            acc_ready(e[0]); acc_ready(e[1]); acc_ready(e[2]);
            st_pkt_if(t4 == 0, dst, pack2(e[0][0], e[0][2]), pack2(e[1][0], e[1][2]), pack2(e[2][0], e[2][2]), m2);
            mbar_arrive_if(lane == 0, bar_at(ps ? B_RV : B_PS));
            TRACES((ps ? 52 : 53) + k * 6);
        }
    }
}

__device__ __forceinline__ void ln_finish(float s, float q, float& mean_b, float& rden) {
    const float mean = s * (1.f / DM);
    const float var = fmaxf(fmaf(q, 1.f / DM, -mean * mean), 0.f);
    mean_b = bfr(mean);
    rden = fast_rcp(bfr(fast_sqrt(bfr(bfr(var) + 1e-5f))));
}
__device__ __forceinline__ void ln_fast(float s, float q, float& mean, float& rstd) {
    mean = s * (1.f / DM);
    asm("rsqrt.approx.ftz.f32 %0, %1;" : "=f"(rstd) : "f"(fmaxf(fmaf(-mean, mean, fmaf(q, 1.f / DM, 1e-5f)), 1e-5f)));
}
__device__ __forceinline__ uint32_t ln_apply(uint32_t w, float mean_b, float rden) {
    const uint32_t d = bsub2(w, __byte_perm(__float_as_uint(mean_b), 0, 0x3232));
    return pack2(bf_lo(d) * rden, bf_hi(d) * rden);
}
__device__ __forceinline__ void spread(uint32_t (&b)[10], uint32_t x01, uint32_t x2, uint32_t wa, uint32_t ra, bool e2) {
    sts16(wa, x01); sts16(wa + 8, x01 >> 16);
    sts16_if(!e2, wa + 16, x2);
    __syncwarp();
    const uint4 u = lds128(ra), v = lds128(ra + 16);
    const uint2 z = lds64(ra + 32);
    b[0] = u.x; b[1] = u.y; b[2] = u.z; b[3] = u.w; b[4] = v.x; b[5] = v.y; b[6] = v.z; b[7] = v.w; b[8] = z.x; b[9] = z.y;
}
__device__ __forceinline__ float fold(float a, float b, bool sel, int m) { return (sel ? b : a) + shx(sel ? a : b, m); }

__device__ __forceinline__ void chain_role(const Params& p, int w, int lane, uint32_t t0) {
    const int cta = blockIdx.x, h = cta >> 2, s = cta & 3;
    const int g = lane >> 2, t4 = lane & 3;
    const bool e1 = t4 & 1, e2 = t4 & 2;
    uint32_t wq[5][3][4], wo[3][5][4], wg[5][4], wh[5][2], wd[4][4];
    const int col0 = 80 * w + (e2 ? 48 : 0) + g + (e1 ? 8 : 0);
    const uint32_t xw = opaque(SM_X + w * 384 + 48 * (g >> 1) + (e2 ? 24 : 0) + (e1 ? 4 : 0) + 2 * (g & 1));
    const uint32_t xr = opaque(g == 1 ? SM_ONES : SM_X + w * 384 + (g == 3 ? 192 : 0) + 48 * t4);
    TRACES(75);
    sts32_if(lane < 12, SM_ONES + lane * 4, 0x3f803f80u);
    uint32_t zero = lane >> 5;
    const int mi = lane >> 3, mr = lane & 7;
    mbar_wait(bar_at(B_W), 0);
    TRACES(74);
    sts16(xw + 192, lds16(ST_X + 5120 + col0 * 2)); sts16(xw + 200, lds16(ST_X + 5120 + col0 * 2 + 32));
    sts16_if(!e2, xw + 208, lds16(ST_X + 5120 + col0 * 2 + 64));
#pragma unroll
    for (int i = 0; i < 5; i++)
#pragma unroll
        for (int mt = 0; mt < 3; mt++) ldsm4t(wq[i][mt], ST_WQ + (80 * w + 16 * i + mr + 8 * (mi >> 1)) * 96 + 32 * mt + 16 * (mi & 1), zero);
    const bool odd = cta & 1;
    const uint32_t lo = ST_WD + (mr + (odd ? 4 : 0)) * 1280 + 160 * w, hi = ST_WD + ((mr & 3) + (odd ? 0 : 8)) * 1280 + 160 * w;
    ldsm4t(wd[0], lo + 16 * mi, zero);
    ldsm4t(wd[1], lo + 64 + 16 * mi, zero);
    ldsm4t(wd[2], hi + 64 * (mi >> 1) + 32 * (mr >> 2) + 16 * (mi & 1), zero);
    ldsm4t(wd[3], (mi < 2 ? lo : hi) + 128 + 16 * (mi & 1), zero);
    fence_async();
    __syncwarp();
    mbar_arrive_if(lane == 0, bar_at(B_WC));
    mbar_wait(bar_at(B_EP), 0);
    uint32_t x01 = 0, x2 = 0;
#pragma unroll 1
    for (int n = -5; n < NROUND; n++) {
        const bool last = (ORD_LAST >> (n & 15)) & 1, head = !((ORD_NO_HEAD >> (n & 15)) & 1);
        const int k = (ORD_BATCH >> (2 * (n & 15))) & 3;
        if (!last) bar_sync<2, 256>();
        TRACES(n <= 0 ? 83 + n : 95);
        const char* const slice = reinterpret_cast<const char*>(g_acc) + k * ACC_SET + (last ? 128 : 0) + w * 2048;
        const char* const cell = opaque(slice + g * 256 + t4 * 16);
        const char* const watch = slice + (cta & 7) * 256 + ((cta >> 3) & 3) * 16;
        if (n >= 0) {
          uint4 v;
          if (head) {
            if (!last || n == NROUND - 1) mbar_wait(bar_at(B_Z), (k + last) & 1);
            const uint4* src = &g_o[last][h][w & 6][g & 3][t4];
            const uint32_t tag = lds32(SM_EPOCH) * NB + k;
            mbar_wait(bar_at(last ? B_RV : B_PS), k & 1);
            wait_clk(clk32() + CFG_DLY_P);
            if (CFG_START && !last && k < NB - 1) wait_ns(t0 + tile_ns(16 * k + 15) + CFG_START);
            uint4 z;
            {
                SPIN_DECL;
                while (true) {
                    v = ld_pkt(src); z = ld_pkt(src + 16);
                    if (__all_sync(0xffffffffu, (((v.w ^ tag) | (z.w ^ tag)) & 0xffu) == 0)) break;
                    SPIN_CHECK(n);
                }
            }
            TRACES(tr + 0);
            float a[3][4] = {};
            const uint32_t bb[3][2] = {{v.x, v.y}, {z.x, z.y}, {v.z, z.z}};
            float sa, sb;
#pragma unroll
            for (int i = 0; i < 3; i++) {
                const uint32_t l0 = g < 4 ? bb[i][0] : 0, l1 = g < 4 ? bb[i][1] : 0, h0 = g < 4 ? 0 : bb[i][0], h1 = g < 4 ? 0 : bb[i][1];
#pragma unroll
                for (int mt = 0; mt < 5; mt++)
                    mma16816(a[mt % 3], wo[i][mt][0], wo[i][mt][1], wo[i][mt][2], wo[i][mt][3], mt < 3 ? l0 : h0, mt < 3 ? l1 : h1);
                if (i == 0) {
                    const float am = F(v.w & 0xffffff00u), al = F(z.w & 0xffffff00u);
                    const float m0 = shi(am, 0), m1 = shi(am, 4), m2 = shi(am, 8), m3 = shi(am, 12);
                    const float s0 = shi(al, 0), s1 = shi(al, 4), s2 = shi(al, 8), s3 = shi(al, 12);
                    const float mb = fmaxf(fmaxf(m0, m1), fmaxf(m2, m3)) * LOG2E;
                    const float w0 = fast_ex2(fmaf(m0, LOG2E, -mb)), w1 = fast_ex2(fmaf(m1, LOG2E, -mb));
                    const float w2 = fast_ex2(fmaf(m2, LOG2E, -mb)), w3 = fast_ex2(fmaf(m3, LOG2E, -mb));
                    const float rl = fast_rcp(fmaf(w0, s0, w1 * s1) + fmaf(w2, s2, w3 * s3));
                    sa = (e1 ? w2 : w0) * rl; sb = (e1 ? w3 : w1) * rl;
                }
            }
            float y[3];
#pragma unroll
            for (int j = 2; j < 5; j++) {
                const int mt = j % 3;
                y[mt] = fold(fmaf(a[mt][0], sa, a[mt][1] * sb), fmaf(a[mt][2], sa, a[mt][3] * sb), e1, 1);
            }
            const uint32_t pa = SM_PO + w * 512 + lane * 16;
            if (w < 2) {
                const char* dst = opaque(cell + s * 4096);
                bar_sync<1, 256>();
                const uint4 c1 = lds128(pa), c2 = lds128(pa + 1024), c3 = lds128(pa + 2048);
                red_cell(dst, (y[0] + F(c1.x)) + (F(c2.x) + F(c3.x)), (y[1] + F(c1.y)) + (F(c2.y) + F(c3.y)), (y[2] + F(c1.z)) + (F(c2.z) + F(c3.z)));
            } else {
                stsf4(pa - 1024, y[0], y[1], y[2], 0.f);
                bar_sync<1, 256>();
            }
            TRACES(tr + 1);
            if ((ORD_NO_TAIL >> n) & 1) continue;
            wait_clk(clk32() + (w < 2 ? 0 : 60) + (n < CFG_TIMED ? CFG_DLY_AL : CFG_DLY_A));
          }
            {
                SPIN_DECL;
                if ((CFG_SENT & 1) && n < CFG_TIMED && head) while (__any_sync(0xffffffffu, cell_count(watch) != FULL_A)) SPIN_CHECK(n);
                while (true) {
                    v = ld_pkt(cell);
                    if (__all_sync(0xffffffffu, v.w == FULL_A)) break;
                    SPIN_CHECK(n);
                }
            }
            TRACES(tr + 2);
            x01 = pack2(F(v.x), F(v.y));
            x2 = pack2(F(v.z), 0.f);
        } else if (n == -1) {
            mbar_wait(bar_at(B_W + 1), 0);
            const uint32_t ln = opaque(lane);
            const int mi = ln >> 3, mr = ln & 7;
            uint32_t zero = ln >> 5;
            TRACES(76);
#pragma unroll
            for (int i = 0; i < 3; i++) {
                const int d = 16 * (w >> 1) + (mr >> 1) + 8 * (mr & 1) + (i < 2 ? 64 * (mi >> 1) + 4 * i : 128 + 4 * (mi >> 1));
#pragma unroll
                for (int mt = 0; mt < 5; mt++) ldsm4t(wo[i][mt], ST_WO + d * 320 + 160 * (w & 1) + 32 * mt + 16 * (mi & 1), zero);
            }
            fence_async();
            __syncwarp();
            mbar_arrive_if(lane == 0, bar_at(B_WC + 1));
            mbar_wait(bar_at(B_W + 2), 0);
            TRACES(77);
#pragma unroll
            for (int i = 0; i < 5; i++) {
                const uint32_t ga = ST_WG + (mi & 1) * 20480 + (80 * w + 16 * i + mr + 8 * (mi >> 1)) * 32;
                uint32_t r[4];
                ldsm4t(wg[i], ga + (odd ? 16 : 0), zero);
                ldsm4t(r, ga + (odd ? 0 : 16), zero);
#pragma unroll
                for (int kh = 0; kh < 2; kh++) {
                    const uint32_t moved = __shfl_xor_sync(0xffffffffu, odd ? r[2 * kh] : r[2 * kh + 1], 16);
                    wh[i][kh] = (g < 4) == odd ? moved : odd ? r[2 * kh + 1] : r[2 * kh];
                }
            }
            fence_async();
            __syncwarp();
            mbar_arrive_if(lane == 0, bar_at(B_WC + 2));
            TRACES(72);
            x01 = 0x3f803f80u; x2 = 0x3f80u;
        } else {
            const uint32_t xa = ST_X + (n + 5) * 1280, ln = opaque(lane);
            const int col0 = 80 * w + (ln & 2 ? 48 : 0) + (ln >> 2) + (ln & 1 ? 8 : 0);
            float sm = 0.f, sq = 0.f;
#pragma unroll
            for (int i = 0; i < 5; i++) {
                const uint2 c = lds64(xa + i * 256 + ln * 8);
                sm += (bf_lo(c.x) + bf_hi(c.x)) + (bf_lo(c.y) + bf_hi(c.y));
                sq = fmaf(bf_lo(c.x), bf_lo(c.x), fmaf(bf_hi(c.x), bf_hi(c.x), fmaf(bf_lo(c.y), bf_lo(c.y), fmaf(bf_hi(c.y), bf_hi(c.y), sq))));
            }
            x01 = lds16(xa + col0 * 2) | lds16(xa + col0 * 2 + 32) << 16;
            x2 = lds16(xa + col0 * 2 + 64);
#pragma unroll
            for (int o = 16; o; o >>= 1) { sm += shx(sm, o); sq += shx(sq, o); }
            float mean_b, rden;
            ln_finish(sm, sq, mean_b, rden);
            x01 = ln_apply(x01, mean_b, rden);
            x2 = ln_apply(x2, mean_b, rden);
        }
        if (n >= -1) {
            uint32_t b[10];
            spread(b, x01, x2, xw, xr, e2);
            float a[2][4] = {};
#pragma unroll
            for (int i = 0; i < 5; i++) {
                mma16816(a[0], wg[i][0], wg[i][1], wg[i][2], wg[i][3], b[2 * i], b[2 * i + 1]);
                mma16816(a[1], wh[i][0], b[2 * i], wh[i][1], b[2 * i + 1], b[2 * i], b[2 * i + 1]);
            }
            stsf(SM_PG + (w >> 2) * 512 + (g + 8 * t4) * 16 + (w & 3) * 4, e2 ? (e1 ? a[1][2] : a[1][0]) : (e1 ? a[0][2] : a[0][0]));
            const uint2 cs = lds64(SM_CSG + lane * 48);
            const char* dst = opaque(cell + (1 + (cta & 1)) * ACC_TYPE);
            bar_sync<2, 256>();
            const float S = sum8(lds128(SM_PG + lane * 16), lds128(SM_PG + 512 + lane * 16));
            const float sx = shi(S, 25), sq = shi(S, 24), Su = shi(S, lane + (lane < 16 ? 8 : 4));
            if (n < 0) {
                if (w == 0) stsf2(SM_CSG + lane * 48, S, Su);
            } else {
                float mean_b, rden;
                ln_fast(sx, sq, mean_b, rden);
                const float gv = bfr(fmaf(-mean_b, F(cs.x), S) * rden), uv = bfr(fmaf(-mean_b, F(cs.y), Su) * rden);
                const float sg = fast_rcp(1.f + fast_ex2(-LOG2E * gv));
                const uint32_t hb = pack2(bfr(gv * sg) * uv, 0.f);
                const uint32_t b0 = __byte_perm(shi(hb, 2 * t4), shi(hb, 2 * t4 + 1), 0x5410);
                const uint32_t b1 = __byte_perm(shi(hb, e1 ? 18 : 16), shi(hb, e1 ? 19 : 17), 0x5410);
                const bool up = g >= 4;
                const uint32_t l0 = up ? 0 : b0, h0 = up ? b0 : 0;
                float d[3][4] = {};
                mma1688(d[0], wd[0][0], wd[0][1], l0); mma1688(d[1], wd[0][2], wd[0][3], l0); mma1688(d[2], wd[1][0], wd[1][1], l0);
                mma1688(d[0], wd[1][2], wd[1][3], h0); mma1688(d[1], wd[3][0], wd[3][1], h0);
                mma1688(d[2], wd[2][2], wd[2][3], up || e2 ? 0 : b1); mma1688(d[0], wd[2][0], wd[2][1], up || e2 ? 0 : b1);
                mma1688(d[1], wd[2][0], wd[2][1], !up && e2 ? b1 : 0);
                mma1688(d[0], wd[2][2], wd[2][3], up && e2 ? b1 : 0); mma1688(d[1], wd[3][2], wd[3][3], up && !e2 ? b1 : 0);
                red_cell(dst, e1 ? d[0][2] : d[0][0], e1 ? d[1][2] : d[1][0], e1 ? d[2][2] : d[2][0]);
                const uint32_t tsend = clk32();
                TRACES(tr + 3);
                if (last && w != cta >> 4) continue;
                if (!last && w == 0) st_pkt8_if(lane < 24, &g_q[4][h][24 * s + lane], 0, 0);
                const float sgr = shi(sg, 27);
                const uint32_t sg2 = pack2(sgr, sgr);
                const uint32_t n01 = opaque(pack2((bf_lo(x01) - mean_b) * rden, (bf_hi(x01) - mean_b) * rden));
                const uint32_t n2 = opaque(pack2((bf_lo(x2) - mean_b) * rden, 0.f));
                if (last) {
                    sts128_if(lane >> 1 == (cta & 15), SM_FIN + (lane & 1) * 16, x01, n01, __byte_perm(x2, n2, 0x5410), sg2);
                    mbar_arrive_if(lane >> 1 == (cta & 15), bar_at(B_FIN));
                    __syncwarp();
                    continue;
                }
                prefetch_if(n > 0 && w * 16 + (lane >> 1) == cta, cell + 128 - (int)ACC_SET);
                wait_clk(tsend + (n < CFG_TIMED ? CFG_DLY_BL : CFG_DLY_B));
                uint4 v, z;
                {
                    SPIN_DECL;
                    if ((CFG_SENT & 2) && n < CFG_TIMED)
                        while (__any_sync(0xffffffffu, cell_count(watch + (e1 ? 2 : 1) * ACC_TYPE) != FULL_B)) SPIN_CHECK(n);
                    while (true) {
                        v = ld_pkt(cell + ACC_TYPE); z = ld_pkt(cell + 2 * ACC_TYPE);
                        if (__all_sync(0xffffffffu, v.w == FULL_B && z.w == FULL_B)) break;
                        SPIN_CHECK(n);
                    }
                }
                x01 = badd2(x01, badd2(n01, bmul2(pack2(F(v.x) + F(z.x), F(v.y) + F(z.y)), sg2)));
                x2 = badd2(x2, badd2(n2, bmul2(pack2(F(v.z) + F(z.z), 0.f), sg2)));
                TRACES(tr + 4);
            }
        }
        {
            uint32_t b[10];
            spread(b, x01, x2, xw, xr, e2);
            float a[3][4] = {};
            const float f0 = bf_lo(x01), f1 = bf_hi(x01), f2 = e2 ? 0.f : bf_lo(x2);
            float st = fold(fmaf(f0, f0, fmaf(f1, f1, f2 * f2)), (f0 + f1) + f2, e1, 1);
#pragma unroll
            for (int i = 0; i < 5; i++) {
#pragma unroll
                for (int mt = 0; mt < 3; mt++) mma16816(a[mt], wq[i][mt][0], wq[i][mt][1], wq[i][mt][2], wq[i][mt][3], b[2 * i], b[2 * i + 1]);
                if (i < 4) st += shx(st, 2 << i);
            }
            const uint32_t pa = SM_PQ + (w >> 2) * 1024 + ((e2 ? 32 : 0) + (e1 ? 8 : 0) + g) * 16 + (w & 3) * 4;
            stsf(pa + 256, e2 ? st : e1 ? a[1][2] : a[1][0]);
            stsf(pa, e2 ? (e1 ? a[2][2] : a[2][0]) : (e1 ? a[0][2] : a[0][0]));
            if (w == 0) {
                const uint2 cs = lds64(SM_CSQ + lane * 48);
                const uint32_t qtag = lds32(SM_EPOCH) * NB + (n < 0 ? n + 5 : k);
                const char* dst = opaque(reinterpret_cast<const char*>(&g_q[n < 0 ? n + 5 : 4][h][24 * s + lane]));
                bar_sync<3, 256>();
                const uint32_t ra = SM_PQ + lane * 32;
                float S0 = sum8(lds128(ra), lds128(ra + 1024)), S1 = sum8(lds128(ra + 16), lds128(ra + 1040));
                if (n >= 0) {
                    float mean_b, rden;
                    ln_fast(shi(S0, 28), shi(S0, 24), mean_b, rden);
                    S0 = fmaf(-mean_b, F(cs.x), S0) * rden;
                    S1 = fmaf(-mean_b, F(cs.y), S1) * rden;
                }
                if (n == -1) stsf2(SM_CSQ + lane * 48, S0, S1);
                st_pkt8_if(lane < 24 && n != -1, dst, pack2(S0, S1), qtag);
                mbar_arrive_if(lane == 0 && (n == -2 || n >= 0), bar_at(B_QS));
                TRACES(n >= 0 ? tr + 5 : 95);
            } else bar_arrive<3, 256>();
            red_cell_if(n >= 0 && w * 16 + (lane >> 1) == cta, cell + 128, f0, f1, f2);
            __syncwarp();
        }
    }
}

template <int ID> __device__ __forceinline__ void role_exit() { asm volatile("exit; // %0" ::"n"(ID)); }
constexpr int NTHREADS = 512;
#define STR2(x) #x
#define STR(x) STR2(x)
__global__ void __launch_bounds__(NTHREADS, 1)
decode_kernel(const __grid_constant__ CUtensorMap tmK, const __grid_constant__ CUtensorMap tmV,
              const __grid_constant__ WeightMaps tmW, const Params p) {
    extern __shared__ __align__(1024) unsigned char smem[];
    const uint32_t t0 = now_ns();
    const int lane = threadIdx.x & 31;
    const int warp = __shfl_sync(0xffffffffu, threadIdx.x >> 5, 0);
    if (warp < 8) {
        asm volatile("setmaxnreg.inc.sync.aligned.u32 " STR(CFG_REG_CHAIN) ";");
        bar_sync<5, 480>();
        chain_role(p, warp, __shfl_sync(0xffffffffu, lane, lane), t0);
        role_exit<3>();
    } else if (warp < 12) {
        asm volatile("setmaxnreg.dec.sync.aligned.u32 " STR(CFG_REG_ATT) ";");
        if (elect_one()) {
#pragma unroll 1
            for (int i = warp - 8; i < NBAR; i += 4)
                if (i < B_W || i >= B_WC) mbar_init(bar_at(i), i == B_FIN ? 2 : i == B_PS || i == B_RP ? 4 : i >= B_F3 ? 1 : i >= B_WC ? 8 : i < B_RR || i > B_RV ? 1 : i < B_RK ? 2 : 4);
            asm volatile("fence.mbarrier_init.release.cluster;" ::: "memory");
            fence_async();
        }
        bar_sync<5, 480>();
        attention_role(p, warp - 8, lane);
        role_exit<2>();
    } else {
        asm volatile("setmaxnreg.dec.sync.aligned.u32 " STR(CFG_REG_HELP) ";");
        if (warp == 12) {
            TRACE(0);
            prefetch_role(p, &tmV, t0);
            role_exit<0>();
        } else {
            if (warp == 14) {
                if (smem_u32(smem) != SB) __trap();
                if (elect_one()) {
                    asm volatile("prefetch.tensormap [%0];" ::"l"(&tmW.q) : "memory");
                    mbar_init(bar_at(B_W), 1); mbar_init(bar_at(B_W + 1), 1); mbar_init(bar_at(B_W + 2), 1);
                    asm volatile("fence.mbarrier_init.release.cluster;" ::: "memory");
                    fence_async();
                    mbar_expect_tx(bar_at(B_W), 61440 + 15360 + 6400); mbar_expect_tx(bar_at(B_W + 1), 61440); mbar_expect_tx(bar_at(B_W + 2), 40960);
                    bulk_load(ST_X, p.x, 5120, bar_at(B_W));
                    bulk_load(ST_X + 5120, p.wr, 1280, bar_at(B_W));
                }
                reload_role(p, &tmK, &tmV, &tmW, t0);
            } else {
                unsigned ticket = 0;
                if (warp == 15 && lane == 0) asm volatile("atom.relaxed.gpu.global.add.u32 %0, [%1], 1;" : "=r"(ticket) : "l"(&g_epoch) : "memory");
                if (warp == 13 && elect_one()) {
                    asm volatile("prefetch.tensormap [%0];" ::"l"(&tmW.g) : "memory");
                    asm volatile("prefetch.tensormap [%0];" ::"l"(&tmW.u) : "memory");
                    asm volatile("prefetch.tensormap [%0];" ::"l"(&tmW.o) : "memory");
                    asm volatile("prefetch.tensormap [%0];" ::"l"(&tmK) : "memory");
                    asm volatile("prefetch.tensormap [%0];" ::"l"(&tmV) : "memory");
                }
                bar_sync<5, 480>();
                if (warp == 13) { sts32(SM_PROG, 0); bar_arrive<6, 64>(); load_role(p, &tmK, &tmV, t0); }
                else zero_role(p, lane, ticket, t0);
            }
            role_exit<1>();
        }
    }
}

typedef CUresult (*EncodeFn)(CUtensorMap*, CUtensorMapDataType, cuuint32_t, void*, const cuuint64_t*, const cuuint64_t*,
                             const cuuint32_t*, const cuuint32_t*, CUtensorMapInterleave, CUtensorMapSwizzle,
                             CUtensorMapL2promotion, CUtensorMapFloatOOBfill);

bool make_map(EncodeFn fn, CUtensorMap* m, const void* ptr, uint64_t cols, uint64_t rows, uint32_t bc, uint32_t br) {
    cuuint64_t dims[2] = {cols, rows};
    cuuint64_t strides[1] = {cols * 2};
    cuuint32_t box[2] = {bc, br};
    cuuint32_t es[2] = {1, 1};
    return fn(m, CU_TENSOR_MAP_DATA_TYPE_BFLOAT16, 2, const_cast<void*>(ptr), dims, strides, box, es, CU_TENSOR_MAP_INTERLEAVE_NONE,
              CU_TENSOR_MAP_SWIZZLE_NONE, CU_TENSOR_MAP_L2_PROMOTION_L2_128B, CU_TENSOR_MAP_FLOAT_OOB_FILL_NONE) == CUDA_SUCCESS;
}

bool make_kv_map(EncodeFn fn, CUtensorMap* m, const void* ptr) {
    cuuint64_t dims[4] = {64, 8, 3, (cuuint64_t)NB * NHEAD * SK / 8};
    cuuint64_t strides[3] = {DH * 2, 128, 8 * DH * 2};
    cuuint32_t box[4] = {64, 8, 3, 4};
    cuuint32_t es[4] = {1, 1, 1, 1};
    return fn(m, CU_TENSOR_MAP_DATA_TYPE_BFLOAT16, 4, const_cast<void*>(ptr), dims, strides, box, es, CU_TENSOR_MAP_INTERLEAVE_NONE,
              CU_TENSOR_MAP_SWIZZLE_128B, CU_TENSOR_MAP_L2_PROMOTION_L2_128B, CU_TENSOR_MAP_FLOAT_OOB_FILL_NONE) == CUDA_SUCCESS;
}

}

extern "C" void kernel_launch(void* const* d_in, const int* in_sizes, int n_in, void* d_out, int out_size) {
    (void)in_sizes; (void)n_in; (void)out_size;
    static EncodeFn fn = nullptr;
    if (!fn) {
        void* f = nullptr;
        cudaDriverEntryPointQueryResult qr;
        if (cudaGetDriverEntryPoint("cuTensorMapEncodeTiled", &f, cudaEnableDefault, &qr) != cudaSuccess || !f) return;
        fn = (EncodeFn)f;
        cudaFuncSetAttribute(decode_kernel, cudaFuncAttributeMaxDynamicSharedMemorySize, SMEM_BYTES);
    }
    CUtensorMap tmK, tmV;
    WeightMaps tmW;
    if (!make_kv_map(fn, &tmK, d_in[1]) || !make_kv_map(fn, &tmV, d_in[2])) return;
    if (!make_map(fn, &tmW.q, d_in[3], NHEAD * DH, DM, 48, 128) || !make_map(fn, &tmW.o, d_in[4], DM, NHEAD * DH, 160, 32)) return;
    if (!make_map(fn, &tmW.g, d_in[7], FF, DM, 16, 128) || !make_map(fn, &tmW.u, d_in[8], FF, DM, 16, 128)) return;
    Params p;
    p.x = (const unsigned short*)d_in[0];
    p.kc = (const char*)d_in[1];
    p.vc = (const char*)d_in[2];
    p.wq = (const char*)d_in[3];
    p.wo = (const char*)d_in[4];
    p.wr = (const unsigned short*)d_in[6];
    p.wg = (const char*)d_in[7];
    p.wu = (const char*)d_in[8];
    p.wd = (const char*)d_in[9];
    p.out = (unsigned short*)d_out;
    decode_kernel<<<NCTA, NTHREADS, SMEM_BYTES>>>(tmK, tmV, tmW, p);
}
```

```cpp
#include <cuda_runtime.h>
#include <cuda_bf16.h>
#include <cuda.h>
#include <stdint.h>

namespace {

constexpr int NB = 4, DM = 640, NHEAD = 32, DH = 192, SK = 4096, WIN = 1024, FF = 1536;
constexpr int NCTA = 128;
constexpr int TILE = 12288, PAIR = 2 * TILE;

#define CFG_LIST(X) \
    X(TICK0, 488)        \
    X(TICKA, 525)        \
    X(TICKB, 525) \
    X(TICKC, 525) \
    X(TICKD, 525) \
    X(STAG, 488)        \
    X(WLAG, 300)        \
    X(GSTEP, 700)        \
    X(PFB, 3072)        \
    X(WIN, 3)        \
    X(WIN2, 2)        \
    X(LMAX0, 100)        \
    X(LMAX, 100) \
    X(VSTEP, 300)        \
    X(RLAG, 0)        \
    X(RSTEP, 620) \
    X(RSTEP3, 450) \
    X(ZTILE, 6)        \
    X(START, 1)        \
    X(DLY_A, 300)        \
    X(DLY_AL, 100) \
    X(DLY_B, 850) \
    X(DLY_BL, 1300) \
    X(DLY_F, 500) \
    X(DLY_P, 0)        \
    X(DLY_PL, 500) \
    X(DLY_PB, 200) \
    X(DLY_Q, 100) \
    X(DLY_QL, 100) \
    X(SENT, 1)        \

#define X(n, v) constexpr int CFG_##n = v;
CFG_LIST(X)
#undef X
#define CFG(n) CFG_##n
constexpr int QUIET = 8;
#define CFG_REG_CHAIN 216
#define CFG_REG_ATT 56
#define CFG_REG_HELP 24
constexpr int KB_KV0 = 165;
__device__ __forceinline__ int kb_ns(int kb) { return kb * CFG(TICK0) / 12; }
__device__ __forceinline__ int pf_ns() { return CFG(TICK0) * CFG(PFB) / TILE; }
__device__ __forceinline__ int tick_ns(int j) {
    return j <= 16 ? CFG(TICK0) : (j & 8 ? (j & 4 ? CFG(TICKD) : CFG(TICKC)) : (j & 4 ? CFG(TICKB) : CFG(TICKA))) - (j == 63 ? pf_ns() : 0);
}
__device__ __forceinline__ int batch_ns(int k) {
    return kb_ns(KB_KV0) + 2 * pf_ns() + (k ? 16 * CFG(TICK0) + (k - 1) * 4 * (CFG(TICKA) + CFG(TICKB) + CFG(TICKC) + CFG(TICKD)) : 0);
}

__device__ __forceinline__ uint32_t slots(int k) { return k & 2 ? (k & 1 ? 0x04321658u : 0x65837104u) : (k & 1 ? 0x10482765u : 0x76543210u); }
__device__ __forceinline__ int pass_nibble(int k, int u) { return k > 0 ? 4 + (u & 1) : u; }
__device__ __forceinline__ uint32_t slot_at(uint32_t tab, int u) { return (tab >> (4 * u)) & 15; }

constexpr int NROUND = 11;
constexpr uint32_t ORD_BATCH = 0x3b9910, ORD_LAST = 0x6da, ORD_NO_HEAD = 0x248, ORD_NO_TAIL = 0x092;

constexpr uint32_t SB = 1024;
constexpr uint32_t SM_BAR = SB + 9 * PAIR;
constexpr int B_F1 = 0;
constexpr int B_RR = 24;
constexpr int B_RK = 32;
constexpr int B_RV = 36;
constexpr int B_Z = 37;
constexpr int B_EP = 38;
constexpr int B_W = 39;
constexpr int B_WC = 42;
constexpr int B_FIN = 45;
constexpr int B_F3 = 46;
constexpr int B_QS = 47;
constexpr int B_PS = 48;
constexpr int B_RP = 49;
constexpr int B_FL = 50;
constexpr int NBAR = 51;
__host__ __device__ constexpr uint32_t bar_at(int i) { return SM_BAR + 8 * i; }
constexpr uint32_t SM_EPOCH = SM_BAR + 416;
constexpr uint32_t SM_PROG = SM_EPOCH + 4;
constexpr uint32_t SM_MAX = SM_EPOCH + 16;
constexpr uint32_t SM_SUM = SM_MAX + 16;
constexpr uint32_t SM_FIN = SM_SUM + 32;
constexpr uint32_t SM_Q = SM_FIN + 32;
constexpr uint32_t PSTR = 144;
constexpr uint32_t SM_P = SM_Q + 5 * 384;
constexpr uint32_t SM_X = SM_P + 8 * PSTR;
constexpr uint32_t SM_CSG = SM_X + 40;
constexpr uint32_t SM_CSQ = SM_CSG + 32 * 48;
constexpr uint32_t SM_ONES = SM_X + 8 * 384;
constexpr uint32_t SM_PG = SM_ONES + 48;
constexpr uint32_t SM_PO = SM_PG + 1024;
constexpr uint32_t SM_PQ = SM_PO;
constexpr int SMEM_BYTES = SM_PO + 3072 - SB;
static_assert(SMEM_BYTES <= 232448 && SM_Q % 16 == 0 && SM_P % 16 == 0 && SM_X % 16 == 0 && SM_PO % 16 == 0, "smem");
constexpr uint32_t ST_WQ = SB, ST_WD = SB + 3 * PAIR, ST_WO = SB + 4 * PAIR, ST_WG = SB + 7 * PAIR, ST_X = ST_WG + 40960;

__device__ unsigned g_epoch;
__device__ unsigned g_init;
__device__ uint2 g_q[5][NHEAD][96];
__device__ uint4 g_o[2][NHEAD][8][4][4];
__device__ float4 g_acc[NB][3][64][2][8];
constexpr uint32_t ACC_TYPE = 64 * 256, ACC_SET = 3 * ACC_TYPE;
constexpr uint32_t FULL_A = 0x42040000u, FULL_B = 0x42800000u;

struct Params {
    const unsigned short* x;
    const char* kc;
    const char* vc;
    const char* wq;
    const char* wo;
    const unsigned short* wr;
    const char* wg;
    const char* wu;
    const char* wd;
    unsigned short* out;
};

__device__ __forceinline__ uint32_t smem_u32(const void* p) { return (uint32_t)__cvta_generic_to_shared(p); }
__device__ __forceinline__ void mbar_init(uint32_t a, uint32_t c) { asm volatile("mbarrier.init.shared::cta.b64 [%0], %1;" ::"r"(a), "r"(c) : "memory"); }
__device__ __forceinline__ void mbar_expect_tx(uint32_t a, uint32_t b) {
    asm volatile("mbarrier.arrive.expect_tx.shared::cta.b64 _, [%0], %1;" ::"r"(a), "r"(b) : "memory");
}
__device__ __forceinline__ void mbar_arrive(uint32_t a) { asm volatile("mbarrier.arrive.shared::cta.b64 _, [%0];" ::"r"(a) : "memory"); }
constexpr uint32_t SPIN_LIMIT = 1u << 22;
#define SPIN_DECL uint32_t spins = 0
#define SPIN_CHECK(info) { if (++spins > SPIN_LIMIT) __trap(); }
__device__ __forceinline__ void mbar_wait(uint32_t a, uint32_t parity) {
    uint32_t ok;
    SPIN_DECL;
    while (true) {
        asm volatile("{\n.reg .pred p;\nmbarrier.try_wait.parity.shared::cta.b64 p, [%1], %2;\nselp.u32 %0, 1, 0, p;\n}"
                     : "=r"(ok) : "r"(a), "r"(parity) : "memory");
        if (ok) break;
        SPIN_CHECK((a - SM_BAR) / 8 * 10 + parity);
    }
}
__device__ __forceinline__ uint32_t now_ns() { uint32_t t; asm volatile("mov.u32 %0, %%globaltimer_lo;" : "=r"(t) :: "memory"); return t; }
__device__ __forceinline__ uint32_t clk32() { uint32_t c; asm volatile("mov.u32 %0, %%clock;" : "=r"(c) :: "memory"); return c; }
__device__ __forceinline__ void wait_ns(uint32_t t) { while ((int)(now_ns() - t) < 0) {} }
__device__ __forceinline__ void wait_clk(uint32_t t) { while ((int)(clk32() - t) < 0) {} }
__device__ __forceinline__ bool elect_one() {
    uint32_t e;
    asm volatile("{\n.reg .pred p;\nelect.sync _|p, 0xffffffff;\nselp.u32 %0, 1, 0, p;\n}" : "=r"(e));
    return e;
}
constexpr uint64_t POL_FIRST = 0x12F0000000000000ull, POL_NORMAL = 0x1000000000000000ull;
__device__ __forceinline__ void tma_tile(uint32_t dst, const CUtensorMap* tm, int group, uint32_t bar, uint64_t pol) {
    asm volatile("cp.async.bulk.tensor.4d.shared::cluster.global.mbarrier::complete_tx::bytes.L2::cache_hint"
                 " [%0], [%1, {%3, %3, %3, %4}], [%2], %5;"
                 ::"r"(dst), "l"(tm), "r"(bar), "r"(0), "r"(group), "l"(pol) : "memory");
}
__device__ __forceinline__ void tma2d(uint32_t dst, const CUtensorMap* tm, int x, int y, uint32_t bar) {
    asm volatile("cp.async.bulk.tensor.2d.shared::cluster.global.mbarrier::complete_tx::bytes [%0], [%1, {%3, %4}], [%2];"
                 ::"r"(dst), "l"(tm), "r"(bar), "r"(x), "r"(y) : "memory");
}
__device__ __forceinline__ void bulk_load(uint32_t dst, const void* src, uint32_t bytes, uint32_t bar) {
    asm volatile("cp.async.bulk.shared::cluster.global.mbarrier::complete_tx::bytes [%0], [%1], %2, [%3];"
                 ::"r"(dst), "l"(src), "r"(bytes), "r"(bar) : "memory");
}
__device__ __forceinline__ void l2_prefetch(const void* p, uint32_t bytes) {
    asm volatile("cp.async.bulk.prefetch.L2.global [%0], %1;" ::"l"(p), "r"(bytes) : "memory");
}
__device__ __forceinline__ void mma16816(float (&c)[4], uint32_t a0, uint32_t a1, uint32_t a2, uint32_t a3, uint32_t b0, uint32_t b1) {
    asm volatile("mma.sync.aligned.m16n8k16.row.col.f32.bf16.bf16.f32 {%0,%1,%2,%3}, {%4,%5,%6,%7}, {%8,%9}, {%0,%1,%2,%3};"
                 : "+f"(c[0]), "+f"(c[1]), "+f"(c[2]), "+f"(c[3]) : "r"(a0), "r"(a1), "r"(a2), "r"(a3), "r"(b0), "r"(b1));
}
__device__ __forceinline__ void mma1688(float (&c)[4], uint32_t a0, uint32_t a1, uint32_t b0) {
    asm volatile("mma.sync.aligned.m16n8k8.row.col.f32.bf16.bf16.f32 {%0,%1,%2,%3}, {%4,%5}, {%6}, {%0,%1,%2,%3};"
                 : "+f"(c[0]), "+f"(c[1]), "+f"(c[2]), "+f"(c[3]) : "r"(a0), "r"(a1), "r"(b0));
}
__device__ __forceinline__ void ldsm4t(uint32_t (&r)[4], uint32_t a, uint32_t& zero) {
    asm volatile("ldmatrix.sync.aligned.m8n8.x4.trans.shared.b16 {%0,%1,%2,%3}, [%4];"
                 : "=r"(r[0]), "=r"(r[1]), "=r"(r[2]), "=r"(r[3]) : "r"(a + zero) : "memory");
    zero &= r[3];
}
__device__ __forceinline__ uint4 ld_pkt(const void* p) {
    uint4 v;
    asm volatile("{\n.reg .b128 t;\nld.relaxed.gpu.global.b128 t, [%4];\nmov.b128 {%0,%1,%2,%3}, t;\n}"
                 : "=r"(v.x), "=r"(v.y), "=r"(v.z), "=r"(v.w) : "l"(p) : "memory");
    return v;
}
__device__ __forceinline__ void st_pkt(const void* p, uint32_t a, uint32_t b, uint32_t c, uint32_t d) {
    asm volatile("{\n.reg .b128 t;\nmov.b128 t, {%1,%2,%3,%4};\nst.relaxed.gpu.global.b128 [%0], t;\n}"
                 ::"l"(p), "r"(a), "r"(b), "r"(c), "r"(d) : "memory");
}
__device__ __forceinline__ uint2 ld_pkt8(const void* p) {
    uint2 v;
    asm volatile("{\n.reg .b64 t;\nld.relaxed.gpu.global.b64 t, [%2];\nmov.b64 {%0,%1}, t;\n}" : "=r"(v.x), "=r"(v.y) : "l"(p) : "memory");
    return v;
}
__device__ __forceinline__ void red_cell(const char* p, float a, float b, float c) {
    asm volatile("red.relaxed.gpu.global.add.v4.f32 [%0], {%1,%2,%3,%4};" ::"l"(p), "f"(a), "f"(b), "f"(c), "f"(1.0f) : "memory");
}
__device__ __forceinline__ uint32_t cell_count(const char* p) {
    uint32_t c;
    asm volatile("ld.relaxed.gpu.global.u32 %0, [%1+12];" : "=r"(c) : "l"(p) : "memory");
    return c;
}
#define PRED(n) "{\n.reg .pred p;\nsetp.ne.u32 p, %" #n ", 0;\n"
__device__ __forceinline__ void red_cell_if(bool on, const char* p, float a, float b, float c) {
    asm volatile(PRED(5) "@p red.relaxed.gpu.global.add.v4.f32 [%0], {%1,%2,%3,%4};\n}"
                 ::"l"(p), "f"(a), "f"(b), "f"(c), "f"(1.0f), "r"((uint32_t)on) : "memory");
}
__device__ __forceinline__ void st_pkt8_if(bool on, const void* p, uint32_t a, uint32_t b) {
    asm volatile(PRED(3) ".reg .b64 t;\nmov.b64 t, {%1,%2};\n@p st.relaxed.gpu.global.b64 [%0], t;\n}" ::"l"(p), "r"(a), "r"(b), "r"((uint32_t)on) : "memory");
}
__device__ __forceinline__ void st_pkt_if(bool on, const void* p, uint32_t a, uint32_t b, uint32_t c, uint32_t d) {
    asm volatile(PRED(5) ".reg .b128 t;\nmov.b128 t, {%1,%2,%3,%4};\n@p st.relaxed.gpu.global.b128 [%0], t;\n}"
                 ::"l"(p), "r"(a), "r"(b), "r"(c), "r"(d), "r"((uint32_t)on) : "memory");
}
__device__ __forceinline__ void mbar_arrive_if(bool on, uint32_t a) {
    asm volatile(PRED(1) "@p mbarrier.arrive.shared::cta.b64 _, [%0];\n}" ::"r"(a), "r"((uint32_t)on) : "memory");
}
__device__ __forceinline__ void sts16_if(bool on, uint32_t a, uint32_t v) {
    asm volatile(PRED(2) "@p st.shared.u16 [%0], %1;\n}" ::"r"(a), "h"((unsigned short)v), "r"((uint32_t)on) : "memory");
}
__device__ __forceinline__ void sts32_if(bool on, uint32_t a, uint32_t v) {
    asm volatile(PRED(2) "@p st.shared.u32 [%0], %1;\n}" ::"r"(a), "r"(v), "r"((uint32_t)on) : "memory");
}
__device__ __forceinline__ void sts128_if(bool on, uint32_t a, uint32_t x, uint32_t y, uint32_t z, uint32_t w) {
    asm volatile(PRED(5) "@p st.shared.v4.u32 [%0], {%1,%2,%3,%4};\n}" ::"r"(a), "r"(x), "r"(y), "r"(z), "r"(w), "r"((uint32_t)on) : "memory");
}
__device__ __forceinline__ void prefetch_if(bool on, const void* p) {
    asm volatile(PRED(1) "@p prefetch.global.L2 [%0];\n}" ::"l"(p), "r"((uint32_t)on) : "memory");
}
__device__ __forceinline__ float fast_rcp(float x) { float r; asm("rcp.approx.ftz.f32 %0, %1;" : "=f"(r) : "f"(x)); return r; }
__device__ __forceinline__ float fast_sqrt(float x) { float r; asm("sqrt.approx.ftz.f32 %0, %1;" : "=f"(r) : "f"(x)); return r; }
__device__ __forceinline__ float fast_ex2(float x) { float r; asm("ex2.approx.ftz.f32 %0, %1;" : "=f"(r) : "f"(x)); return r; }
__device__ __forceinline__ uint32_t pack2(float lo, float hi) {
    uint32_t r;
    asm("cvt.rn.bf16x2.f32 %0, %1, %2;" : "=r"(r) : "f"(hi), "f"(lo));
    return r;
}
__device__ __forceinline__ float bfr(float x) { return __uint_as_float(pack2(0.f, x)); }
__device__ __forceinline__ uint32_t badd2(uint32_t a, uint32_t b) { uint32_t r; asm("add.rn.bf16x2 %0, %1, %2;" : "=r"(r) : "r"(a), "r"(b)); return r; }
__device__ __forceinline__ uint32_t bsub2(uint32_t a, uint32_t b) { uint32_t r; asm("sub.rn.bf16x2 %0, %1, %2;" : "=r"(r) : "r"(a), "r"(b)); return r; }
__device__ __forceinline__ uint32_t bmul2(uint32_t a, uint32_t b) { uint32_t r; asm("mul.rn.bf16x2 %0, %1, %2;" : "=r"(r) : "r"(a), "r"(b)); return r; }
__device__ __forceinline__ float bf_lo(uint32_t w) { return __uint_as_float(w << 16); }
__device__ __forceinline__ float bf_hi(uint32_t w) { return __uint_as_float(w & 0xffff0000u); }
__device__ __forceinline__ float F(uint32_t t) { return __uint_as_float(t); }
__device__ __forceinline__ uint32_t lds16(uint32_t a) { unsigned short h; asm volatile("ld.shared.u16 %0, [%1];" : "=h"(h) : "r"(a) : "memory"); return h; }
__device__ __forceinline__ uint32_t lds32(uint32_t a) { uint32_t v; asm volatile("ld.shared.u32 %0, [%1];" : "=r"(v) : "r"(a) : "memory"); return v; }
__device__ __forceinline__ uint2 lds64(uint32_t a) {
    uint2 v; asm volatile("ld.shared.v2.u32 {%0,%1}, [%2];" : "=r"(v.x), "=r"(v.y) : "r"(a) : "memory"); return v;
}
__device__ __forceinline__ uint4 lds128(uint32_t a) {
    uint4 v; asm volatile("ld.shared.v4.u32 {%0,%1,%2,%3}, [%4];" : "=r"(v.x), "=r"(v.y), "=r"(v.z), "=r"(v.w) : "r"(a) : "memory"); return v;
}
__device__ __forceinline__ float sum8(const uint4& u, const uint4& v) {
    return ((F(u.x) + F(u.y)) + (F(u.z) + F(u.w))) + ((F(v.x) + F(v.y)) + (F(v.z) + F(v.w)));
}
__device__ __forceinline__ void sts16(uint32_t a, uint32_t v) { asm volatile("st.shared.u16 [%0], %1;" ::"r"(a), "h"((unsigned short)v) : "memory"); }
__device__ __forceinline__ void sts32(uint32_t a, uint32_t v) { asm volatile("st.shared.u32 [%0], %1;" ::"r"(a), "r"(v) : "memory"); }
__device__ __forceinline__ void stsf(uint32_t a, float v) { asm volatile("st.shared.f32 [%0], %1;" ::"r"(a), "f"(v) : "memory"); }
__device__ __forceinline__ void stsf2(uint32_t a, float x, float y) { asm volatile("st.shared.v2.f32 [%0], {%1,%2};" ::"r"(a), "f"(x), "f"(y) : "memory"); }
__device__ __forceinline__ void stsf4(uint32_t a, float x, float y, float z, float w) {
    asm volatile("st.shared.v4.f32 [%0], {%1,%2,%3,%4};" ::"r"(a), "f"(x), "f"(y), "f"(z), "f"(w) : "memory");
}
template <int ID, int N> __device__ __forceinline__ void bar_sync() { asm volatile("bar.sync %0, %1;" ::"n"(ID), "n"(N) : "memory"); }
template <int ID, int N> __device__ __forceinline__ void bar_arrive() { asm volatile("bar.arrive %0, %1;" ::"n"(ID), "n"(N) : "memory"); }
__device__ __forceinline__ void fence_async() { asm volatile("fence.proxy.async.shared::cta;" ::: "memory"); }
__device__ __forceinline__ float shx(float v, int m) { return __shfl_xor_sync(0xffffffffu, v, m); }
__device__ __forceinline__ float shi(float v, int l) { return __shfl_sync(0xffffffffu, v, l); }
__device__ __forceinline__ uint32_t shi(uint32_t v, int l) { return __shfl_sync(0xffffffffu, v, l); }
__device__ __forceinline__ uint32_t opaque(uint32_t x) { asm volatile("mov.u32 %0, %0;" : "+r"(x)); return x; }
__device__ __forceinline__ const char* opaque(const char* x) { asm volatile("mov.u64 %0, %0;" : "+l"(x)); return x; }
constexpr float LOG2E = 1.4426950408889634f;

#define TRACE(idx) do {} while (0)
#define TRACES(slot) do {} while (0)

__device__ __forceinline__ int kv_group(int k, int t) {
    const int cta = blockIdx.x;
    return ((k * NHEAD + (cta >> 2)) * SK + (SK - WIN) + (cta & 3) * 256 + t * 32) / 8;
}
__device__ __forceinline__ uint32_t phase_ns() { return (((blockIdx.x >> 2) * 13) & 31) * CFG(STAG) / 32; }

__device__ __forceinline__ void prefetch_role(const Params& p, const CUtensorMap* tmV, uint32_t t0) {
    const int cta = blockIdx.x;
    t0 += phase_ns();
#pragma unroll 1
    for (int i = 0; i < 5; i++) {
        wait_ns(t0 + i * CFG(TICK0));
        if (elect_one()) l2_prefetch(p.wq + (size_t)(128 * i + cta) * 12288, 12288);
    }
#pragma unroll 1
    for (int i = 0; i < 5; i++) {
        wait_ns(t0 + kb_ns(75) + i * kb_ns(6));
        if (elect_one()) { l2_prefetch(p.wg + (128 * i + cta) * 3072, 3072); l2_prefetch(p.wu + (128 * i + cta) * 3072, 3072); }
    }
#pragma unroll 1
    for (int i = 0; i < 6; i++) {
        wait_ns(t0 + kb_ns(105) + i * kb_ns(10));
        if (elect_one()) l2_prefetch(p.wo + (size_t)((cta >> 2) * DH + 32 * i + 8 * (cta & 3)) * 1280, 10240);
    }
    bar_sync<6, 64>();
#pragma unroll 1
    for (int i = 4; i < 4 * NB; i++) {
        const int k = i >> 2, t = 12 + (i & 3);
        mbar_wait(bar_at(B_RK + ((i >> 1) & 1)), (k - 1) & 1);
        SPIN_DECL;
        while ((int)lds32(SM_PROG) <= 16 * k + t) SPIN_CHECK(i);
        if (i < 4 * NB - 1) wait_ns(t0);
        t0 = now_ns() + CFG(VSTEP);
        if (elect_one()) {
            mbar_expect_tx(bar_at(B_F1 + t), TILE);
            tma_tile(SB + slot_at(slots(k), t >> 1) * PAIR + (t & 1) * TILE, tmV, kv_group(k, t & 7), bar_at(B_F1 + t), POL_FIRST);
        }
        TRACE(256 + 16 * k + t);
    }
}

struct WeightMaps { CUtensorMap q, o, g, u; };
__device__ __forceinline__ void load_role(const Params& p, const CUtensorMap* tmK, const CUtensorMap* tmV, uint32_t t0) {
    t0 += phase_ns();
    wait_ns(t0 + kb_ns(60));
    if (elect_one()) bulk_load(ST_WD, p.wd + blockIdx.x * 15360, 15360, bar_at(B_W));
    auto ahead = [&](int j) {
        if (CFG(PFB) > 0) l2_prefetch((j & 8 ? p.vc : p.kc) + (size_t)kv_group(j >> 4, j & 7) * 3072 + (TILE - CFG(PFB)), CFG(PFB));
    };
#pragma unroll 1
    for (int j = 0; j < 2; j++) {
        wait_ns(t0 + kb_ns(KB_KV0) + j * pf_ns());
        if (elect_one()) ahead(j);
    }
#pragma unroll 1
    for (int j = 0; j < 16 * NB; j++) {
        const int k = j >> 4, t = j & 15, u = t >> 1;
        if (j == 0 || j == 8 || j == 14) mbar_wait(bar_at(B_WC + j / 7), 0);
        if (k > 0 && t < 12) {
            if (t >= 4) mbar_wait(bar_at(B_RR + t - 4), k & 1);
            else if (t >= 2) mbar_wait(bar_at(B_RP), (k - 1) & 1);
            else if (k > 1) mbar_wait(bar_at(B_RK + 3), k & 1);
            else mbar_wait(bar_at(B_RR + t), 0);
        }
        const int jw = j - CFG(WIN);
        if (jw >= 0 && (jw < 16 || (jw & 15) < 12)) mbar_wait(bar_at(B_F1 + (jw & 15)), (jw >> 4) & 1);
        const int jv = j - CFG(WIN2);
        if (jv >= 16 && (jv & 15) >= 12 && t < 12) mbar_wait(bar_at(B_F1 + (jv & 15)), (jv >> 4) & 1);
        const uint32_t dst = SB + slot_at(slots(k), t < 8 ? pass_nibble(k, u) : u) * PAIR + (t & 1) * TILE;
        t0 += j ? tick_ns(j) : batch_ns(0);
        const int late = now_ns() - t0;
        const int lmax = j < 12 ? CFG(LMAX0) : CFG(LMAX);
        if (late > lmax) t0 += late - lmax;
        wait_ns(t0);
        if (elect_one()) {
            if (k > 0 && t >= 12) {
                l2_prefetch(p.vc + (size_t)kv_group(k, t & 7) * 3072, TILE - CFG(PFB));
            } else {
                mbar_expect_tx(bar_at(B_F1 + t), TILE);
                tma_tile(dst, t & 8 ? tmV : tmK, kv_group(k, t & 7), bar_at(B_F1 + t), t < 10 && j >= 8 && j < 56 ? POL_NORMAL : POL_FIRST);
            }
            if (j + 2 < 16 * NB) ahead(j + 2);
            sts32(SM_PROG, j + 1);
        }
        TRACE(128 + j);
    }
}

__device__ __forceinline__ void reload_role(const Params& p, const CUtensorMap* tmK, const CUtensorMap* tmV, const WeightMaps* tm, uint32_t t0) {
    const int cta = blockIdx.x;
    t0 += CFG(TICK0) + CFG(WLAG) + phase_ns();
#pragma unroll 1
    for (int i = 0; i < 5; i++) {
        wait_ns(t0 + i * CFG(TICK0));
        if (elect_one()) tma2d(ST_WQ + i * 12288, &tm->q, 48 * cta, 128 * i, bar_at(B_W));
        if (i == 1) bar_sync<5, 480>();
    }
#pragma unroll 1
    for (int i = 0, o = 0; i < 10;) {
        const uint32_t now = now_ns() - t0;
        if (o < 6 && (int)now >= kb_ns(105) + o * kb_ns(10)) {
            if (elect_one()) tma2d(ST_WO + o * 10240, &tm->o, 160 * (cta & 3), (cta >> 2) * DH + 32 * o, bar_at(B_W + 1));
            o++;
        } else if ((int)now >= kb_ns(77) + i * CFG(GSTEP) && (i < 9 || o == 6)) {
            if (elect_one()) tma2d(ST_WG + (i & 1) * 20480 + (i >> 1) * 4096, i & 1 ? &tm->u : &tm->g, (12 * cta) & ~7, 128 * (i >> 1), bar_at(B_W + 2));
            i++;
        }
    }
#pragma unroll 1
    for (int k = 0; k < NB - 1; k++) {
        mbar_wait(bar_at(B_RK + 2), k & 1);
        if (elect_one()) {
            const uint32_t dst = SB + slot_at(slots(k), 2) * PAIR;
            mbar_expect_tx(bar_at(B_FL), PAIR);
            tma_tile(dst, tmV, kv_group(k, 0), bar_at(B_FL), POL_FIRST);
            tma_tile(dst + TILE, tmV, kv_group(k, 1), bar_at(B_FL), POL_FIRST);
        }
        mbar_wait(bar_at(B_RV), k & 1);
        uint32_t due = now_ns() + (k == NB - 2 ? 0 : CFG(RLAG));
        if (elect_one()) mbar_expect_tx(bar_at(B_F3), 4 * PAIR);
#pragma unroll 1
        for (int t = 0; t < 8; t++) {
            wait_ns(due);
            due += k == NB - 2 ? CFG(RSTEP3) : CFG(RSTEP);
            if (elect_one())
                tma_tile(SB + slot_at(slots(k + 1), t >> 1) * PAIR + (t & 1) * TILE, tmK, kv_group(k + 1, t), bar_at(B_F3), POL_FIRST);
        }
        TRACE(121 + k);
    }
}

__device__ __forceinline__ void zero_role(const Params& p, int lane, unsigned ticket, uint32_t t0) {
    const int cta = blockIdx.x;
    const uint32_t epoch = __shfl_sync(0xffffffffu, ticket, 0) / NCTA + 1;
    if (lane == 0) { sts32(SM_EPOCH, epoch); mbar_arrive(bar_at(B_EP)); }
#pragma unroll 1
    for (int k = 0; k < NB + 2; k++) {
        lane = opaque(lane);
        const int cl = 2 * (cta & 15) + (lane & 1);
        const int col = 80 * (cta >> 4) + (cl & 2 ? 48 : 0) + (cl >> 2) + (cl & 1 ? 8 : 0);
        const char* own = reinterpret_cast<const char*>(g_acc) + (cta >> 4) * 2048 + (cl >> 2) * 256 + (cl & 3) * 16;
        if (k < NB) {
            wait_ns(t0 + batch_ns(k) + CFG(ZTILE) * CFG(TICK0));
            const int lg = lane >> 3, ty = (lane & 7) >> 1;
            const char* dst = own + (k - (lg >> 1)) * (int)ACC_SET + ty * ACC_TYPE + (lg ? 128 : 0);
            uint32_t v0 = 0, v1 = 0, v2 = 0, v3 = 0;
            if (lane < 2) {
                const unsigned short* xp = p.x + k * DM + col;
                v0 = __ldg(xp) << 16; v1 = __ldg(xp + 16) << 16; v2 = cl & 2 ? 0 : __ldg(xp + 32) << 16; v3 = 0x3f800000u;
            }
            if (ty < 3 && (lg == 0 || (lg == 1 && (ty == 0 || k == NB - 1)) || (lg == 2 && k > 0 && ty > 0))) st_pkt(dst, v0, v1, v2, v3);
            asm volatile("fence.acq_rel.gpu;" ::: "memory");
            __syncwarp();
            if (lane == 0) asm volatile("red.relaxed.gpu.global.add.u32 [%0], 1;" ::"l"(&g_init) : "memory");
            const uint32_t target = ((epoch - 1) * NB + k + 1) * NCTA;
            SPIN_DECL;
            while (true) {
                __nanosleep(400);
                uint32_t v;
                asm volatile("ld.acquire.gpu.global.u32 %0, [%1];" : "=r"(v) : "l"(&g_init) : "memory");
                if (__all_sync(0xffffffffu, (int)(v - target) >= 0)) break;
                SPIN_CHECK(v);
            }
        }
        uint4 r;
        if (k == 1) mbar_wait(bar_at(B_RK), 0);
        if (k > 1) {
            mbar_wait(bar_at(B_FIN), k & 1);
            r = lds128(SM_FIN + (lane & 1) * 16);
        }
        __syncwarp();
        if (lane == 0) mbar_arrive(bar_at(B_Z));
        if (k > 1) {
            const int b = k - 2;
            const char* src = own + b * ACC_SET + (1 + ((lane >> 1) & 1)) * ACC_TYPE + 128;
            unsigned short* o = p.out + b * DM + col;
            wait_clk(clk32() + CFG(DLY_F));
            uint4 v = {};
            SPIN_DECL;
            while (true) {
                v = ld_pkt(src);
                if (__all_sync(0xffffffffu, v.w == FULL_B)) break;
                SPIN_CHECK(k);
            }
            const float y0 = F(v.x) + shx(F(v.x), 2), y1 = F(v.y) + shx(F(v.y), 2), y2 = F(v.z) + shx(F(v.z), 2);
            const uint32_t x01 = badd2(r.x, badd2(r.y, bmul2(pack2(y0, y1), r.w)));
            const uint32_t x2 = badd2(r.z, badd2(r.z >> 16, bmul2(pack2(y2, 0.f), r.w)));
            if (lane < 2) {
                o[0] = x01; o[16] = x01 >> 16;
                if (!(cl & 2)) o[32] = x2;
            }
            TRACES((2 * b + 1) * 6 + 4);
        }
    }
}

__host__ __device__ constexpr uint32_t desc_lo(uint32_t addr) { return ((addr & 0x3FFFFu) >> 4) | (1u << 16); }
constexpr uint32_t DESC_HI_TILE = (3072u >> 4) | (1u << 30);
constexpr uint32_t DESC_HI_VEC = 1u;
template <int TA, int AOFF, int BOFF>
__device__ __forceinline__ void wgmma_n8(float (&d)[4], uint32_t alo, uint32_t blo, int accumulate) {
    asm volatile("{\n.reg .pred p;\n.reg .b32 a, b;\n.reg .b64 da, db;\nsetp.ne.b32 p, %6, 0;\n"
                 "add.u32 a, %4, %8;\nadd.u32 b, %5, %9;\nmov.b64 da, {a, %10};\nmov.b64 db, {b, %11};\n"
                 "wgmma.mma_async.sync.aligned.m64n8k16.f32.bf16.bf16 {%0,%1,%2,%3}, da, db, p, 1, 1, %7, 0;\n}"
                 : "+f"(d[0]), "+f"(d[1]), "+f"(d[2]), "+f"(d[3])
                 : "r"(alo), "r"(blo), "r"(accumulate), "n"(TA), "n"(AOFF >> 4), "n"(BOFF >> 4), "n"(DESC_HI_TILE), "n"(DESC_HI_VEC));
}
template <int KS>
__device__ __forceinline__ void qk_steps(float (&d)[4], uint32_t alo, uint32_t blo) {
    if constexpr (KS < 12) {
        wgmma_n8<0, (KS >> 2) * 1024 + (KS & 3) * 32, KS * 32>(d, alo, blo, KS > 0);
        qk_steps<KS + 1>(d, alo, blo);
    }
}
__device__ __forceinline__ void pv_steps(float (&e)[3][4], uint32_t alo, uint32_t blo, int acc) {
    wgmma_n8<1, 0, 0>(e[0], alo, blo, acc); wgmma_n8<1, 1024, 0>(e[1], alo, blo, acc); wgmma_n8<1, 2048, 0>(e[2], alo, blo, acc);
    wgmma_n8<1, 6144, 32>(e[0], alo, blo, 1); wgmma_n8<1, 7168, 32>(e[1], alo, blo, 1); wgmma_n8<1, 8192, 32>(e[2], alo, blo, 1);
}
__device__ __forceinline__ void wg_fence() { asm volatile("wgmma.fence.sync.aligned;" ::: "memory"); }
__device__ __forceinline__ void wg_commit() { asm volatile("wgmma.commit_group.sync.aligned;" ::: "memory"); }
template <int N> __device__ __forceinline__ void wg_wait() { asm volatile("wgmma.wait_group.sync.aligned %0;" ::"n"(N) : "memory"); }
__device__ __forceinline__ void qk_pair(float (&d)[4], uint32_t slot, uint32_t qslot) {
    wg_fence();
    qk_steps<0>(d, desc_lo(SB) + slot * (PAIR >> 4), desc_lo(SM_Q) + qslot * (384 >> 4));
    wg_commit();
}
__device__ __forceinline__ void acc_ready(float (&d)[4]) { asm volatile("" : "+f"(d[0]), "+f"(d[1]), "+f"(d[2]), "+f"(d[3]) :: "memory"); }
__device__ __forceinline__ uint32_t score_pair(float (&d)[4], int lane) {
    acc_ready(d);
    const float scale = 0.07216878364870322f;
    const uint32_t r = pack2(d[0], d[2]);
    return shi(pack2(bf_lo(r) * scale, bf_hi(r) * scale), lane & 28);
}

__device__ __forceinline__ void attention_role(const Params& p, int w, int lane) {
    const int cta = blockIdx.x, t4 = lane & 3, g = lane >> 2;
    mbar_wait(bar_at(B_EP), 0);
    const uint32_t tag0 = lds32(SM_EPOCH) * NB;
    const char* const qsrc = reinterpret_cast<const char*>(&g_q[0][cta >> 2][min(w * 32 + lane, 95)]);
    const char* const odst = reinterpret_cast<const char*>(&g_o[0][cta >> 2][2 * w + (g >> 2)][cta & 3][g & 3]);
    const uint32_t pdst = SM_P + t4 * PSTR + (16 * w + g) * 2;
    auto get_q = [&](int slot, uint32_t tag) {
        if (w < 3) {
            uint2 v;
            SPIN_DECL;
            while (true) {
                v = ld_pkt8(qsrc + slot * sizeof(g_q[0]));
                if (__all_sync(0xffffffffu, v.y == tag)) break;
                SPIN_CHECK(slot);
            }
            sts32(SM_Q + slot * 384 + (w * 32 + lane) * 4, v.x);
            fence_async();
        }
        bar_sync<4, 128>();
    };
    auto softmax = [&](uint32_t sc, int ps) -> uint32_t {
        const float s0 = bf_lo(sc), s1 = bf_hi(sc);
        int key = __float_as_int(fmaxf(s0, s1));
        key ^= (key >> 31) & 0x7fffffff;
        key = __reduce_max_sync(0xffffffffu, key);
        sts32(SM_MAX + w * 4, key);
        bar_sync<4, 128>();
        const uint4 mx = lds128(SM_MAX);
        key = max(max((int)mx.x, (int)mx.y), max((int)mx.z, (int)mx.w));
        key ^= (key >> 31) & 0x7fffffff;
        const float mb = __int_as_float(key) * LOG2E;
        const uint32_t pp = pack2(fast_ex2(fmaf(s0, LOG2E, -mb)), fast_ex2(fmaf(s1, LOG2E, -mb)));
        sts16(pdst + ps * 4 * PSTR, pp); sts16(pdst + ps * 4 * PSTR + 16, pp >> 16);
        uint32_t fs;
        asm volatile("redux.sync.add.u32 %0, %1, 0xffffffff;" : "=r"(fs) : "r"(__float2uint_rn((bf_lo(pp) + bf_hi(pp)) * 8388608.f)));
        fence_async();
        bar_sync<4, 128>();
        sts32(SM_SUM + ps * 16 + w * 4, fs);
        return key;
    };
    auto aux_word = [&](uint32_t mx, const uint4& u, int k) {
        const float l = __uint2float_rn((u.x + u.y) + (u.z + u.w)) * (1.f / 8388608.f);
        return (g < 4 ? mx : (__float_as_uint(l) + 0x80u) & 0xffffff00u) | ((tag0 + k) & 0xffu);
    };
    auto send = [&](float (&e)[3][4], uint32_t aux, int ps) {
        acc_ready(e[0]); acc_ready(e[1]); acc_ready(e[2]);
        st_pkt_if(t4 == 0, odst + ps * sizeof(g_o[0]), pack2(e[0][0], e[0][2]), pack2(e[1][0], e[1][2]), pack2(e[2][0], e[2][2]), aux);
        mbar_arrive_if(lane == 0, bar_at(ps ? B_RV : B_PS));
    };
    mbar_wait(bar_at(B_QS), 0);
#pragma unroll 1
    for (int b = 0; b < NB; b++) { TRACES(84 + b); get_q(b, tag0 + b); }
    TRACES(73);
#pragma unroll 1
    for (int it = 0; it <= NB; it++) {
        uint32_t m1 = 0;
        if (it < NB) {
            const uint32_t tab = slots(it);
            uint32_t sc = 0;
#pragma unroll 1
            for (int t = 0; t < 8; t++) {
                const uint32_t alo = desc_lo(SB) + slot_at(tab, pass_nibble(it, t >> 1)) * (PAIR >> 4), blo = desc_lo(SM_Q) + it * (384 >> 4);
                mbar_wait(bar_at(B_F1 + t), it & 1);
                float d[4] = {};
#pragma unroll 1
                for (int c = 0; c < 3; c++) {
                    wg_fence();
                    wgmma_n8<0, 0, 0>(d, alo + c * 64, blo + c * 8, c > 0); wgmma_n8<0, 32, 32>(d, alo + c * 64, blo + c * 8, 1);
                    wgmma_n8<0, 64, 64>(d, alo + c * 64, blo + c * 8, 1); wgmma_n8<0, 96, 96>(d, alo + c * 64, blo + c * 8, 1);
                    wg_commit();
                    wg_wait<0>();
                }
                if ((t & 1) == (w >> 1)) {
                    mbar_arrive_if(lane == 0, bar_at(B_RR + t));
                    const uint32_t s = score_pair(d, lane);
                    if (t4 == t >> 1) sc = s;
                }
            }
            m1 = softmax(sc, 0);
        }
        if (it > 0) {
            const int k = it - 1;
            const uint32_t tab = slots(k);
            const uint32_t v0 = slot_at(tab, k < NB - 1 ? 2 : 4);
            TRACES(48 + k * 6);
            if (k > 0) mbar_wait(bar_at(B_F3), it & 1);
            mbar_wait(bar_at(B_QS), it & 1);
            wait_clk(clk32() + (k < NB - 1 ? CFG(DLY_QL) : CFG(DLY_Q)));
            get_q(4, tag0 + k);
            TRACES(49 + k * 6);
            float d[4][4] = {};
#pragma unroll
            for (int u = 0; u < 4; u++) {
                qk_pair(d[u], slot_at(tab, u), 4);
                if (u > 0) { wg_wait<1>(); mbar_arrive_if(lane == 0, bar_at(B_RK + u - 1)); }
            }
            uint32_t sc = score_pair(d[0], lane), s = score_pair(d[1], lane);
            if (t4 == 1) sc = s;
            s = score_pair(d[2], lane);
            if (t4 == 2) sc = s;
            wg_wait<0>();
            s = score_pair(d[3], lane);
            mbar_arrive_if(lane == 0, bar_at(B_RK + 3));
            if (t4 == 3) sc = s;
            TRACES(50 + k * 6);
            const uint32_t m2 = softmax(sc, 1);
            TRACES(51 + k * 6);
            float e[3][4] = {};
            uint4 u;
            wg_fence();
#pragma unroll
            for (int t = 0; t < 8; t++) {
                const int pr = ((t >> 1) + 1) & 3;
                if (t == 6 && k < NB - 1) mbar_wait(bar_at(B_FL), k & 1);
                if (t == 7) { bar_sync<4, 128>(); u = lds128(SM_SUM + 16); }
                if (t == 6) wg_fence();
                pv_steps(e, desc_lo(SB + (t & 1) * TILE) + (pr ? slot_at(tab, 4 + pr) : v0) * (PAIR >> 4), desc_lo(SM_P + (4 + pr) * PSTR + (t & 1) * 64), t > 0);
                if (t == 0) st_pkt_if(t4 == 0, odst + sizeof(g_o[0]), 0, 0, 0, tag0 + k + 128);
            }
            wg_commit();
            const uint32_t aux = opaque(aux_word(m2, u, k));
            wg_wait<0>();
            send(e, aux, 1);
            TRACES(52 + k * 6);
        }
        if (it < NB) {
            const uint32_t tab = slots(it);
            st_pkt_if(t4 == 0, odst, 0, 0, 0, tag0 + it + 128);
            bar_sync<4, 128>();
            const uint32_t aux = opaque(aux_word(m1, lds128(SM_SUM), it));
            float e[3][4] = {};
#pragma unroll 1
            for (int u = 0; u < 4; u++) {
                const uint32_t alo = desc_lo(SB) + slot_at(tab, 4 + u) * (PAIR >> 4), blo = desc_lo(SM_P) + u * (PSTR >> 4);
                mbar_wait(bar_at(B_F1 + 8 + 2 * u), it & 1);
                wg_fence();
                pv_steps(e, alo, blo, u > 0);
                wg_commit();
                if (u == 1) { wg_wait<1>(); mbar_arrive_if(lane == 0, bar_at(B_RP)); }
                mbar_wait(bar_at(B_F1 + 9 + 2 * u), it & 1);
                wg_fence();
                pv_steps(e, alo + (TILE >> 4), blo + 4, 1);
                wg_commit();
            }
            wg_wait<0>();
            send(e, aux, 0);
            TRACES(53 + it * 6);
        }
    }
}

__device__ __forceinline__ void ln_finish(float s, float q, float& mean_b, float& rden) {
    const float mean = s * (1.f / DM);
    const float var = fmaxf(fmaf(q, 1.f / DM, -mean * mean), 0.f);
    mean_b = bfr(mean);
    rden = fast_rcp(bfr(fast_sqrt(bfr(bfr(var) + 1e-5f))));
}
__device__ __forceinline__ void ln_fast(float s, float q, float& mean, float& rstd) {
    mean = s * (1.f / DM);
    asm("rsqrt.approx.ftz.f32 %0, %1;" : "=f"(rstd) : "f"(fmaxf(fmaf(-mean, mean, fmaf(q, 1.f / DM, 1e-5f)), 1e-5f)));
}
__device__ __forceinline__ uint32_t ln_apply(uint32_t w, float mean_b, float rden) {
    const uint32_t d = bsub2(w, __byte_perm(__float_as_uint(mean_b), 0, 0x3232));
    return pack2(bf_lo(d) * rden, bf_hi(d) * rden);
}
__device__ __forceinline__ void spread(uint32_t (&b)[10], uint32_t x01, uint32_t x2, uint32_t wa, uint32_t ra, bool e2) {
    sts16(wa, x01); sts16(wa + 8, x01 >> 16);
    sts16_if(!e2, wa + 16, x2);
    __syncwarp();
    const uint4 u = lds128(ra), v = lds128(ra + 16);
    const uint2 z = lds64(ra + 32);
    b[0] = u.x; b[1] = u.y; b[2] = u.z; b[3] = u.w; b[4] = v.x; b[5] = v.y; b[6] = v.z; b[7] = v.w; b[8] = z.x; b[9] = z.y;
}
__device__ __forceinline__ float fold(float a, float b, bool sel, int m) { return (sel ? b : a) + shx(sel ? a : b, m); }

__device__ __forceinline__ void chain_role(const Params& p, int w, int lane, uint32_t t0) {
    const int cta = blockIdx.x, h = cta >> 2, s = cta & 3;
    const int g = lane >> 2, t4 = lane & 3;
    const bool e1 = t4 & 1, e2 = t4 & 2;
    uint32_t wq[5][3][4], wo[3][5][4], wg[5][4], wh[5][2], wd[4][4];
    const int col0 = 80 * w + (e2 ? 48 : 0) + g + (e1 ? 8 : 0);
    const uint32_t xw = opaque(SM_X + w * 384 + 48 * (g >> 1) + (e2 ? 24 : 0) + (e1 ? 4 : 0) + 2 * (g & 1));
    const uint32_t xr = opaque(g == 1 ? SM_ONES : SM_X + w * 384 + (g == 3 ? 192 : 0) + 48 * t4);
    TRACES(75);
    sts32_if(lane < 12, SM_ONES + lane * 4, 0x3f803f80u);
    uint32_t zero = lane >> 5;
    const int mi = lane >> 3, mr = lane & 7;
    mbar_wait(bar_at(B_W), 0);
    TRACES(74);
    sts16(xw + 192, lds16(ST_X + 5120 + col0 * 2)); sts16(xw + 200, lds16(ST_X + 5120 + col0 * 2 + 32));
    sts16_if(!e2, xw + 208, lds16(ST_X + 5120 + col0 * 2 + 64));
#pragma unroll
    for (int i = 0; i < 5; i++)
#pragma unroll
        for (int mt = 0; mt < 3; mt++) ldsm4t(wq[i][mt], ST_WQ + (80 * w + 16 * i + mr + 8 * (mi >> 1)) * 96 + 32 * mt + 16 * (mi & 1), zero);
    const bool odd = cta & 1;
    const uint32_t lo = ST_WD + (mr + (odd ? 4 : 0)) * 1280 + 160 * w, hi = ST_WD + ((mr & 3) + (odd ? 0 : 8)) * 1280 + 160 * w;
    ldsm4t(wd[0], lo + 16 * mi, zero);
    ldsm4t(wd[1], lo + 64 + 16 * mi, zero);
    ldsm4t(wd[2], hi + 64 * (mi >> 1) + 32 * (mr >> 2) + 16 * (mi & 1), zero);
    ldsm4t(wd[3], (mi < 2 ? lo : hi) + 128 + 16 * (mi & 1), zero);
    fence_async();
    __syncwarp();
    mbar_arrive_if(lane == 0, bar_at(B_WC));
    mbar_wait(bar_at(B_EP), 0);
    uint32_t x01 = 0, x2 = 0;
#pragma unroll 1
    for (int n = -5; n < NROUND; n++) {
        const bool last = (ORD_LAST >> (n & 15)) & 1, head = !((ORD_NO_HEAD >> (n & 15)) & 1);
        const int k = (ORD_BATCH >> (2 * (n & 15))) & 3;
        if (!last) bar_sync<2, 256>();
        TRACES(n <= 0 ? 83 + n : 95);
        const char* const slice = reinterpret_cast<const char*>(g_acc) + k * ACC_SET + (last ? 128 : 0) + w * 2048;
        const char* const cell = opaque(slice + g * 256 + t4 * 16);
        const char* const watch = slice + (cta & 7) * 256 + ((cta >> 3) & 3) * 16;
        if (n >= 0) {
          uint4 v;
          if (head) {
            if (!last || n == NROUND - 1) mbar_wait(bar_at(B_Z), (k + last) & 1);
            const uint4* src = &g_o[last][h][w & 6][g & 3][t4];
            const uint32_t tag = lds32(SM_EPOCH) * NB + k;
            mbar_wait(bar_at(last ? B_RV : B_PS), k & 1);
            wait_clk(clk32() + (n < QUIET ? (last ? CFG(DLY_PB) : CFG(DLY_PL)) : CFG(DLY_P)));
            if (!last && k < NB - 1) wait_ns(t0 + batch_ns(k + 1) + CFG(START));
            uint4 z;
            {
                SPIN_DECL;
                while (true) {
                    v = ld_pkt(src); z = ld_pkt(src + 16);
                    if (__all_sync(0xffffffffu, (((v.w ^ tag) | (z.w ^ tag)) & 0xffu) == 0)) break;
                    SPIN_CHECK(n);
                }
            }
            TRACES(tr + 0);
            float a[3][4] = {};
            const uint32_t bb[3][2] = {{v.x, v.y}, {z.x, z.y}, {v.z, z.z}};
            float sa, sb;
#pragma unroll
            for (int i = 0; i < 3; i++) {
                const uint32_t l0 = g < 4 ? bb[i][0] : 0, l1 = g < 4 ? bb[i][1] : 0, h0 = g < 4 ? 0 : bb[i][0], h1 = g < 4 ? 0 : bb[i][1];
#pragma unroll
                for (int mt = 0; mt < 5; mt++)
                    mma16816(a[mt % 3], wo[i][mt][0], wo[i][mt][1], wo[i][mt][2], wo[i][mt][3], mt < 3 ? l0 : h0, mt < 3 ? l1 : h1);
                if (i == 0) {
                    const float am = F(v.w & 0xffffff00u), al = F(z.w & 0xffffff00u);
                    const float m0 = shi(am, 0), m1 = shi(am, 4), m2 = shi(am, 8), m3 = shi(am, 12);
                    const float s0 = shi(al, 0), s1 = shi(al, 4), s2 = shi(al, 8), s3 = shi(al, 12);
                    const float mb = fmaxf(fmaxf(m0, m1), fmaxf(m2, m3)) * LOG2E;
                    const float w0 = fast_ex2(fmaf(m0, LOG2E, -mb)), w1 = fast_ex2(fmaf(m1, LOG2E, -mb));
                    const float w2 = fast_ex2(fmaf(m2, LOG2E, -mb)), w3 = fast_ex2(fmaf(m3, LOG2E, -mb));
                    const float rl = fast_rcp(fmaf(w0, s0, w1 * s1) + fmaf(w2, s2, w3 * s3));
                    sa = (e1 ? w2 : w0) * rl; sb = (e1 ? w3 : w1) * rl;
                }
            }
            float y[3];
#pragma unroll
            for (int j = 2; j < 5; j++) {
                const int mt = j % 3;
                y[mt] = fold(fmaf(a[mt][0], sa, a[mt][1] * sb), fmaf(a[mt][2], sa, a[mt][3] * sb), e1, 1);
            }
            const uint32_t pa = SM_PO + w * 512 + lane * 16;
            if (w < 2) {
                const char* dst = opaque(cell + s * 4096);
                bar_sync<1, 256>();
                const uint4 c1 = lds128(pa), c2 = lds128(pa + 1024), c3 = lds128(pa + 2048);
                red_cell(dst, (y[0] + F(c1.x)) + (F(c2.x) + F(c3.x)), (y[1] + F(c1.y)) + (F(c2.y) + F(c3.y)), (y[2] + F(c1.z)) + (F(c2.z) + F(c3.z)));
            } else {
                stsf4(pa - 1024, y[0], y[1], y[2], 0.f);
                bar_sync<1, 256>();
            }
            TRACES(tr + 1);
            if ((ORD_NO_TAIL >> n) & 1) continue;
            wait_clk(clk32() + (w < 2 ? 0 : 60) + (n < QUIET ? CFG(DLY_AL) : CFG(DLY_A)));
          }
            {
                SPIN_DECL;
                if ((CFG(SENT) & 1) && n < QUIET && head) while (__any_sync(0xffffffffu, cell_count(watch) != FULL_A)) SPIN_CHECK(n);
                while (true) {
                    v = ld_pkt(cell);
                    if (__all_sync(0xffffffffu, v.w == FULL_A)) break;
                    SPIN_CHECK(n);
                }
            }
            TRACES(tr + 2);
            x01 = pack2(F(v.x), F(v.y));
            x2 = pack2(F(v.z), 0.f);
        } else if (n == -1) {
            mbar_wait(bar_at(B_W + 1), 0);
            const uint32_t ln = opaque(lane);
            const int mi = ln >> 3, mr = ln & 7;
            uint32_t zero = ln >> 5;
            TRACES(76);
#pragma unroll
            for (int i = 0; i < 3; i++) {
                const int d = 16 * (w >> 1) + (mr >> 1) + 8 * (mr & 1) + (i < 2 ? 64 * (mi >> 1) + 4 * i : 128 + 4 * (mi >> 1));
#pragma unroll
                for (int mt = 0; mt < 5; mt++) ldsm4t(wo[i][mt], ST_WO + d * 320 + 160 * (w & 1) + 32 * mt + 16 * (mi & 1), zero);
            }
            fence_async();
            __syncwarp();
            mbar_arrive_if(lane == 0, bar_at(B_WC + 1));
            mbar_wait(bar_at(B_W + 2), 0);
            TRACES(77);
#pragma unroll
            for (int i = 0; i < 5; i++) {
                const uint32_t ga = ST_WG + (mi & 1) * 20480 + (80 * w + 16 * i + mr + 8 * (mi >> 1)) * 32;
                uint32_t r[4];
                ldsm4t(wg[i], ga + (odd ? 16 : 0), zero);
                ldsm4t(r, ga + (odd ? 0 : 16), zero);
#pragma unroll
                for (int kh = 0; kh < 2; kh++) {
                    const uint32_t moved = __shfl_xor_sync(0xffffffffu, odd ? r[2 * kh] : r[2 * kh + 1], 16);
                    wh[i][kh] = (g < 4) == odd ? moved : odd ? r[2 * kh + 1] : r[2 * kh];
                }
            }
            fence_async();
            __syncwarp();
            mbar_arrive_if(lane == 0, bar_at(B_WC + 2));
            TRACES(72);
            x01 = 0x3f803f80u; x2 = 0x3f80u;
        } else {
            const uint32_t xa = ST_X + (n + 5) * 1280, ln = opaque(lane);
            const int col0 = 80 * w + (ln & 2 ? 48 : 0) + (ln >> 2) + (ln & 1 ? 8 : 0);
            float sm = 0.f, sq = 0.f;
#pragma unroll
            for (int i = 0; i < 5; i++) {
                const uint2 c = lds64(xa + i * 256 + ln * 8);
                sm += (bf_lo(c.x) + bf_hi(c.x)) + (bf_lo(c.y) + bf_hi(c.y));
                sq = fmaf(bf_lo(c.x), bf_lo(c.x), fmaf(bf_hi(c.x), bf_hi(c.x), fmaf(bf_lo(c.y), bf_lo(c.y), fmaf(bf_hi(c.y), bf_hi(c.y), sq))));
            }
            x01 = lds16(xa + col0 * 2) | lds16(xa + col0 * 2 + 32) << 16;
            x2 = lds16(xa + col0 * 2 + 64);
#pragma unroll
            for (int o = 16; o; o >>= 1) { sm += shx(sm, o); sq += shx(sq, o); }
            float mean_b, rden;
            ln_finish(sm, sq, mean_b, rden);
            x01 = ln_apply(x01, mean_b, rden);
            x2 = ln_apply(x2, mean_b, rden);
        }
        if (n >= -1) {
            uint32_t b[10];
            spread(b, x01, x2, xw, xr, e2);
            float a[2][4] = {};
#pragma unroll
            for (int i = 0; i < 5; i++) {
                mma16816(a[0], wg[i][0], wg[i][1], wg[i][2], wg[i][3], b[2 * i], b[2 * i + 1]);
                mma16816(a[1], wh[i][0], b[2 * i], wh[i][1], b[2 * i + 1], b[2 * i], b[2 * i + 1]);
            }
            stsf(SM_PG + (w >> 2) * 512 + (g + 8 * t4) * 16 + (w & 3) * 4, e2 ? (e1 ? a[1][2] : a[1][0]) : (e1 ? a[0][2] : a[0][0]));
            const uint2 cs = lds64(SM_CSG + lane * 48);
            const char* dst = opaque(cell + (1 + (cta & 1)) * ACC_TYPE);
            bar_sync<2, 256>();
            const float S = sum8(lds128(SM_PG + lane * 16), lds128(SM_PG + 512 + lane * 16));
            const float sx = shi(S, 25), sq = shi(S, 24), Su = shi(S, lane + (lane < 16 ? 8 : 4));
            if (n < 0) {
                if (w == 0) stsf2(SM_CSG + lane * 48, S, Su);
            } else {
                float mean_b, rden;
                ln_fast(sx, sq, mean_b, rden);
                const float gv = bfr(fmaf(-mean_b, F(cs.x), S) * rden), uv = bfr(fmaf(-mean_b, F(cs.y), Su) * rden);
                const float sg = fast_rcp(1.f + fast_ex2(-LOG2E * gv));
                const uint32_t hb = pack2(bfr(gv * sg) * uv, 0.f);
                const uint32_t b0 = __byte_perm(shi(hb, 2 * t4), shi(hb, 2 * t4 + 1), 0x5410);
                const uint32_t b1 = __byte_perm(shi(hb, e1 ? 18 : 16), shi(hb, e1 ? 19 : 17), 0x5410);
                const bool up = g >= 4;
                const uint32_t l0 = up ? 0 : b0, h0 = up ? b0 : 0;
                float d[3][4] = {};
                mma1688(d[0], wd[0][0], wd[0][1], l0); mma1688(d[1], wd[0][2], wd[0][3], l0); mma1688(d[2], wd[1][0], wd[1][1], l0);
                mma1688(d[0], wd[1][2], wd[1][3], h0); mma1688(d[1], wd[3][0], wd[3][1], h0);
                mma1688(d[2], wd[2][2], wd[2][3], up || e2 ? 0 : b1); mma1688(d[0], wd[2][0], wd[2][1], up || e2 ? 0 : b1);
                mma1688(d[1], wd[2][0], wd[2][1], !up && e2 ? b1 : 0);
                mma1688(d[0], wd[2][2], wd[2][3], up && e2 ? b1 : 0); mma1688(d[1], wd[3][2], wd[3][3], up && !e2 ? b1 : 0);
                red_cell(dst, e1 ? d[0][2] : d[0][0], e1 ? d[1][2] : d[1][0], e1 ? d[2][2] : d[2][0]);
                const uint32_t tsend = clk32();
                TRACES(tr + 3);
                if (last && w != cta >> 4) continue;
                if (!last && w == 0) st_pkt8_if(lane < 24, &g_q[4][h][24 * s + lane], 0, 0);
                const float sgr = shi(sg, 27);
                const uint32_t sg2 = pack2(sgr, sgr);
                const uint32_t n01 = opaque(pack2((bf_lo(x01) - mean_b) * rden, (bf_hi(x01) - mean_b) * rden));
                const uint32_t n2 = opaque(pack2((bf_lo(x2) - mean_b) * rden, 0.f));
                if (last) {
                    sts128_if(lane >> 1 == (cta & 15), SM_FIN + (lane & 1) * 16, x01, n01, __byte_perm(x2, n2, 0x5410), sg2);
                    mbar_arrive_if(lane >> 1 == (cta & 15), bar_at(B_FIN));
                    __syncwarp();
                    continue;
                }
                prefetch_if(n > 0 && w * 16 + (lane >> 1) == cta, cell + 128 - (int)ACC_SET);
                wait_clk(tsend + (n < QUIET ? CFG(DLY_BL) : CFG(DLY_B)));
                uint4 v, z;
                {
                    SPIN_DECL;
                    if ((CFG(SENT) & 2) && n < QUIET)
                        while (__any_sync(0xffffffffu, cell_count(watch + (e1 ? 2 : 1) * ACC_TYPE) != FULL_B)) SPIN_CHECK(n);
                    while (true) {
                        v = ld_pkt(cell + ACC_TYPE); z = ld_pkt(cell + 2 * ACC_TYPE);
                        if (__all_sync(0xffffffffu, v.w == FULL_B && z.w == FULL_B)) break;
                        SPIN_CHECK(n);
                    }
                }
                x01 = badd2(x01, badd2(n01, bmul2(pack2(F(v.x) + F(z.x), F(v.y) + F(z.y)), sg2)));
                x2 = badd2(x2, badd2(n2, bmul2(pack2(F(v.z) + F(z.z), 0.f), sg2)));
                TRACES(tr + 4);
            }
        }
        {
            uint32_t b[10];
            spread(b, x01, x2, xw, xr, e2);
            float a[3][4] = {};
            const float f0 = bf_lo(x01), f1 = bf_hi(x01), f2 = e2 ? 0.f : bf_lo(x2);
            float st = fold(fmaf(f0, f0, fmaf(f1, f1, f2 * f2)), (f0 + f1) + f2, e1, 1);
#pragma unroll
            for (int i = 0; i < 5; i++) {
#pragma unroll
                for (int mt = 0; mt < 3; mt++) mma16816(a[mt], wq[i][mt][0], wq[i][mt][1], wq[i][mt][2], wq[i][mt][3], b[2 * i], b[2 * i + 1]);
                if (i < 4) st += shx(st, 2 << i);
            }
            const uint32_t pa = SM_PQ + (w >> 2) * 1024 + ((e2 ? 32 : 0) + (e1 ? 8 : 0) + g) * 16 + (w & 3) * 4;
            stsf(pa + 256, e2 ? st : e1 ? a[1][2] : a[1][0]);
            stsf(pa, e2 ? (e1 ? a[2][2] : a[2][0]) : (e1 ? a[0][2] : a[0][0]));
            if (w == 0) {
                const uint2 cs = lds64(SM_CSQ + lane * 48);
                const uint32_t qtag = lds32(SM_EPOCH) * NB + (n < 0 ? n + 5 : k);
                const char* dst = opaque(reinterpret_cast<const char*>(&g_q[n < 0 ? n + 5 : 4][h][24 * s + lane]));
                bar_sync<3, 256>();
                const uint32_t ra = SM_PQ + lane * 32;
                float S0 = sum8(lds128(ra), lds128(ra + 1024)), S1 = sum8(lds128(ra + 16), lds128(ra + 1040));
                if (n >= 0) {
                    float mean_b, rden;
                    ln_fast(shi(S0, 28), shi(S0, 24), mean_b, rden);
                    S0 = fmaf(-mean_b, F(cs.x), S0) * rden;
                    S1 = fmaf(-mean_b, F(cs.y), S1) * rden;
                }
                if (n == -1) stsf2(SM_CSQ + lane * 48, S0, S1);
                st_pkt8_if(lane < 24 && n != -1, dst, pack2(S0, S1), qtag);
                mbar_arrive_if(lane == 0 && (n == -2 || n >= 0), bar_at(B_QS));
                TRACES(n >= 0 ? tr + 5 : 95);
            } else bar_arrive<3, 256>();
            red_cell_if(n >= 0 && w * 16 + (lane >> 1) == cta, cell + 128, f0, f1, f2);
            __syncwarp();
        }
    }
}

template <int ID> __device__ __forceinline__ void role_exit() { asm volatile("exit; // %0" ::"n"(ID)); }
constexpr int NTHREADS = 512;
#define STR2(x) #x
#define STR(x) STR2(x)
__global__ void __launch_bounds__(NTHREADS, 1)
decode_kernel(const __grid_constant__ CUtensorMap tmK, const __grid_constant__ CUtensorMap tmV,
              const __grid_constant__ WeightMaps tmW, const Params p) {
    extern __shared__ __align__(1024) unsigned char smem[];
    const uint32_t t0 = now_ns();
    const int lane = threadIdx.x & 31;
    const int warp = __shfl_sync(0xffffffffu, threadIdx.x >> 5, 0);
    if (warp < 8) {
        asm volatile("setmaxnreg.inc.sync.aligned.u32 " STR(CFG_REG_CHAIN) ";");
        bar_sync<5, 480>();
        chain_role(p, warp, __shfl_sync(0xffffffffu, lane, lane), t0);
        role_exit<3>();
    } else if (warp < 12) {
        asm volatile("setmaxnreg.dec.sync.aligned.u32 " STR(CFG_REG_ATT) ";");
        if (elect_one()) {
#pragma unroll 1
            for (int i = warp - 8; i < NBAR; i += 4)
                if (i < B_W || i >= B_WC) mbar_init(bar_at(i), i == B_FIN ? 2 : i == B_PS || i == B_RP ? 4 : i >= B_F3 ? 1 : i >= B_WC ? 8 : i < B_RR || i > B_RV ? 1 : i < B_RK ? 2 : 4);
            asm volatile("fence.mbarrier_init.release.cluster;" ::: "memory");
            fence_async();
        }
        bar_sync<5, 480>();
        attention_role(p, warp - 8, lane);
        role_exit<2>();
    } else {
        asm volatile("setmaxnreg.dec.sync.aligned.u32 " STR(CFG_REG_HELP) ";");
        if (warp == 12) {
            TRACE(0);
            prefetch_role(p, &tmV, t0);
            role_exit<0>();
        } else {
            if (warp == 14) {
                if (smem_u32(smem) != SB) __trap();
                if (elect_one()) {
                    asm volatile("prefetch.tensormap [%0];" ::"l"(&tmW.q) : "memory");
                    mbar_init(bar_at(B_W), 1); mbar_init(bar_at(B_W + 1), 1); mbar_init(bar_at(B_W + 2), 1);
                    asm volatile("fence.mbarrier_init.release.cluster;" ::: "memory");
                    fence_async();
                    mbar_expect_tx(bar_at(B_W), 61440 + 15360 + 6400); mbar_expect_tx(bar_at(B_W + 1), 61440); mbar_expect_tx(bar_at(B_W + 2), 40960);
                    bulk_load(ST_X, p.x, 5120, bar_at(B_W));
                    bulk_load(ST_X + 5120, p.wr, 1280, bar_at(B_W));
                }
                reload_role(p, &tmK, &tmV, &tmW, t0);
            } else {
                unsigned ticket = 0;
                if (warp == 15 && lane == 0) asm volatile("atom.relaxed.gpu.global.add.u32 %0, [%1], 1;" : "=r"(ticket) : "l"(&g_epoch) : "memory");
                if (warp == 13 && elect_one()) {
                    asm volatile("prefetch.tensormap [%0];" ::"l"(&tmW.g) : "memory");
                    asm volatile("prefetch.tensormap [%0];" ::"l"(&tmW.u) : "memory");
                    asm volatile("prefetch.tensormap [%0];" ::"l"(&tmW.o) : "memory");
                    asm volatile("prefetch.tensormap [%0];" ::"l"(&tmK) : "memory");
                    asm volatile("prefetch.tensormap [%0];" ::"l"(&tmV) : "memory");
                }
                bar_sync<5, 480>();
                if (warp == 13) { sts32(SM_PROG, 0); bar_arrive<6, 64>(); load_role(p, &tmK, &tmV, t0); }
                else zero_role(p, lane, ticket, t0);
            }
            role_exit<1>();
        }
    }
}

typedef CUresult (*EncodeFn)(CUtensorMap*, CUtensorMapDataType, cuuint32_t, void*, const cuuint64_t*, const cuuint64_t*,
                             const cuuint32_t*, const cuuint32_t*, CUtensorMapInterleave, CUtensorMapSwizzle,
                             CUtensorMapL2promotion, CUtensorMapFloatOOBfill);

bool make_map(EncodeFn fn, CUtensorMap* m, const void* ptr, uint64_t cols, uint64_t rows, uint32_t bc, uint32_t br) {
    cuuint64_t dims[2] = {cols, rows};
    cuuint64_t strides[1] = {cols * 2};
    cuuint32_t box[2] = {bc, br};
    cuuint32_t es[2] = {1, 1};
    return fn(m, CU_TENSOR_MAP_DATA_TYPE_BFLOAT16, 2, const_cast<void*>(ptr), dims, strides, box, es, CU_TENSOR_MAP_INTERLEAVE_NONE,
              CU_TENSOR_MAP_SWIZZLE_NONE, CU_TENSOR_MAP_L2_PROMOTION_L2_128B, CU_TENSOR_MAP_FLOAT_OOB_FILL_NONE) == CUDA_SUCCESS;
}

bool make_kv_map(EncodeFn fn, CUtensorMap* m, const void* ptr) {
    cuuint64_t dims[4] = {64, 8, 3, (cuuint64_t)NB * NHEAD * SK / 8};
    cuuint64_t strides[3] = {DH * 2, 128, 8 * DH * 2};
    cuuint32_t box[4] = {64, 8, 3, 4};
    cuuint32_t es[4] = {1, 1, 1, 1};
    return fn(m, CU_TENSOR_MAP_DATA_TYPE_BFLOAT16, 4, const_cast<void*>(ptr), dims, strides, box, es, CU_TENSOR_MAP_INTERLEAVE_NONE,
              CU_TENSOR_MAP_SWIZZLE_128B, CU_TENSOR_MAP_L2_PROMOTION_L2_128B, CU_TENSOR_MAP_FLOAT_OOB_FILL_NONE) == CUDA_SUCCESS;
}

}

extern "C" void kernel_launch(void* const* d_in, const int* in_sizes, int n_in, void* d_out, int out_size) {
    (void)in_sizes; (void)n_in; (void)out_size;
    static EncodeFn fn = nullptr;
    if (!fn) {
        void* f = nullptr;
        cudaDriverEntryPointQueryResult qr;
        if (cudaGetDriverEntryPoint("cuTensorMapEncodeTiled", &f, cudaEnableDefault, &qr) != cudaSuccess || !f) return;
        fn = (EncodeFn)f;
        cudaFuncSetAttribute(decode_kernel, cudaFuncAttributeMaxDynamicSharedMemorySize, SMEM_BYTES);
    }
    CUtensorMap tmK, tmV;
    WeightMaps tmW;
    if (!make_kv_map(fn, &tmK, d_in[1]) || !make_kv_map(fn, &tmV, d_in[2])) return;
    if (!make_map(fn, &tmW.q, d_in[3], NHEAD * DH, DM, 48, 128) || !make_map(fn, &tmW.o, d_in[4], DM, NHEAD * DH, 160, 32)) return;
    if (!make_map(fn, &tmW.g, d_in[7], FF, DM, 16, 128) || !make_map(fn, &tmW.u, d_in[8], FF, DM, 16, 128)) return;
    Params p;
    p.x = (const unsigned short*)d_in[0];
    p.kc = (const char*)d_in[1];
    p.vc = (const char*)d_in[2];
    p.wq = (const char*)d_in[3];
    p.wo = (const char*)d_in[4];
    p.wr = (const unsigned short*)d_in[6];
    p.wg = (const char*)d_in[7];
    p.wu = (const char*)d_in[8];
    p.wd = (const char*)d_in[9];
    p.out = (unsigned short*)d_out;
    decode_kernel<<<NCTA, NTHREADS, SMEM_BYTES>>>(tmK, tmV, tmW, p);
}
```

```cpp
#include <cuda_runtime.h>
#include <cuda_bf16.h>
#include <cuda.h>
#include <stdint.h>

namespace {

constexpr int NB = 4, DM = 640, NHEAD = 32, DH = 192, SK = 4096, WIN = 1024, FF = 1536;
constexpr int NCTA = 128;
constexpr int TILE = 12288, PAIR = 2 * TILE;

#define CFG_LIST(X) \
    X(TICK0, 476)        \
    X(TICK, 515)        \
    X(TICKA, 0) \
    X(TICKB, 0) \
    X(TICKC, 0) \
    X(TICKD, 0) \
    X(STAG, 488)        \
    X(WLAG, 300)        \
    X(GSTEP, 700)        \
    X(WIN, 4)        \
    X(WIN2, 4)        \
    X(LMAX0, 500)        \
    X(LMAX, 400) \
    X(GAIN, 30)        \
    X(VSTEP, 300)        \
    X(RLAG, 0)        \
    X(RSTEP, 700) \
    X(RSTEP3, 450) \
    X(ZTILE, 10)        \
    X(START, 1)        \
    X(DLY_A, 400)        \
    X(DLY_AL, 100) \
    X(DLY_B, 600) \
    X(DLY_BL, 900) \
    X(DLY_F, 400) \
    X(DLY_P, 0)        \
    X(DLY_PL, 100) \
    X(DLY_PB, 300) \
    X(DLY_Q, 20) \
    X(DLY_QL, 100) \
    X(FLIP, 0) \
    X(SENT, 0)        \

#define X(n, v) constexpr int CFG_##n = v;
CFG_LIST(X)
#undef X
#define CFG(n) CFG_##n
constexpr int QUIET = 8;
#define CFG_REG_CHAIN 216
#define CFG_REG_ATT 56
#define CFG_REG_HELP 24
constexpr int KB_KV0 = 165;
__device__ __forceinline__ int kb_ns(int kb) { return kb * CFG(TICK0) / 12; }
__device__ __forceinline__ int tick_ns(int j) {
    return j <= 16 ? CFG(TICK0) : CFG(TICK) + (j & 8 ? (j & 4 ? CFG(TICKD) : CFG(TICKC)) : (j & 4 ? CFG(TICKB) : CFG(TICKA)));
}
__device__ __forceinline__ int batch_ns(int k) {
    return kb_ns(KB_KV0) + (k ? 16 * CFG(TICK0) + (k - 1) * 4 * (4 * CFG(TICK) + CFG(TICKA) + CFG(TICKB) + CFG(TICKC) + CFG(TICKD)) : 0);
}

__device__ __forceinline__ uint32_t slots(int k) { return k & 2 ? (k & 1 ? 0x04321658u : 0x65837104u) : (k & 1 ? 0x10482765u : 0x76543210u); }
__device__ __forceinline__ int pass_nibble(int k, int u) { return k > 0 ? 4 + (u & 1) : u; }
__device__ __forceinline__ uint32_t slot_at(uint32_t tab, int u) { return (tab >> (4 * u)) & 15; }

constexpr int NROUND = 11;
constexpr uint32_t ORD_BATCH = 0x3b9910, ORD_LAST = 0x6da, ORD_NO_HEAD = 0x248, ORD_NO_TAIL = 0x092;

constexpr uint32_t SB = 1024;
constexpr uint32_t SM_BAR = SB + 9 * PAIR;
constexpr int B_F1 = 0;
constexpr int B_RR = 24;
constexpr int B_RK = 32;
constexpr int B_RV = 36;
constexpr int B_Z = 37;
constexpr int B_EP = 38;
constexpr int B_W = 39;
constexpr int B_WC = 42;
constexpr int B_FIN = 45;
constexpr int B_F3 = 46;
constexpr int B_QS = 47;
constexpr int B_PS = 48;
constexpr int B_RP = 49;
constexpr int B_FL = 50;
constexpr int B_QR = 51;
constexpr int NBAR = 52;
__host__ __device__ constexpr uint32_t bar_at(int i) { return SM_BAR + 8 * i; }
constexpr uint32_t SM_EPOCH = SM_BAR + 416;
constexpr uint32_t SM_NEAR = SM_EPOCH + 4;
constexpr uint32_t SM_PROG = SM_EPOCH + 8;
constexpr uint32_t SM_MAX = SM_EPOCH + 16;
constexpr uint32_t SM_SUM = SM_MAX + 16;
constexpr uint32_t SM_FIN = SM_SUM + 32;
constexpr uint32_t SM_Q = SM_FIN + 32;
constexpr uint32_t PSTR = 144;
constexpr uint32_t SM_P = SM_Q + 5 * 384;
constexpr uint32_t SM_X = SM_P + 8 * PSTR;
constexpr uint32_t SM_CSG = SM_X + 40;
constexpr uint32_t SM_CSQ = SM_CSG + 32 * 48;
constexpr uint32_t SM_ONES = SM_X + 8 * 384;
constexpr uint32_t SM_PG = SM_ONES + 48;
constexpr uint32_t SM_PO = SM_PG + 1024;
constexpr uint32_t SM_PQ = SM_PO;
constexpr int SMEM_BYTES = SM_PO + 3072 - SB;
static_assert(SMEM_BYTES <= 232448 && SM_Q % 16 == 0 && SM_P % 16 == 0 && SM_X % 16 == 0 && SM_PO % 16 == 0, "smem");
constexpr uint32_t ST_WQ = SB, ST_WD = SB + 3 * PAIR, ST_WO = SB + 4 * PAIR, ST_WG = SB + 7 * PAIR, ST_X = ST_WG + 40960;

__device__ unsigned g_epoch;
__device__ unsigned g_init;
__device__ unsigned char g_scratch[4 << 20];
constexpr uint32_t HALF = 4096, SCR_O = 1 << 16, SCR_Q = 1 << 17, SCR_PROBE = 1 << 19;
__device__ __forceinline__ uint32_t acc_off(int k, int layer, int w) { return (k & 1) << 18 | (k >> 1) << 20 | (w >> 1) << 14 | (w & 1) << 11 | layer << 7; }
__device__ __forceinline__ uint32_t head_off(int h) { return (h & 3) << 14 | (h & 4) << 16 | (h & 8) << 17 | (h & 16) << 9; }
__device__ __forceinline__ uint32_t head_near(int h, uint32_t near) { return near ^ HALF ^ (h & 16) << 8; }
constexpr uint32_t FULL_A = 0x42040000u;

struct Params {
    const unsigned short* x;
    const char* kc;
    const char* vc;
    const char* wq;
    const char* wo;
    const unsigned short* wr;
    const char* wg;
    const char* wu;
    const char* wd;
    unsigned short* out;
    const char* scr;
};

__device__ __forceinline__ uint32_t smem_u32(const void* p) { return (uint32_t)__cvta_generic_to_shared(p); }
__device__ __forceinline__ void mbar_init(uint32_t a, uint32_t c) { asm volatile("mbarrier.init.shared::cta.b64 [%0], %1;" ::"r"(a), "r"(c) : "memory"); }
__device__ __forceinline__ void mbar_expect_tx(uint32_t a, uint32_t b) {
    asm volatile("mbarrier.arrive.expect_tx.shared::cta.b64 _, [%0], %1;" ::"r"(a), "r"(b) : "memory");
}
__device__ __forceinline__ void mbar_arrive(uint32_t a) { asm volatile("mbarrier.arrive.shared::cta.b64 _, [%0];" ::"r"(a) : "memory"); }
constexpr uint32_t SPIN_LIMIT = 1u << 22;
#define SPIN_DECL uint32_t spins = 0
#define SPIN_CHECK(info) { if (++spins > SPIN_LIMIT) __trap(); }
__device__ __forceinline__ void mbar_wait(uint32_t a, uint32_t parity) {
    uint32_t ok;
    SPIN_DECL;
    while (true) {
        asm volatile("{\n.reg .pred p;\nmbarrier.try_wait.parity.shared::cta.b64 p, [%1], %2;\nselp.u32 %0, 1, 0, p;\n}"
                     : "=r"(ok) : "r"(a), "r"(parity) : "memory");
        if (ok) break;
        SPIN_CHECK((a - SM_BAR) / 8 * 10 + parity);
    }
}
__device__ __forceinline__ uint32_t now_ns() { uint32_t t; asm volatile("mov.u32 %0, %%globaltimer_lo;" : "=r"(t) :: "memory"); return t; }
__device__ __forceinline__ uint32_t clk32() { uint32_t c; asm volatile("mov.u32 %0, %%clock;" : "=r"(c) :: "memory"); return c; }
__device__ __forceinline__ void wait_ns(uint32_t t) { while ((int)(now_ns() - t) < 0) {} }
__device__ __forceinline__ void wait_clk(uint32_t t) { while ((int)(clk32() - t) < 0) {} }
__device__ __forceinline__ bool elect_one() {
    uint32_t e;
    asm volatile("{\n.reg .pred p;\nelect.sync _|p, 0xffffffff;\nselp.u32 %0, 1, 0, p;\n}" : "=r"(e));
    return e;
}
constexpr uint64_t POL_FIRST = 0x12F0000000000000ull, POL_NORMAL = 0x1000000000000000ull;
__device__ __forceinline__ void tma_tile(uint32_t dst, const CUtensorMap* tm, int group, uint32_t bar, uint64_t pol) {
    asm volatile("cp.async.bulk.tensor.4d.shared::cluster.global.mbarrier::complete_tx::bytes.L2::cache_hint"
                 " [%0], [%1, {%3, %3, %3, %4}], [%2], %5;"
                 ::"r"(dst), "l"(tm), "r"(bar), "r"(0), "r"(group), "l"(pol) : "memory");
}
__device__ __forceinline__ void tma2d(uint32_t dst, const CUtensorMap* tm, int x, int y, uint32_t bar) {
    asm volatile("cp.async.bulk.tensor.2d.shared::cluster.global.mbarrier::complete_tx::bytes [%0], [%1, {%3, %4}], [%2];"
                 ::"r"(dst), "l"(tm), "r"(bar), "r"(x), "r"(y) : "memory");
}
__device__ __forceinline__ void bulk_load(uint32_t dst, const void* src, uint32_t bytes, uint32_t bar) {
    asm volatile("cp.async.bulk.shared::cluster.global.mbarrier::complete_tx::bytes [%0], [%1], %2, [%3];"
                 ::"r"(dst), "l"(src), "r"(bytes), "r"(bar) : "memory");
}
__device__ __forceinline__ void l2_prefetch(const void* p, uint32_t bytes) {
    asm volatile("cp.async.bulk.prefetch.L2.global [%0], %1;" ::"l"(p), "r"(bytes) : "memory");
}
__device__ __forceinline__ void mma16816(float (&c)[4], uint32_t a0, uint32_t a1, uint32_t a2, uint32_t a3, uint32_t b0, uint32_t b1) {
    asm volatile("mma.sync.aligned.m16n8k16.row.col.f32.bf16.bf16.f32 {%0,%1,%2,%3}, {%4,%5,%6,%7}, {%8,%9}, {%0,%1,%2,%3};"
                 : "+f"(c[0]), "+f"(c[1]), "+f"(c[2]), "+f"(c[3]) : "r"(a0), "r"(a1), "r"(a2), "r"(a3), "r"(b0), "r"(b1));
}
__device__ __forceinline__ void mma1688(float (&c)[4], uint32_t a0, uint32_t a1, uint32_t b0) {
    asm volatile("mma.sync.aligned.m16n8k8.row.col.f32.bf16.bf16.f32 {%0,%1,%2,%3}, {%4,%5}, {%6}, {%0,%1,%2,%3};"
                 : "+f"(c[0]), "+f"(c[1]), "+f"(c[2]), "+f"(c[3]) : "r"(a0), "r"(a1), "r"(b0));
}
__device__ __forceinline__ void ldsm4t(uint32_t (&r)[4], uint32_t a, uint32_t& zero) {
    asm volatile("ldmatrix.sync.aligned.m8n8.x4.trans.shared.b16 {%0,%1,%2,%3}, [%4];"
                 : "=r"(r[0]), "=r"(r[1]), "=r"(r[2]), "=r"(r[3]) : "r"(a + zero) : "memory");
    zero &= r[3];
}
__device__ __forceinline__ uint4 ld_pkt(const void* p) {
    uint4 v;
    asm volatile("{\n.reg .b128 t;\nld.relaxed.gpu.global.b128 t, [%4];\nmov.b128 {%0,%1,%2,%3}, t;\n}"
                 : "=r"(v.x), "=r"(v.y), "=r"(v.z), "=r"(v.w) : "l"(p) : "memory");
    return v;
}
__device__ __forceinline__ void st_pkt(const void* p, uint32_t a, uint32_t b, uint32_t c, uint32_t d) {
    asm volatile("{\n.reg .b128 t;\nmov.b128 t, {%1,%2,%3,%4};\nst.relaxed.gpu.global.b128 [%0], t;\n}"
                 ::"l"(p), "r"(a), "r"(b), "r"(c), "r"(d) : "memory");
}
__device__ __forceinline__ uint2 ld_pkt8(const void* p) {
    uint2 v;
    asm volatile("{\n.reg .b64 t;\nld.relaxed.gpu.global.b64 t, [%2];\nmov.b64 {%0,%1}, t;\n}" : "=r"(v.x), "=r"(v.y) : "l"(p) : "memory");
    return v;
}
__device__ __forceinline__ void red_cell(const char* p, float a, float b, float c) {
    asm volatile("red.relaxed.gpu.global.add.v4.f32 [%0], {%1,%2,%3,%4};" ::"l"(p), "f"(a), "f"(b), "f"(c), "f"(1.0f) : "memory");
}
__device__ __forceinline__ uint32_t cell_count(const char* p) {
    uint32_t c;
    asm volatile("ld.relaxed.gpu.global.u32 %0, [%1+12];" : "=r"(c) : "l"(p) : "memory");
    return c;
}
#define PRED(n) "{\n.reg .pred p;\nsetp.ne.u32 p, %" #n ", 0;\n"
__device__ __forceinline__ void red_cell2_if(bool on, const char* p, float a, float b, float c) {
    asm volatile(PRED(5) "@p red.relaxed.gpu.global.add.v4.f32 [%0], {%1,%2,%3,%4};\n@p red.relaxed.gpu.global.add.v4.f32 [%0+4096], {%1,%2,%3,%4};\n}"
                 ::"l"(p), "f"(a), "f"(b), "f"(c), "f"(1.0f), "r"((uint32_t)on) : "memory");
}
__device__ __forceinline__ void st_pkt82_if(bool on, const void* p, uint32_t a, uint32_t b) {
    asm volatile(PRED(3) ".reg .b64 t;\nmov.b64 t, {%1,%2};\n@p st.relaxed.gpu.global.b64 [%0], t;\n@p st.relaxed.gpu.global.b64 [%0+4096], t;\n}"
                 ::"l"(p), "r"(a), "r"(b), "r"((uint32_t)on) : "memory");
}
__device__ __forceinline__ void st_pkt2_if(bool on, const void* p, uint32_t a, uint32_t b, uint32_t c, uint32_t d) {
    asm volatile(PRED(5) ".reg .b128 t;\nmov.b128 t, {%1,%2,%3,%4};\n@p st.relaxed.gpu.global.b128 [%0], t;\n@p st.relaxed.gpu.global.b128 [%0+4096], t;\n}"
                 ::"l"(p), "r"(a), "r"(b), "r"(c), "r"(d), "r"((uint32_t)on) : "memory");
}
__device__ __forceinline__ void mbar_arrive_if(bool on, uint32_t a) {
    asm volatile(PRED(1) "@p mbarrier.arrive.shared::cta.b64 _, [%0];\n}" ::"r"(a), "r"((uint32_t)on) : "memory");
}
__device__ __forceinline__ void sts16_if(bool on, uint32_t a, uint32_t v) {
    asm volatile(PRED(2) "@p st.shared.u16 [%0], %1;\n}" ::"r"(a), "h"((unsigned short)v), "r"((uint32_t)on) : "memory");
}
__device__ __forceinline__ void sts32_if(bool on, uint32_t a, uint32_t v) {
    asm volatile(PRED(2) "@p st.shared.u32 [%0], %1;\n}" ::"r"(a), "r"(v), "r"((uint32_t)on) : "memory");
}
__device__ __forceinline__ void sts128_if(bool on, uint32_t a, uint32_t x, uint32_t y, uint32_t z, uint32_t w) {
    asm volatile(PRED(5) "@p st.shared.v4.u32 [%0], {%1,%2,%3,%4};\n}" ::"r"(a), "r"(x), "r"(y), "r"(z), "r"(w), "r"((uint32_t)on) : "memory");
}
__device__ __forceinline__ float fast_rcp(float x) { float r; asm("rcp.approx.ftz.f32 %0, %1;" : "=f"(r) : "f"(x)); return r; }
__device__ __forceinline__ float fast_sqrt(float x) { float r; asm("sqrt.approx.ftz.f32 %0, %1;" : "=f"(r) : "f"(x)); return r; }
__device__ __forceinline__ float fast_ex2(float x) { float r; asm("ex2.approx.ftz.f32 %0, %1;" : "=f"(r) : "f"(x)); return r; }
__device__ __forceinline__ uint32_t pack2(float lo, float hi) {
    uint32_t r;
    asm("cvt.rn.bf16x2.f32 %0, %1, %2;" : "=r"(r) : "f"(hi), "f"(lo));
    return r;
}
__device__ __forceinline__ float bfr(float x) { return __uint_as_float(pack2(0.f, x)); }
__device__ __forceinline__ uint32_t badd2(uint32_t a, uint32_t b) { uint32_t r; asm("add.rn.bf16x2 %0, %1, %2;" : "=r"(r) : "r"(a), "r"(b)); return r; }
__device__ __forceinline__ uint32_t bsub2(uint32_t a, uint32_t b) { uint32_t r; asm("sub.rn.bf16x2 %0, %1, %2;" : "=r"(r) : "r"(a), "r"(b)); return r; }
__device__ __forceinline__ uint32_t bmul2(uint32_t a, uint32_t b) { uint32_t r; asm("mul.rn.bf16x2 %0, %1, %2;" : "=r"(r) : "r"(a), "r"(b)); return r; }
__device__ __forceinline__ float bf_lo(uint32_t w) { return __uint_as_float(w << 16); }
__device__ __forceinline__ float bf_hi(uint32_t w) { return __uint_as_float(w & 0xffff0000u); }
__device__ __forceinline__ float F(uint32_t t) { return __uint_as_float(t); }
__device__ __forceinline__ uint32_t lds16(uint32_t a) { unsigned short h; asm volatile("ld.shared.u16 %0, [%1];" : "=h"(h) : "r"(a) : "memory"); return h; }
__device__ __forceinline__ uint32_t lds32(uint32_t a) { uint32_t v; asm volatile("ld.shared.u32 %0, [%1];" : "=r"(v) : "r"(a) : "memory"); return v; }
__device__ __forceinline__ uint2 lds64(uint32_t a) {
    uint2 v; asm volatile("ld.shared.v2.u32 {%0,%1}, [%2];" : "=r"(v.x), "=r"(v.y) : "r"(a) : "memory"); return v;
}
__device__ __forceinline__ uint4 lds128(uint32_t a) {
    uint4 v; asm volatile("ld.shared.v4.u32 {%0,%1,%2,%3}, [%4];" : "=r"(v.x), "=r"(v.y), "=r"(v.z), "=r"(v.w) : "r"(a) : "memory"); return v;
}
__device__ __forceinline__ float sum8(const uint4& u, const uint4& v) {
    return ((F(u.x) + F(u.y)) + (F(u.z) + F(u.w))) + ((F(v.x) + F(v.y)) + (F(v.z) + F(v.w)));
}
__device__ __forceinline__ void sts16(uint32_t a, uint32_t v) { asm volatile("st.shared.u16 [%0], %1;" ::"r"(a), "h"((unsigned short)v) : "memory"); }
__device__ __forceinline__ void sts32(uint32_t a, uint32_t v) { asm volatile("st.shared.u32 [%0], %1;" ::"r"(a), "r"(v) : "memory"); }
__device__ __forceinline__ void stsf(uint32_t a, float v) { asm volatile("st.shared.f32 [%0], %1;" ::"r"(a), "f"(v) : "memory"); }
__device__ __forceinline__ void stsf2(uint32_t a, float x, float y) { asm volatile("st.shared.v2.f32 [%0], {%1,%2};" ::"r"(a), "f"(x), "f"(y) : "memory"); }
__device__ __forceinline__ void stsf4(uint32_t a, float x, float y, float z, float w) {
    asm volatile("st.shared.v4.f32 [%0], {%1,%2,%3,%4};" ::"r"(a), "f"(x), "f"(y), "f"(z), "f"(w) : "memory");
}
template <int ID, int N> __device__ __forceinline__ void bar_sync() { asm volatile("bar.sync %0, %1;" ::"n"(ID), "n"(N) : "memory"); }
template <int ID, int N> __device__ __forceinline__ void bar_arrive() { asm volatile("bar.arrive %0, %1;" ::"n"(ID), "n"(N) : "memory"); }
__device__ __forceinline__ void fence_async() { asm volatile("fence.proxy.async.shared::cta;" ::: "memory"); }
__device__ __forceinline__ float shx(float v, int m) { return __shfl_xor_sync(0xffffffffu, v, m); }
__device__ __forceinline__ float shi(float v, int l) { return __shfl_sync(0xffffffffu, v, l); }
__device__ __forceinline__ uint32_t shi(uint32_t v, int l) { return __shfl_sync(0xffffffffu, v, l); }
__device__ __forceinline__ uint32_t opaque(uint32_t x) { asm volatile("mov.u32 %0, %0;" : "+r"(x)); return x; }
__device__ __forceinline__ const char* opaque(const char* x) { asm volatile("mov.u64 %0, %0;" : "+l"(x)); return x; }
constexpr float LOG2E = 1.4426950408889634f;

#define TRACE(idx) do {} while (0)
#define TRACES(slot) do {} while (0)

__device__ __forceinline__ int kv_group(int k, int t) {
    const int cta = blockIdx.x;
    return ((k * NHEAD + (cta >> 2)) * SK + (SK - WIN) + (cta & 3) * 256 + t * 32) / 8;
}
__device__ __forceinline__ uint32_t phase_ns() { return (((blockIdx.x >> 2) * 13) & 31) * CFG(STAG) / 32; }

__device__ __forceinline__ void prefetch_role(const Params& p, const CUtensorMap* tmV, int lane, uint32_t t0) {
    const int cta = blockIdx.x;
    t0 += phase_ns();
#pragma unroll 1
    for (int i = 0; i < 5; i++) {
        wait_ns(t0 + i * CFG(TICK0));
        if (elect_one()) l2_prefetch(p.wq + (size_t)(128 * i + cta) * 12288, 12288);
    }
#pragma unroll 1
    for (int i = 0; i < 5; i++) {
        wait_ns(t0 + kb_ns(75) + i * kb_ns(6));
        if (elect_one()) { l2_prefetch(p.wg + (128 * i + cta) * 3072, 3072); l2_prefetch(p.wu + (128 * i + cta) * 3072, 3072); }
    }
#pragma unroll 1
    for (int i = 0; i < 6; i++) {
        wait_ns(t0 + kb_ns(105) + i * kb_ns(10));
        if (elect_one()) l2_prefetch(p.wo + (size_t)((cta >> 2) * DH + 32 * i + 8 * (cta & 3)) * 1280, 10240);
    }
    bar_sync<6, 64>();
    mbar_wait(bar_at(B_EP), 0);
    const uint32_t tag0 = lds32(SM_EPOCH) * NB;
    const char* const qsrc = p.scr + SCR_Q + head_off(cta >> 2) + head_near(cta >> 2, lds32(SM_NEAR)) + lane * 8;
#pragma unroll 1
    for (int i = 0; i < 2 * NB; i++) {
        const int slot = min(i, NB), k = i - NB + 1;
        if (i == 0 || i >= NB) {
            mbar_wait(bar_at(B_QS), i ? k & 1 : 0);
            wait_clk(clk32() + (i < 2 * NB - 1 ? CFG(DLY_QL) : CFG(DLY_Q)));
        }
        const uint32_t tag = tag0 + (i & 3);
        uint2 a, b, c;
        {
            SPIN_DECL;
            while (true) {
                a = ld_pkt8(qsrc + slot * 768); b = ld_pkt8(qsrc + slot * 768 + 256); c = ld_pkt8(qsrc + slot * 768 + 512);
                if (__all_sync(0xffffffffu, a.y == tag && b.y == tag && c.y == tag)) break;
                SPIN_CHECK(slot);
            }
        }
        const uint32_t qd = SM_Q + slot * 384 + lane * 4;
        sts32(qd, a.x); sts32(qd + 128, b.x); sts32(qd + 256, c.x);
        fence_async();
        if (i >= NB - 1) mbar_arrive(bar_at(B_QR));
        if (k < 1 || k == NB) continue;
#pragma unroll 1
        for (int t = 12; t < 16; t++) {
            mbar_wait(bar_at(B_RK + ((t >> 1) & 1)), (k - 1) & 1);
            SPIN_DECL;
            while ((int)lds32(SM_PROG) <= 16 * k + t) SPIN_CHECK(i);
            wait_ns(t0);
            t0 = now_ns() + CFG(VSTEP);
            if (elect_one()) {
                mbar_expect_tx(bar_at(B_F1 + t), TILE);
                tma_tile(SB + slot_at(slots(k), t >> 1) * PAIR + (t & 1) * TILE, tmV, kv_group(k, t & 7), bar_at(B_F1 + t), POL_FIRST);
            }
            TRACE(256 + 16 * k + t);
        }
    }
}

struct WeightMaps { CUtensorMap q, o, g, u; };
__device__ __forceinline__ void load_role(const Params& p, const CUtensorMap* tmK, const CUtensorMap* tmV, uint32_t t0) {
    t0 += phase_ns();
    wait_ns(t0 + kb_ns(60));
    if (elect_one()) bulk_load(ST_WD, p.wd + blockIdx.x * 15360, 15360, bar_at(B_W));
    int shift = 0;
#pragma unroll 1
    for (int j = 0; j < 16 * NB; j++) {
        const int k = j >> 4, t = j & 15, u = t >> 1;
        if (j == 0 || j == 8 || j == 14) mbar_wait(bar_at(B_WC + j / 7), 0);
        if (k > 0 && t < 12) {
            if (t >= 4) mbar_wait(bar_at(B_RR + t - 4), k & 1);
            else if (t >= 2) mbar_wait(bar_at(B_RP), (k - 1) & 1);
            else if (k > 1) mbar_wait(bar_at(B_RK + 3), k & 1);
            else mbar_wait(bar_at(B_RR + t), 0);
        }
        const int jw = j - CFG(WIN);
        if (jw >= 0 && (jw < 16 || (jw & 15) < 12)) mbar_wait(bar_at(B_F1 + (jw & 15)), (jw >> 4) & 1);
        const int jv = j - CFG(WIN2);
        if (jv >= 16 && (jv & 15) >= 12 && t < 12) mbar_wait(bar_at(B_F1 + (jv & 15)), (jv >> 4) & 1);
        const uint32_t dst = SB + slot_at(slots(k), t < 8 ? pass_nibble(k, u) : u) * PAIR + (t & 1) * TILE;
        t0 += j ? tick_ns(j) : batch_ns(0);
        shift = max(shift - CFG(GAIN), 0);
        shift = max(shift, (int)(now_ns() - t0) - (j < 12 ? CFG(LMAX0) : CFG(LMAX)));
        wait_ns(t0 + shift);
        if (elect_one()) {
            if (k > 0 && t >= 12) {
                l2_prefetch(p.vc + (size_t)kv_group(k, t & 7) * 3072, TILE);
            } else {
                mbar_expect_tx(bar_at(B_F1 + t), TILE);
                tma_tile(dst, t & 8 ? tmV : tmK, kv_group(k, t & 7), bar_at(B_F1 + t), t < 10 && j >= 8 && j < 56 ? POL_NORMAL : POL_FIRST);
            }
            sts32(SM_PROG, j + 1);
        }
        TRACE(128 + j);
    }
}

__device__ __forceinline__ void reload_role(const Params& p, const CUtensorMap* tmK, const CUtensorMap* tmV, const WeightMaps* tm, uint32_t t0) {
    const int cta = blockIdx.x;
    t0 += CFG(TICK0) + CFG(WLAG) + phase_ns();
#pragma unroll 1
    for (int i = 0; i < 5; i++) {
        wait_ns(t0 + i * CFG(TICK0));
        if (elect_one()) tma2d(ST_WQ + i * 12288, &tm->q, 48 * cta, 128 * i, bar_at(B_W));
        if (i == 1) bar_sync<5, 480>();
    }
#pragma unroll 1
    for (int i = 0, o = 0; i < 10;) {
        const uint32_t now = now_ns() - t0;
        if (o < 6 && (int)now >= kb_ns(105) + o * kb_ns(10)) {
            if (elect_one()) tma2d(ST_WO + o * 10240, &tm->o, 160 * (cta & 3), (cta >> 2) * DH + 32 * o, bar_at(B_W + 1));
            o++;
        } else if ((int)now >= kb_ns(77) + i * CFG(GSTEP) && (i < 9 || o == 6)) {
            if (elect_one()) tma2d(ST_WG + (i & 1) * 20480 + (i >> 1) * 4096, i & 1 ? &tm->u : &tm->g, (12 * cta) & ~7, 128 * (i >> 1), bar_at(B_W + 2));
            i++;
        }
    }
#pragma unroll 1
    for (int k = 0; k < NB - 1; k++) {
        mbar_wait(bar_at(B_RK + 2), k & 1);
        if (elect_one()) {
            const uint32_t dst = SB + slot_at(slots(k), 2) * PAIR;
            mbar_expect_tx(bar_at(B_FL), PAIR);
            tma_tile(dst, tmV, kv_group(k, 0), bar_at(B_FL), POL_FIRST);
            tma_tile(dst + TILE, tmV, kv_group(k, 1), bar_at(B_FL), POL_FIRST);
        }
        mbar_wait(bar_at(B_RV), k & 1);
        uint32_t due = now_ns() + (k == NB - 2 ? 0 : CFG(RLAG));
        if (elect_one()) mbar_expect_tx(bar_at(B_F3), 4 * PAIR);
#pragma unroll 1
        for (int t = 0; t < 8; t++) {
            wait_ns(due);
            due += k == NB - 2 ? CFG(RSTEP3) : CFG(RSTEP);
            if (elect_one())
                tma_tile(SB + slot_at(slots(k + 1), t >> 1) * PAIR + (t & 1) * TILE, tmK, kv_group(k + 1, t), bar_at(B_F3), POL_FIRST);
        }
        TRACE(121 + k);
    }
}

__device__ __forceinline__ void zero_role(const Params& p, int lane, unsigned ticket, uint32_t t0) {
    const int cta = blockIdx.x;
    const uint32_t epoch = __shfl_sync(0xffffffffu, ticket, 0) / NCTA + 1;
    {
        const char* pr = p.scr + SCR_PROBE + (cta & 31) * 128 + (cta >> 5) * 16384;
        if (lane < 4) st_pkt(pr + (lane & 1) * 16 + (lane >> 1) * HALF, 0, 0, 0, 0);
        uint32_t best0 = ~0u, best1 = ~0u;
#pragma unroll 1
        for (int i = 0; i < 8; i++) {
            uint32_t c = clk32(), v = 0;
            if (lane == 0) asm volatile("atom.relaxed.gpu.global.add.u32 %0, [%1], 1;" : "=r"(v) : "l"(pr + (i & 1) * HALF) : "memory");
            c += __shfl_sync(0xffffffffu, v, 0) >> 16;
            c = clk32() - c;
            if (i & 1) best1 = min(best1, c); else best0 = min(best0, c);
        }
        if (lane == 0) { sts32(SM_EPOCH, epoch); sts32(SM_NEAR, (best1 < best0) == (CFG(FLIP) != 0) ? HALF : 0); mbar_arrive(bar_at(B_EP)); }
    }
#pragma unroll 1
    for (int k = 0; k < NB + 2; k++) {
        lane = opaque(lane);
        const int cl = 2 * (cta & 15) + (lane & 1);
        const int col = 80 * (cta >> 4) + (cl & 2 ? 48 : 0) + (cl >> 2) + (cl & 1 ? 8 : 0);
        const char* own = p.scr + (cl >> 2) * 256 + (cl & 3) * 16;
        if (k < NB) {
            wait_ns(t0 + batch_ns(k) + CFG(ZTILE) * CFG(TICK0));
            const int lg = lane >> 3, ty = (lane & 7) >> 1;
            const char* dst = own + acc_off((k - (lg >> 1)) & 3, lg != 0, cta >> 4) + ty * HALF;
            uint32_t v0 = 0, v1 = 0, v2 = 0, v3 = 0;
            if (lane < 4) {
                const unsigned short* xp = p.x + k * DM + col;
                v0 = __ldg(xp) << 16; v1 = __ldg(xp + 16) << 16; v2 = cl & 2 ? 0 : __ldg(xp + 32) << 16; v3 = 0x3f800000u;
            }
            if (lg == 0 || (lg == 1 && (ty < 2 || k == NB - 1)) || (lg == 2 && k > 0 && ty > 1)) st_pkt(dst, v0, v1, v2, v3);
            asm volatile("fence.acq_rel.gpu;" ::: "memory");
            __syncwarp();
            if (lane == 0) asm volatile("red.relaxed.gpu.global.add.u32 [%0], 1;" ::"l"(&g_init) : "memory");
            const uint32_t target = ((epoch - 1) * NB + k + 1) * NCTA;
            SPIN_DECL;
            while (true) {
                __nanosleep(400);
                uint32_t v;
                asm volatile("ld.acquire.gpu.global.u32 %0, [%1];" : "=r"(v) : "l"(&g_init) : "memory");
                if (__all_sync(0xffffffffu, (int)(v - target) >= 0)) break;
                SPIN_CHECK(v);
            }
        }
        uint4 r;
        if (k == 1) mbar_wait(bar_at(B_RK), 0);
        if (k > 1) {
            mbar_wait(bar_at(B_FIN), k & 1);
            r = lds128(SM_FIN + (lane & 1) * 16);
        }
        __syncwarp();
        if (lane == 0) mbar_arrive(bar_at(B_Z));
        if (k > 1) {
            const int b = k - 2;
            const char* src = own + acc_off(b, 1, cta >> 4) + (2 + ((lane >> 1) & 1)) * HALF;
            unsigned short* o = p.out + b * DM + col;
            wait_clk(clk32() + CFG(DLY_F));
            uint4 v = {};
            SPIN_DECL;
            while (true) {
                v = ld_pkt(src);
                if (__all_sync(0xffffffffu, F(v.w) + shx(F(v.w), 2) == NCTA)) break;
                SPIN_CHECK(k);
            }
            const float y0 = F(v.x) + shx(F(v.x), 2), y1 = F(v.y) + shx(F(v.y), 2), y2 = F(v.z) + shx(F(v.z), 2);
            const uint32_t x01 = badd2(r.x, badd2(r.y, bmul2(pack2(y0, y1), r.w)));
            const uint32_t x2 = badd2(r.z, badd2(r.z >> 16, bmul2(pack2(y2, 0.f), r.w)));
            if (lane < 2) {
                o[0] = x01; o[16] = x01 >> 16;
                if (!(cl & 2)) o[32] = x2;
            }
            TRACES((2 * b + 1) * 6 + 4);
        }
    }
}

__host__ __device__ constexpr uint32_t desc_lo(uint32_t addr) { return ((addr & 0x3FFFFu) >> 4) | (1u << 16); }
constexpr uint32_t DESC_HI_TILE = (3072u >> 4) | (1u << 30);
constexpr uint32_t DESC_HI_VEC = 1u;
template <int TA, int AOFF, int BOFF>
__device__ __forceinline__ void wgmma_n8(float (&d)[4], uint32_t alo, uint32_t blo, int accumulate) {
    asm volatile("{\n.reg .pred p;\n.reg .b32 a, b;\n.reg .b64 da, db;\nsetp.ne.b32 p, %6, 0;\n"
                 "add.u32 a, %4, %8;\nadd.u32 b, %5, %9;\nmov.b64 da, {a, %10};\nmov.b64 db, {b, %11};\n"
                 "wgmma.mma_async.sync.aligned.m64n8k16.f32.bf16.bf16 {%0,%1,%2,%3}, da, db, p, 1, 1, %7, 0;\n}"
                 : "+f"(d[0]), "+f"(d[1]), "+f"(d[2]), "+f"(d[3])
                 : "r"(alo), "r"(blo), "r"(accumulate), "n"(TA), "n"(AOFF >> 4), "n"(BOFF >> 4), "n"(DESC_HI_TILE), "n"(DESC_HI_VEC));
}
template <int KS>
__device__ __forceinline__ void qk_steps(float (&d)[4], uint32_t alo, uint32_t blo) {
    if constexpr (KS < 12) {
        wgmma_n8<0, (KS >> 2) * 1024 + (KS & 3) * 32, KS * 32>(d, alo, blo, KS > 0);
        qk_steps<KS + 1>(d, alo, blo);
    }
}
__device__ __forceinline__ void pv_steps(float (&e)[3][4], uint32_t alo, uint32_t blo, int acc) {
    wgmma_n8<1, 0, 0>(e[0], alo, blo, acc); wgmma_n8<1, 1024, 0>(e[1], alo, blo, acc); wgmma_n8<1, 2048, 0>(e[2], alo, blo, acc);
    wgmma_n8<1, 6144, 32>(e[0], alo, blo, 1); wgmma_n8<1, 7168, 32>(e[1], alo, blo, 1); wgmma_n8<1, 8192, 32>(e[2], alo, blo, 1);
}
__device__ __forceinline__ void wg_fence() { asm volatile("wgmma.fence.sync.aligned;" ::: "memory"); }
__device__ __forceinline__ void wg_commit() { asm volatile("wgmma.commit_group.sync.aligned;" ::: "memory"); }
template <int N> __device__ __forceinline__ void wg_wait() { asm volatile("wgmma.wait_group.sync.aligned %0;" ::"n"(N) : "memory"); }
__device__ __forceinline__ void qk_pair(float (&d)[4], uint32_t slot, uint32_t qslot) {
    wg_fence();
    qk_steps<0>(d, desc_lo(SB) + slot * (PAIR >> 4), desc_lo(SM_Q) + qslot * (384 >> 4));
    wg_commit();
}
__device__ __forceinline__ void acc_ready(float (&d)[4]) { asm volatile("" : "+f"(d[0]), "+f"(d[1]), "+f"(d[2]), "+f"(d[3]) :: "memory"); }
__device__ __forceinline__ uint32_t score_pair(float (&d)[4], int lane) {
    acc_ready(d);
    const float scale = 0.07216878364870322f;
    const uint32_t r = pack2(d[0], d[2]);
    return shi(pack2(bf_lo(r) * scale, bf_hi(r) * scale), lane & 28);
}

__device__ __forceinline__ void attention_role(const Params& p, int w, int lane) {
    const int cta = blockIdx.x, t4 = lane & 3, g = lane >> 2;
    mbar_wait(bar_at(B_EP), 0);
    const uint32_t tag0 = lds32(SM_EPOCH) * NB;
    const char* const odst = p.scr + SCR_O + head_off(cta >> 2) + (2 * w + (g >> 2)) * 256 + (cta & 3) * 64 + (g & 3) * 16;
    const uint32_t pdst = SM_P + t4 * PSTR + (16 * w + g) * 2;
    auto softmax = [&](uint32_t sc, int ps) -> uint32_t {
        const float s0 = bf_lo(sc), s1 = bf_hi(sc);
        int key = __float_as_int(fmaxf(s0, s1));
        key ^= (key >> 31) & 0x7fffffff;
        key = __reduce_max_sync(0xffffffffu, key);
        sts32(SM_MAX + w * 4, key);
        bar_sync<4, 128>();
        const uint4 mx = lds128(SM_MAX);
        key = max(max((int)mx.x, (int)mx.y), max((int)mx.z, (int)mx.w));
        key ^= (key >> 31) & 0x7fffffff;
        const float mb = __int_as_float(key) * LOG2E;
        const uint32_t pp = pack2(fast_ex2(fmaf(s0, LOG2E, -mb)), fast_ex2(fmaf(s1, LOG2E, -mb)));
        sts16(pdst + ps * 4 * PSTR, pp); sts16(pdst + ps * 4 * PSTR + 16, pp >> 16);
        uint32_t fs;
        asm volatile("redux.sync.add.u32 %0, %1, 0xffffffff;" : "=r"(fs) : "r"(__float2uint_rn((bf_lo(pp) + bf_hi(pp)) * 8388608.f)));
        fence_async();
        bar_sync<4, 128>();
        sts32(SM_SUM + ps * 16 + w * 4, fs);
        return key;
    };
    auto aux_word = [&](uint32_t mx, const uint4& u, int k) {
        const float l = __uint2float_rn((u.x + u.y) + (u.z + u.w)) * (1.f / 8388608.f);
        return (g < 4 ? mx : (__float_as_uint(l) + 0x80u) & 0xffffff00u) | ((tag0 + k) & 0xffu);
    };
    auto send = [&](float (&e)[3][4], uint32_t aux, int ps) {
        acc_ready(e[0]); acc_ready(e[1]); acc_ready(e[2]);
        const uint32_t o0 = pack2(e[0][0], e[0][2]), o1 = pack2(e[1][0], e[1][2]), o2 = pack2(e[2][0], e[2][2]);
        st_pkt2_if(t4 == 0, odst + ps * 2048, o0, o1, o2, aux);
        mbar_arrive_if(lane == 0, bar_at(ps ? B_RV : B_PS));
    };
    mbar_wait(bar_at(B_QR), 0);
    TRACES(73);
#pragma unroll 1
    for (int it = 0; it <= NB; it++) {
        uint32_t m1 = 0;
        if (it < NB) {
            const uint32_t tab = slots(it);
            uint32_t sc = 0;
#pragma unroll 1
            for (int t = 0; t < 8; t++) {
                const uint32_t alo = desc_lo(SB) + slot_at(tab, pass_nibble(it, t >> 1)) * (PAIR >> 4), blo = desc_lo(SM_Q) + it * (384 >> 4);
                mbar_wait(bar_at(B_F1 + t), it & 1);
                float d[4] = {};
#pragma unroll 1
                for (int c = 0; c < 3; c++) {
                    wg_fence();
                    wgmma_n8<0, 0, 0>(d, alo + c * 64, blo + c * 8, c > 0); wgmma_n8<0, 32, 32>(d, alo + c * 64, blo + c * 8, 1);
                    wgmma_n8<0, 64, 64>(d, alo + c * 64, blo + c * 8, 1); wgmma_n8<0, 96, 96>(d, alo + c * 64, blo + c * 8, 1);
                    wg_commit();
                    wg_wait<0>();
                }
                if ((t & 1) == (w >> 1)) {
                    mbar_arrive_if(lane == 0, bar_at(B_RR + t));
                    const uint32_t s = score_pair(d, lane);
                    if (t4 == t >> 1) sc = s;
                }
            }
            m1 = softmax(sc, 0);
        }
        if (it > 0) {
            const int k = it - 1;
            const uint32_t tab = slots(k);
            const uint32_t v0 = slot_at(tab, k < NB - 1 ? 2 : 4);
            TRACES(48 + k * 6);
            if (k > 0) mbar_wait(bar_at(B_F3), it & 1);
            mbar_wait(bar_at(B_QR), it & 1);
            TRACES(49 + k * 6);
            float d[4][4] = {};
#pragma unroll
            for (int u = 0; u < 4; u++) {
                qk_pair(d[u], slot_at(tab, u), 4);
                if (u > 0) { wg_wait<1>(); mbar_arrive_if(lane == 0, bar_at(B_RK + u - 1)); }
            }
            uint32_t sc = score_pair(d[0], lane), s = score_pair(d[1], lane);
            if (t4 == 1) sc = s;
            s = score_pair(d[2], lane);
            if (t4 == 2) sc = s;
            wg_wait<0>();
            s = score_pair(d[3], lane);
            mbar_arrive_if(lane == 0, bar_at(B_RK + 3));
            if (t4 == 3) sc = s;
            TRACES(50 + k * 6);
            const uint32_t m2 = softmax(sc, 1);
            TRACES(51 + k * 6);
            float e[3][4] = {};
            uint4 u;
            wg_fence();
#pragma unroll
            for (int t = 0; t < 8; t++) {
                const int pr = ((t >> 1) + 1) & 3;
                if (t == 6 && k < NB - 1) mbar_wait(bar_at(B_FL), k & 1);
                if (t == 7) { bar_sync<4, 128>(); u = lds128(SM_SUM + 16); }
                if (t == 1 || t == 6) wg_fence();
                pv_steps(e, desc_lo(SB + (t & 1) * TILE) + (pr ? slot_at(tab, 4 + pr) : v0) * (PAIR >> 4), desc_lo(SM_P + (4 + pr) * PSTR + (t & 1) * 64), t > 0);
                if (t == 0) st_pkt2_if(t4 == 0, odst + 2048, 0, 0, 0, tag0 + k + 128);
            }
            wg_commit();
            const uint32_t aux = opaque(aux_word(m2, u, k));
            wg_wait<0>();
            send(e, aux, 1);
            TRACES(52 + k * 6);
        }
        if (it < NB) {
            const uint32_t tab = slots(it);
            st_pkt2_if(t4 == 0, odst, 0, 0, 0, tag0 + it + 128);
            bar_sync<4, 128>();
            const uint32_t aux = opaque(aux_word(m1, lds128(SM_SUM), it));
            float e[3][4] = {};
#pragma unroll 1
            for (int u = 0; u < 4; u++) {
                const uint32_t alo = desc_lo(SB) + slot_at(tab, 4 + u) * (PAIR >> 4), blo = desc_lo(SM_P) + u * (PSTR >> 4);
                mbar_wait(bar_at(B_F1 + 8 + 2 * u), it & 1);
                wg_fence();
                pv_steps(e, alo, blo, u > 0);
                wg_commit();
                if (u == 1) { wg_wait<1>(); mbar_arrive_if(lane == 0, bar_at(B_RP)); }
                mbar_wait(bar_at(B_F1 + 9 + 2 * u), it & 1);
                wg_fence();
                pv_steps(e, alo + (TILE >> 4), blo + 4, 1);
                wg_commit();
            }
            wg_wait<0>();
            send(e, aux, 0);
            TRACES(53 + it * 6);
        }
    }
}

__device__ __forceinline__ void ln_finish(float s, float q, float& mean_b, float& rden) {
    const float mean = s * (1.f / DM);
    const float var = fmaxf(fmaf(q, 1.f / DM, -mean * mean), 0.f);
    mean_b = bfr(mean);
    rden = fast_rcp(bfr(fast_sqrt(bfr(bfr(var) + 1e-5f))));
}
__device__ __forceinline__ void ln_fast(float s, float q, float& mean, float& rstd) {
    mean = s * (1.f / DM);
    asm("rsqrt.approx.ftz.f32 %0, %1;" : "=f"(rstd) : "f"(fmaxf(fmaf(-mean, mean, fmaf(q, 1.f / DM, 1e-5f)), 1e-5f)));
}
__device__ __forceinline__ uint32_t ln_apply(uint32_t w, float mean_b, float rden) {
    const uint32_t d = bsub2(w, __byte_perm(__float_as_uint(mean_b), 0, 0x3232));
    return pack2(bf_lo(d) * rden, bf_hi(d) * rden);
}
__device__ __forceinline__ void spread(uint32_t (&b)[10], uint32_t x01, uint32_t x2, uint32_t wa, uint32_t ra, bool e2) {
    sts16(wa, x01); sts16(wa + 8, x01 >> 16);
    sts16_if(!e2, wa + 16, x2);
    __syncwarp();
    const uint4 u = lds128(ra), v = lds128(ra + 16);
    const uint2 z = lds64(ra + 32);
    b[0] = u.x; b[1] = u.y; b[2] = u.z; b[3] = u.w; b[4] = v.x; b[5] = v.y; b[6] = v.z; b[7] = v.w; b[8] = z.x; b[9] = z.y;
}
__device__ __forceinline__ float fold(float a, float b, bool sel, int m) { return (sel ? b : a) + shx(sel ? a : b, m); }

__device__ __forceinline__ void chain_role(const Params& p, int w, int lane, uint32_t t0) {
    const int cta = blockIdx.x, h = cta >> 2, s = cta & 3;
    const int g = lane >> 2, t4 = lane & 3;
    const bool e1 = t4 & 1, e2 = t4 & 2;
    uint32_t wq[5][3][4], wo[3][5][4], wg[5][4], wh[5][2], wd[4][4];
    const int col0 = 80 * w + (e2 ? 48 : 0) + g + (e1 ? 8 : 0);
    const uint32_t xw = opaque(SM_X + w * 384 + 48 * (g >> 1) + (e2 ? 24 : 0) + (e1 ? 4 : 0) + 2 * (g & 1));
    const uint32_t xr = opaque(g == 1 ? SM_ONES : SM_X + w * 384 + (g == 3 ? 192 : 0) + 48 * t4);
    TRACES(75);
    sts32_if(lane < 12, SM_ONES + lane * 4, 0x3f803f80u);
    uint32_t zero = lane >> 5;
    const int mi = lane >> 3, mr = lane & 7;
    mbar_wait(bar_at(B_W), 0);
    TRACES(74);
    sts16(xw + 192, lds16(ST_X + 5120 + col0 * 2)); sts16(xw + 200, lds16(ST_X + 5120 + col0 * 2 + 32));
    sts16_if(!e2, xw + 208, lds16(ST_X + 5120 + col0 * 2 + 64));
#pragma unroll
    for (int i = 0; i < 5; i++)
#pragma unroll
        for (int mt = 0; mt < 3; mt++) ldsm4t(wq[i][mt], ST_WQ + (80 * w + 16 * i + mr + 8 * (mi >> 1)) * 96 + 32 * mt + 16 * (mi & 1), zero);
    const bool odd = cta & 1;
    const uint32_t lo = ST_WD + (mr + (odd ? 4 : 0)) * 1280 + 160 * w, hi = ST_WD + ((mr & 3) + (odd ? 0 : 8)) * 1280 + 160 * w;
    ldsm4t(wd[0], lo + 16 * mi, zero);
    ldsm4t(wd[1], lo + 64 + 16 * mi, zero);
    ldsm4t(wd[2], hi + 64 * (mi >> 1) + 32 * (mr >> 2) + 16 * (mi & 1), zero);
    ldsm4t(wd[3], (mi < 2 ? lo : hi) + 128 + 16 * (mi & 1), zero);
    fence_async();
    __syncwarp();
    mbar_arrive_if(lane == 0, bar_at(B_WC));
    mbar_wait(bar_at(B_EP), 0);
    const uint32_t near = __shfl_sync(0xffffffffu, lds32(SM_NEAR), 0);
    uint32_t x01 = 0, x2 = 0, nx01 = 0, nx2 = 0;
#pragma unroll 1
    for (int n = -5; n < NROUND; n++) {
        const bool last = (ORD_LAST >> (n & 15)) & 1, head = !((ORD_NO_HEAD >> (n & 15)) & 1);
        const int k = (ORD_BATCH >> (2 * (n & 15))) & 3;
        if (!last) bar_sync<2, 256>();
        TRACES(n <= 0 ? 83 + n : 95);
        const char* const slice = p.scr + acc_off(k, last, w);
        const char* const cell = opaque(slice + g * 256 + t4 * 16);
        const char* const watch = slice + near + (cta & 7) * 256 + ((cta >> 3) & 3) * 16;
        if (n >= 0) {
          if (head) {
            if (!last || n == NROUND - 1) mbar_wait(bar_at(B_Z), (k + last) & 1);
            const char* src = p.scr + SCR_O + head_off(h) + head_near(h, near) + last * 2048 + (w & 6) * 256 + (lane & 15) * 16;
            const uint32_t tag = lds32(SM_EPOCH) * NB + k;
            mbar_wait(bar_at(last ? B_RV : B_PS), k & 1);
            wait_clk(clk32() + (n < QUIET ? (last ? CFG(DLY_PB) : CFG(DLY_PL)) : CFG(DLY_P)));
            if (!last && k < NB - 1) wait_ns(t0 + batch_ns(k + 1) + CFG(START));
            uint4 v, z;
            {
                SPIN_DECL;
                while (true) {
                    v = ld_pkt(src); z = ld_pkt(src + 256);
                    if (__all_sync(0xffffffffu, (((v.w ^ tag) | (z.w ^ tag)) & 0xffu) == 0)) break;
                    SPIN_CHECK(n);
                }
            }
            TRACES(tr + 0);
            float a[3][4] = {};
            const uint32_t bb[3][2] = {{v.x, v.y}, {z.x, z.y}, {v.z, z.z}};
            float sa, sb;
#pragma unroll
            for (int i = 0; i < 3; i++) {
                const uint32_t l0 = g < 4 ? bb[i][0] : 0, l1 = g < 4 ? bb[i][1] : 0, h0 = g < 4 ? 0 : bb[i][0], h1 = g < 4 ? 0 : bb[i][1];
#pragma unroll
                for (int mt = 0; mt < 5; mt++)
                    mma16816(a[mt % 3], wo[i][mt][0], wo[i][mt][1], wo[i][mt][2], wo[i][mt][3], mt < 3 ? l0 : h0, mt < 3 ? l1 : h1);
                if (i == 0) {
                    const float am = F(v.w & 0xffffff00u), al = F(z.w & 0xffffff00u);
                    const float m0 = shi(am, 0), m1 = shi(am, 4), m2 = shi(am, 8), m3 = shi(am, 12);
                    const float s0 = shi(al, 0), s1 = shi(al, 4), s2 = shi(al, 8), s3 = shi(al, 12);
                    const float mb = fmaxf(fmaxf(m0, m1), fmaxf(m2, m3)) * LOG2E;
                    const float w0 = fast_ex2(fmaf(m0, LOG2E, -mb)), w1 = fast_ex2(fmaf(m1, LOG2E, -mb));
                    const float w2 = fast_ex2(fmaf(m2, LOG2E, -mb)), w3 = fast_ex2(fmaf(m3, LOG2E, -mb));
                    const float rl = fast_rcp(fmaf(w0, s0, w1 * s1) + fmaf(w2, s2, w3 * s3));
                    sa = (e1 ? w2 : w0) * rl; sb = (e1 ? w3 : w1) * rl;
                }
            }
            float y[3];
#pragma unroll
            for (int j = 2; j < 5; j++) {
                const int mt = j % 3;
                y[mt] = fold(fmaf(a[mt][0], sa, a[mt][1] * sb), fmaf(a[mt][2], sa, a[mt][3] * sb), e1, 1);
            }
            const uint32_t pa = SM_PO + w * 512 + lane * 16;
            if (w < 2) {
                const char* dst = opaque(cell + s * 16384);
                bar_sync<1, 256>();
                const uint4 c1 = lds128(pa), c2 = lds128(pa + 1024), c3 = lds128(pa + 2048);
                red_cell2_if(true, dst, (y[0] + F(c1.x)) + (F(c2.x) + F(c3.x)), (y[1] + F(c1.y)) + (F(c2.y) + F(c3.y)), (y[2] + F(c1.z)) + (F(c2.z) + F(c3.z)));
            } else {
                stsf4(pa - 1024, y[0], y[1], y[2], 0.f);
                bar_sync<1, 256>();
            }
            TRACES(tr + 1);
            if ((ORD_NO_TAIL >> n) & 1) continue;
            wait_clk(clk32() + (w < 2 ? 0 : 60) + (n < QUIET ? CFG(DLY_AL) : CFG(DLY_A)));
            {
                SPIN_DECL;
                if ((CFG(SENT) & 1) && n < QUIET) while (__any_sync(0xffffffffu, cell_count(watch) != FULL_A)) SPIN_CHECK(n);
                while (true) {
                    v = ld_pkt(cell + near);
                    if (__all_sync(0xffffffffu, v.w == FULL_A)) break;
                    SPIN_CHECK(n);
                }
            }
            TRACES(tr + 2);
            x01 = pack2(F(v.x), F(v.y));
            x2 = pack2(F(v.z), 0.f);
          } else { x01 = nx01; x2 = nx2; }
        } else if (n == -1) {
            mbar_wait(bar_at(B_W + 1), 0);
            const uint32_t ln = opaque(lane);
            const int mi = ln >> 3, mr = ln & 7;
            uint32_t zero = ln >> 5;
            TRACES(76);
#pragma unroll
            for (int i = 0; i < 3; i++) {
                const int d = 16 * (w >> 1) + (mr >> 1) + 8 * (mr & 1) + (i < 2 ? 64 * (mi >> 1) + 4 * i : 128 + 4 * (mi >> 1));
#pragma unroll
                for (int mt = 0; mt < 5; mt++) ldsm4t(wo[i][mt], ST_WO + d * 320 + 160 * (w & 1) + 32 * mt + 16 * (mi & 1), zero);
            }
            fence_async();
            __syncwarp();
            mbar_arrive_if(lane == 0, bar_at(B_WC + 1));
            mbar_wait(bar_at(B_W + 2), 0);
            TRACES(77);
#pragma unroll
            for (int i = 0; i < 5; i++) {
                const uint32_t ga = ST_WG + (mi & 1) * 20480 + (80 * w + 16 * i + mr + 8 * (mi >> 1)) * 32;
                uint32_t r[4];
                ldsm4t(wg[i], ga + (odd ? 16 : 0), zero);
                ldsm4t(r, ga + (odd ? 0 : 16), zero);
#pragma unroll
                for (int kh = 0; kh < 2; kh++) {
                    const uint32_t moved = __shfl_xor_sync(0xffffffffu, odd ? r[2 * kh] : r[2 * kh + 1], 16);
                    wh[i][kh] = (g < 4) == odd ? moved : odd ? r[2 * kh + 1] : r[2 * kh];
                }
            }
            fence_async();
            __syncwarp();
            mbar_arrive_if(lane == 0, bar_at(B_WC + 2));
            TRACES(72);
            x01 = 0x3f803f80u; x2 = 0x3f80u;
        } else {
            const uint32_t xa = ST_X + (n + 5) * 1280, ln = opaque(lane);
            const int col0 = 80 * w + (ln & 2 ? 48 : 0) + (ln >> 2) + (ln & 1 ? 8 : 0);
            float sm = 0.f, sq = 0.f;
#pragma unroll
            for (int i = 0; i < 5; i++) {
                const uint2 c = lds64(xa + i * 256 + ln * 8);
                sm += (bf_lo(c.x) + bf_hi(c.x)) + (bf_lo(c.y) + bf_hi(c.y));
                sq = fmaf(bf_lo(c.x), bf_lo(c.x), fmaf(bf_hi(c.x), bf_hi(c.x), fmaf(bf_lo(c.y), bf_lo(c.y), fmaf(bf_hi(c.y), bf_hi(c.y), sq))));
            }
            x01 = lds16(xa + col0 * 2) | lds16(xa + col0 * 2 + 32) << 16;
            x2 = lds16(xa + col0 * 2 + 64);
#pragma unroll
            for (int o = 16; o; o >>= 1) { sm += shx(sm, o); sq += shx(sq, o); }
            float mean_b, rden;
            ln_finish(sm, sq, mean_b, rden);
            x01 = ln_apply(x01, mean_b, rden);
            x2 = ln_apply(x2, mean_b, rden);
        }
        if (n >= -1) {
            uint32_t b[10];
            spread(b, x01, x2, xw, xr, e2);
            float a[2][4] = {};
#pragma unroll
            for (int i = 0; i < 5; i++) {
                mma16816(a[0], wg[i][0], wg[i][1], wg[i][2], wg[i][3], b[2 * i], b[2 * i + 1]);
                mma16816(a[1], wh[i][0], b[2 * i], wh[i][1], b[2 * i + 1], b[2 * i], b[2 * i + 1]);
            }
            stsf(SM_PG + (w >> 2) * 512 + (g + 8 * t4) * 16 + (w & 3) * 4, e2 ? (e1 ? a[1][2] : a[1][0]) : (e1 ? a[0][2] : a[0][0]));
            const uint2 cs = lds64(SM_CSG + lane * 48);
            const char* dst = opaque(cell + 3 * HALF - near);
            bar_sync<2, 256>();
            const float S = sum8(lds128(SM_PG + lane * 16), lds128(SM_PG + 512 + lane * 16));
            const float sx = shi(S, 25), sq = shi(S, 24), Su = shi(S, lane + (lane < 16 ? 8 : 4));
            if (n < 0) {
                if (w == 0) stsf2(SM_CSG + lane * 48, S, Su);
            } else {
                float mean_b, rden;
                ln_fast(sx, sq, mean_b, rden);
                const float gv = bfr(fmaf(-mean_b, F(cs.x), S) * rden), uv = bfr(fmaf(-mean_b, F(cs.y), Su) * rden);
                const float sg = fast_rcp(1.f + fast_ex2(-LOG2E * gv));
                const uint32_t hb = pack2(bfr(gv * sg) * uv, 0.f);
                const uint32_t b0 = __byte_perm(shi(hb, 2 * t4), shi(hb, 2 * t4 + 1), 0x5410);
                const uint32_t b1 = __byte_perm(shi(hb, e1 ? 18 : 16), shi(hb, e1 ? 19 : 17), 0x5410);
                const bool up = g >= 4;
                const uint32_t l0 = up ? 0 : b0, h0 = up ? b0 : 0;
                float d[3][4] = {};
                mma1688(d[0], wd[0][0], wd[0][1], l0); mma1688(d[1], wd[0][2], wd[0][3], l0); mma1688(d[2], wd[1][0], wd[1][1], l0);
                mma1688(d[0], wd[1][2], wd[1][3], h0); mma1688(d[1], wd[3][0], wd[3][1], h0);
                mma1688(d[2], wd[2][2], wd[2][3], up || e2 ? 0 : b1); mma1688(d[0], wd[2][0], wd[2][1], up || e2 ? 0 : b1);
                mma1688(d[1], wd[2][0], wd[2][1], !up && e2 ? b1 : 0);
                mma1688(d[0], wd[2][2], wd[2][3], up && e2 ? b1 : 0); mma1688(d[1], wd[3][2], wd[3][3], up && !e2 ? b1 : 0);
                red_cell(dst, e1 ? d[0][2] : d[0][0], e1 ? d[1][2] : d[1][0], e1 ? d[2][2] : d[2][0]);
                const uint32_t tsend = clk32();
                TRACES(tr + 3);
                if (last && w != cta >> 4) continue;
                if (!last && w == 0) st_pkt82_if(lane < 24, p.scr + SCR_Q + head_off(h) + 4 * 768 + (24 * s + lane) * 8, 0, 0);
                const float sgr = shi(sg, 27);
                const uint32_t sg2 = pack2(sgr, sgr);
                const uint32_t n01 = opaque(pack2((bf_lo(x01) - mean_b) * rden, (bf_hi(x01) - mean_b) * rden));
                const uint32_t n2 = opaque(pack2((bf_lo(x2) - mean_b) * rden, 0.f));
                if (last) {
                    sts128_if(lane >> 1 == (cta & 15), SM_FIN + (lane & 1) * 16, x01, n01, __byte_perm(x2, n2, 0x5410), sg2);
                    mbar_arrive_if(lane >> 1 == (cta & 15), bar_at(B_FIN));
                    __syncwarp();
                    continue;
                }
                if (n > 0) {
                    const char* src = p.scr + acc_off(k - 1, 1, w) + near + g * 256 + t4 * 16;
                    SPIN_DECL;
                    while (true) {
                        const uint4 u = ld_pkt(src);
                        nx01 = pack2(F(u.x), F(u.y)); nx2 = pack2(F(u.z), 0.f);
                        if (__all_sync(0xffffffffu, u.w == FULL_A)) break;
                        SPIN_CHECK(n);
                    }
                }
                wait_clk(tsend + (n < QUIET ? CFG(DLY_BL) : CFG(DLY_B)));
                uint4 v, z;
                {
                    SPIN_DECL;
                    while (true) {
                        v = ld_pkt(cell + 2 * HALF); z = ld_pkt(cell + 3 * HALF);
                        if (__all_sync(0xffffffffu, F(v.w) + F(z.w) == NCTA)) break;
                        SPIN_CHECK(n);
                    }
                }
                x01 = badd2(x01, badd2(n01, bmul2(pack2(F(v.x) + F(z.x), F(v.y) + F(z.y)), sg2)));
                x2 = badd2(x2, badd2(n2, bmul2(pack2(F(v.z) + F(z.z), 0.f), sg2)));
                TRACES(tr + 4);
            }
        }
        {
            uint32_t b[10];
            spread(b, x01, x2, xw, xr, e2);
            float a[3][4] = {};
            const float f0 = bf_lo(x01), f1 = bf_hi(x01), f2 = e2 ? 0.f : bf_lo(x2);
            float st = fold(fmaf(f0, f0, fmaf(f1, f1, f2 * f2)), (f0 + f1) + f2, e1, 1);
#pragma unroll
            for (int i = 0; i < 5; i++) {
#pragma unroll
                for (int mt = 0; mt < 3; mt++) mma16816(a[mt], wq[i][mt][0], wq[i][mt][1], wq[i][mt][2], wq[i][mt][3], b[2 * i], b[2 * i + 1]);
                if (i < 4) st += shx(st, 2 << i);
            }
            const uint32_t pa = SM_PQ + (w >> 2) * 1024 + ((e2 ? 32 : 0) + (e1 ? 8 : 0) + g) * 16 + (w & 3) * 4;
            stsf(pa + 256, e2 ? st : e1 ? a[1][2] : a[1][0]);
            stsf(pa, e2 ? (e1 ? a[2][2] : a[2][0]) : (e1 ? a[0][2] : a[0][0]));
            if (w == 0) {
                const uint2 cs = lds64(SM_CSQ + lane * 48);
                const uint32_t qtag = lds32(SM_EPOCH) * NB + (n < 0 ? n + 5 : k);
                const char* dst = opaque(p.scr + SCR_Q + head_off(h) + (n < 0 ? n + 5 : 4) * 768 + (24 * s + lane) * 8);
                bar_sync<3, 256>();
                const uint32_t ra = SM_PQ + lane * 32;
                float S0 = sum8(lds128(ra), lds128(ra + 1024)), S1 = sum8(lds128(ra + 16), lds128(ra + 1040));
                if (n >= 0) {
                    float mean_b, rden;
                    ln_fast(shi(S0, 28), shi(S0, 24), mean_b, rden);
                    S0 = fmaf(-mean_b, F(cs.x), S0) * rden;
                    S1 = fmaf(-mean_b, F(cs.y), S1) * rden;
                }
                if (n == -1) stsf2(SM_CSQ + lane * 48, S0, S1);
                st_pkt82_if(lane < 24 && n != -1, dst, pack2(S0, S1), qtag);
                mbar_arrive_if(lane == 0 && (n == -2 || n >= 0), bar_at(B_QS));
                TRACES(n >= 0 ? tr + 5 : 95);
            } else bar_arrive<3, 256>();
            red_cell2_if(n >= 0 && w * 16 + (lane >> 1) == cta, cell + 128, f0, f1, f2);
            __syncwarp();
        }
    }
}

template <int ID> __device__ __forceinline__ void role_exit() { asm volatile("exit; // %0" ::"n"(ID)); }
constexpr int NTHREADS = 512;
#define STR2(x) #x
#define STR(x) STR2(x)
__global__ void __launch_bounds__(NTHREADS, 1)
decode_kernel(const __grid_constant__ CUtensorMap tmK, const __grid_constant__ CUtensorMap tmV,
              const __grid_constant__ WeightMaps tmW, const Params p) {
    extern __shared__ __align__(1024) unsigned char smem[];
    const uint32_t t0 = now_ns();
    const int lane = threadIdx.x & 31;
    const int warp = __shfl_sync(0xffffffffu, threadIdx.x >> 5, 0);
    if (warp < 8) {
        asm volatile("setmaxnreg.inc.sync.aligned.u32 " STR(CFG_REG_CHAIN) ";");
        bar_sync<5, 480>();
        chain_role(p, warp, __shfl_sync(0xffffffffu, lane, lane), t0);
        role_exit<3>();
    } else if (warp < 12) {
        asm volatile("setmaxnreg.dec.sync.aligned.u32 " STR(CFG_REG_ATT) ";");
        if (elect_one()) {
#pragma unroll 1
            for (int i = warp - 8; i < NBAR; i += 4)
                if (i < B_W || i >= B_WC) mbar_init(bar_at(i), i == B_FIN ? 2 : i == B_QR ? 32 : i == B_PS || i == B_RP ? 4 : i >= B_F3 ? 1 : i >= B_WC ? 8 : i < B_RR || i > B_RV ? 1 : i < B_RK ? 2 : 4);
            asm volatile("fence.mbarrier_init.release.cluster;" ::: "memory");
            fence_async();
        }
        bar_sync<5, 480>();
        attention_role(p, warp - 8, lane);
        role_exit<2>();
    } else {
        asm volatile("setmaxnreg.dec.sync.aligned.u32 " STR(CFG_REG_HELP) ";");
        if (warp == 12) {
            TRACE(0);
            prefetch_role(p, &tmV, lane, t0);
            role_exit<0>();
        } else {
            if (warp == 14) {
                if (smem_u32(smem) != SB) __trap();
                if (elect_one()) {
                    asm volatile("prefetch.tensormap [%0];" ::"l"(&tmW.q) : "memory");
                    mbar_init(bar_at(B_W), 1); mbar_init(bar_at(B_W + 1), 1); mbar_init(bar_at(B_W + 2), 1);
                    asm volatile("fence.mbarrier_init.release.cluster;" ::: "memory");
                    fence_async();
                    mbar_expect_tx(bar_at(B_W), 61440 + 15360 + 6400); mbar_expect_tx(bar_at(B_W + 1), 61440); mbar_expect_tx(bar_at(B_W + 2), 40960);
                    bulk_load(ST_X, p.x, 5120, bar_at(B_W));
                    bulk_load(ST_X + 5120, p.wr, 1280, bar_at(B_W));
                }
                reload_role(p, &tmK, &tmV, &tmW, t0);
            } else {
                unsigned ticket = 0;
                if (warp == 15 && lane == 0) asm volatile("atom.relaxed.gpu.global.add.u32 %0, [%1], 1;" : "=r"(ticket) : "l"(&g_epoch) : "memory");
                if (warp == 13 && elect_one()) {
                    asm volatile("prefetch.tensormap [%0];" ::"l"(&tmW.g) : "memory");
                    asm volatile("prefetch.tensormap [%0];" ::"l"(&tmW.u) : "memory");
                    asm volatile("prefetch.tensormap [%0];" ::"l"(&tmW.o) : "memory");
                    asm volatile("prefetch.tensormap [%0];" ::"l"(&tmK) : "memory");
                    asm volatile("prefetch.tensormap [%0];" ::"l"(&tmV) : "memory");
                }
                bar_sync<5, 480>();
                if (warp == 13) { sts32(SM_PROG, 0); bar_arrive<6, 64>(); load_role(p, &tmK, &tmV, t0); }
                else zero_role(p, lane, ticket, t0);
            }
            role_exit<1>();
        }
    }
}

typedef CUresult (*EncodeFn)(CUtensorMap*, CUtensorMapDataType, cuuint32_t, void*, const cuuint64_t*, const cuuint64_t*,
                             const cuuint32_t*, const cuuint32_t*, CUtensorMapInterleave, CUtensorMapSwizzle,
                             CUtensorMapL2promotion, CUtensorMapFloatOOBfill);

bool make_map(EncodeFn fn, CUtensorMap* m, const void* ptr, uint64_t cols, uint64_t rows, uint32_t bc, uint32_t br) {
    cuuint64_t dims[2] = {cols, rows};
    cuuint64_t strides[1] = {cols * 2};
    cuuint32_t box[2] = {bc, br};
    cuuint32_t es[2] = {1, 1};
    return fn(m, CU_TENSOR_MAP_DATA_TYPE_BFLOAT16, 2, const_cast<void*>(ptr), dims, strides, box, es, CU_TENSOR_MAP_INTERLEAVE_NONE,
              CU_TENSOR_MAP_SWIZZLE_NONE, CU_TENSOR_MAP_L2_PROMOTION_L2_128B, CU_TENSOR_MAP_FLOAT_OOB_FILL_NONE) == CUDA_SUCCESS;
}

bool make_kv_map(EncodeFn fn, CUtensorMap* m, const void* ptr) {
    cuuint64_t dims[4] = {64, 8, 3, (cuuint64_t)NB * NHEAD * SK / 8};
    cuuint64_t strides[3] = {DH * 2, 128, 8 * DH * 2};
    cuuint32_t box[4] = {64, 8, 3, 4};
    cuuint32_t es[4] = {1, 1, 1, 1};
    return fn(m, CU_TENSOR_MAP_DATA_TYPE_BFLOAT16, 4, const_cast<void*>(ptr), dims, strides, box, es, CU_TENSOR_MAP_INTERLEAVE_NONE,
              CU_TENSOR_MAP_SWIZZLE_128B, CU_TENSOR_MAP_L2_PROMOTION_L2_128B, CU_TENSOR_MAP_FLOAT_OOB_FILL_NONE) == CUDA_SUCCESS;
}

}

extern "C" void kernel_launch(void* const* d_in, const int* in_sizes, int n_in, void* d_out, int out_size) {
    (void)in_sizes; (void)n_in; (void)out_size;
    static EncodeFn fn = nullptr;
    static const char* scr = nullptr;
    if (!fn) {
        void* f = nullptr;
        cudaDriverEntryPointQueryResult qr;
        if (cudaGetDriverEntryPoint("cuTensorMapEncodeTiled", &f, cudaEnableDefault, &qr) != cudaSuccess || !f) return;
        void* sp = nullptr;
        if (cudaGetSymbolAddress(&sp, g_scratch) != cudaSuccess) return;
        scr = (const char*)(((uintptr_t)sp + (2 << 20) - 1) & ~(uintptr_t)((2 << 20) - 1));
        fn = (EncodeFn)f;
        cudaFuncSetAttribute(decode_kernel, cudaFuncAttributeMaxDynamicSharedMemorySize, SMEM_BYTES);
    }
    CUtensorMap tmK, tmV;
    WeightMaps tmW;
    if (!make_kv_map(fn, &tmK, d_in[1]) || !make_kv_map(fn, &tmV, d_in[2])) return;
    if (!make_map(fn, &tmW.q, d_in[3], NHEAD * DH, DM, 48, 128) || !make_map(fn, &tmW.o, d_in[4], DM, NHEAD * DH, 160, 32)) return;
    if (!make_map(fn, &tmW.g, d_in[7], FF, DM, 16, 128) || !make_map(fn, &tmW.u, d_in[8], FF, DM, 16, 128)) return;
    Params p;
    p.x = (const unsigned short*)d_in[0];
    p.kc = (const char*)d_in[1];
    p.vc = (const char*)d_in[2];
    p.wq = (const char*)d_in[3];
    p.wo = (const char*)d_in[4];
    p.wr = (const unsigned short*)d_in[6];
    p.wg = (const char*)d_in[7];
    p.wu = (const char*)d_in[8];
    p.wd = (const char*)d_in[9];
    p.out = (unsigned short*)d_out;
    p.scr = scr;
    decode_kernel<<<NCTA, NTHREADS, SMEM_BYTES>>>(tmK, tmV, tmW, p);
}
```

```cpp
#include <cuda_runtime.h>
#include <cuda_bf16.h>
#include <cuda.h>
#include <stdint.h>

namespace {

constexpr int NB = 4, DM = 640, NHEAD = 32, DH = 192, SK = 4096, WIN = 1024, FF = 1536;
constexpr int NCTA = 128;
constexpr int TILE = 12288, PAIR = 2 * TILE;

#define CFG_LIST(X) \
    X(TICK0, 480)        \
    X(TICK, 516)        \
    X(TICKA, 0) \
    X(TICKB, 0) \
    X(TICKC, 0) \
    X(TICKD, 0) \
    X(STAG, 488)        \
    X(WLAG, 300)        \
    X(GSTEP, 700)        \
    X(WIN, 4)        \
    X(WIN2, 4)        \
    X(LMAX0, 300)        \
    X(LMAX, 400) \
    X(GAIN, 30)        \
    X(VSTEP, 300)        \
    X(RLAG, 0)        \
    X(RSTEP, 700) \
    X(RSTEP3, 390) \
    X(ZTILE, 10)        \
    X(START, 1)        \
    X(DLY_A, 400)        \
    X(DLY_AL, 100) \
    X(DLY_B, 600) \
    X(DLY_BL, 900) \
    X(DLY_F, 250) \
    X(DLY_PL, 100)        \
    X(DLY_PB, 300) \
    X(DLY_QL, 200) \
    X(FLIP, 0) \

#define X(n, v) constexpr int CFG_##n = v;
CFG_LIST(X)
#undef X
#define CFG(n) CFG_##n
constexpr int QUIET = 8;
#define CFG_REG_CHAIN 216
#define CFG_REG_ATT 48
#define CFG_REG_HELP 32
constexpr int KB_KV0 = 165;
__device__ __forceinline__ int kb_ns(int kb) { return kb * CFG(TICK0) / 12; }
__device__ __forceinline__ int tick_ns(int j) {
    return j <= 16 ? CFG(TICK0) : CFG(TICK) + (j & 8 ? (j & 4 ? CFG(TICKD) : CFG(TICKC)) : (j & 4 ? CFG(TICKB) : CFG(TICKA)));
}
__device__ __forceinline__ int batch_ns(int k) {
    return kb_ns(KB_KV0) + (k ? 16 * CFG(TICK0) + (k - 1) * 4 * (4 * CFG(TICK) + CFG(TICKA) + CFG(TICKB) + CFG(TICKC) + CFG(TICKD)) : 0);
}

__device__ __forceinline__ uint32_t slots(int k) { return k & 2 ? (k & 1 ? 0x04321658u : 0x65837104u) : (k & 1 ? 0x10482765u : 0x76543210u); }
__device__ __forceinline__ int pass_nibble(int k, int u) { return k > 0 ? 4 + (u & 1) : u; }
__device__ __forceinline__ uint32_t slot_at(uint32_t tab, int u) { return (tab >> (4 * u)) & 15; }

constexpr int NROUND = 11;
constexpr uint32_t ORD_BATCH = 0x3b9910, ORD_LAST = 0x6da, ORD_NO_HEAD = 0x248, ORD_NO_TAIL = 0x092;

constexpr uint32_t SB = 1024;
constexpr uint32_t SM_BAR = SB + 9 * PAIR;
constexpr int B_F1 = 0;
constexpr int B_RR = 24;
constexpr int B_RK = 32;
constexpr int B_RV = 36;
constexpr int B_Z = 37;
constexpr int B_EP = 38;
constexpr int B_W = 39;
constexpr int B_WC = 42;
constexpr int B_FIN = 45;
constexpr int B_F3 = 46;
constexpr int B_PS = 48;
constexpr int B_RP = 49;
constexpr int B_FL = 50;
constexpr int B_QR = 51;
constexpr int NBAR = 52;
__host__ __device__ constexpr uint32_t bar_at(int i) { return SM_BAR + 8 * i; }
constexpr uint32_t SM_EPOCH = SM_BAR + 416;
constexpr uint32_t SM_NEAR = SM_EPOCH + 8;
constexpr uint32_t SM_PROG = SM_EPOCH + 4;
constexpr uint32_t SM_MAX = SM_EPOCH + 16;
constexpr uint32_t SM_SUM = SM_MAX + 16;
constexpr uint32_t SM_FIN = SM_SUM + 32;
constexpr uint32_t SM_Q = SM_FIN + 32;
constexpr uint32_t PSTR = 144;
constexpr uint32_t SM_P = SM_Q + 5 * 384;
constexpr uint32_t SM_X = SM_P + 8 * PSTR;
constexpr uint32_t SM_CSG = SM_X + 40;
constexpr uint32_t SM_ONES = SM_X + 8 * 384;
constexpr uint32_t SM_PG = SM_ONES + 48;
constexpr uint32_t SM_PO = SM_PG + 1024;
constexpr uint32_t SM_PQ = SM_PO;
constexpr int SMEM_BYTES = SM_PO + 3072 - SB;
static_assert(SMEM_BYTES <= 232448 && SM_Q % 16 == 0 && SM_P % 16 == 0 && SM_X % 16 == 0 && SM_PO % 16 == 0, "smem");
constexpr uint32_t ST_WQ = SB, ST_WD = SB + 3 * PAIR, ST_WO = SB + 4 * PAIR, ST_WG = SB + 7 * PAIR, ST_X = ST_WG + 40960;

__device__ unsigned g_epoch;
__device__ unsigned g_init;
__device__ unsigned char g_scratch[4 << 20];
constexpr uint32_t HALF = 4096, SCR_O = 1 << 16, SCR_Q = 1 << 17, SCR_PROBE = 1 << 19;
__device__ __forceinline__ uint32_t acc_off(int k, int layer, int w) { return (k & 1) << 18 | (k >> 1) << 20 | (w >> 1) << 14 | (w & 1) << 11 | layer << 7; }
__device__ __forceinline__ uint32_t head_off(int h) { return (h & 3) << 14 | (h & 4) << 16 | (h & 8) << 17 | (h & 16) << 9; }
__device__ __forceinline__ uint32_t head_near(int h, uint32_t near) { return near ^ HALF ^ (h & 16) << 8; }
constexpr uint32_t FULL_A = 0x42040000u;

struct Params {
    const unsigned short* x;
    const char* kc;
    const char* vc;
    const char* wq;
    const char* wo;
    const unsigned short* wr;
    const char* wg;
    const char* wu;
    const char* wd;
    unsigned short* out;
    const char* scr;
};

__device__ __forceinline__ uint32_t smem_u32(const void* p) { return (uint32_t)__cvta_generic_to_shared(p); }
__device__ __forceinline__ void mbar_init(uint32_t a, uint32_t c) { asm volatile("mbarrier.init.shared::cta.b64 [%0], %1;" ::"r"(a), "r"(c) : "memory"); }
__device__ __forceinline__ void mbar_expect_tx(uint32_t a, uint32_t b) {
    asm volatile("mbarrier.arrive.expect_tx.shared::cta.b64 _, [%0], %1;" ::"r"(a), "r"(b) : "memory");
}
__device__ __forceinline__ void mbar_arrive(uint32_t a) { asm volatile("mbarrier.arrive.shared::cta.b64 _, [%0];" ::"r"(a) : "memory"); }
constexpr uint32_t SPIN_LIMIT = 1u << 22;
#define SPIN_DECL uint32_t spins = 0
#define SPIN_CHECK(info) { if (++spins > SPIN_LIMIT) __trap(); }
__device__ __forceinline__ void mbar_wait(uint32_t a, uint32_t parity) {
    uint32_t ok;
    SPIN_DECL;
    while (true) {
        asm volatile("{\n.reg .pred p;\nmbarrier.try_wait.parity.shared::cta.b64 p, [%1], %2;\nselp.u32 %0, 1, 0, p;\n}"
                     : "=r"(ok) : "r"(a), "r"(parity) : "memory");
        if (ok) break;
        SPIN_CHECK((a - SM_BAR) / 8 * 10 + parity);
    }
}
__device__ __forceinline__ uint32_t now_ns() { uint32_t t; asm volatile("mov.u32 %0, %%globaltimer_lo;" : "=r"(t) :: "memory"); return t; }
__device__ __forceinline__ uint32_t clk32() { uint32_t c; asm volatile("mov.u32 %0, %%clock;" : "=r"(c) :: "memory"); return c; }
__device__ __forceinline__ void wait_ns(uint32_t t) { while ((int)(now_ns() - t) < 0) {} }
__device__ __forceinline__ void wait_clk(uint32_t t) { while ((int)(clk32() - t) < 0) {} }
__device__ __forceinline__ bool elect_one() {
    uint32_t e;
    asm volatile("{\n.reg .pred p;\nelect.sync _|p, 0xffffffff;\nselp.u32 %0, 1, 0, p;\n}" : "=r"(e));
    return e;
}
constexpr uint64_t POL_FIRST = 0x12F0000000000000ull, POL_NORMAL = 0x1000000000000000ull;
__device__ __forceinline__ void tma_tile(uint32_t dst, const CUtensorMap* tm, int group, uint32_t bar, uint64_t pol) {
    asm volatile("cp.async.bulk.tensor.4d.shared::cluster.global.mbarrier::complete_tx::bytes.L2::cache_hint"
                 " [%0], [%1, {%3, %3, %3, %4}], [%2], %5;"
                 ::"r"(dst), "l"(tm), "r"(bar), "r"(0), "r"(group), "l"(pol) : "memory");
}
__device__ __forceinline__ void tma2d(uint32_t dst, const CUtensorMap* tm, int x, int y, uint32_t bar) {
    asm volatile("cp.async.bulk.tensor.2d.shared::cluster.global.mbarrier::complete_tx::bytes [%0], [%1, {%3, %4}], [%2];"
                 ::"r"(dst), "l"(tm), "r"(bar), "r"(x), "r"(y) : "memory");
}
__device__ __forceinline__ void bulk_load(uint32_t dst, const void* src, uint32_t bytes, uint32_t bar) {
    asm volatile("cp.async.bulk.shared::cluster.global.mbarrier::complete_tx::bytes [%0], [%1], %2, [%3];"
                 ::"r"(dst), "l"(src), "r"(bytes), "r"(bar) : "memory");
}
__device__ __forceinline__ void l2_prefetch(const void* p, uint32_t bytes) {
    asm volatile("cp.async.bulk.prefetch.L2.global [%0], %1;" ::"l"(p), "r"(bytes) : "memory");
}
__device__ __forceinline__ void mma16816(float (&c)[4], uint32_t a0, uint32_t a1, uint32_t a2, uint32_t a3, uint32_t b0, uint32_t b1) {
    asm volatile("mma.sync.aligned.m16n8k16.row.col.f32.bf16.bf16.f32 {%0,%1,%2,%3}, {%4,%5,%6,%7}, {%8,%9}, {%0,%1,%2,%3};"
                 : "+f"(c[0]), "+f"(c[1]), "+f"(c[2]), "+f"(c[3]) : "r"(a0), "r"(a1), "r"(a2), "r"(a3), "r"(b0), "r"(b1));
}
__device__ __forceinline__ void mma1688(float (&c)[4], uint32_t a0, uint32_t a1, uint32_t b0) {
    asm volatile("mma.sync.aligned.m16n8k8.row.col.f32.bf16.bf16.f32 {%0,%1,%2,%3}, {%4,%5}, {%6}, {%0,%1,%2,%3};"
                 : "+f"(c[0]), "+f"(c[1]), "+f"(c[2]), "+f"(c[3]) : "r"(a0), "r"(a1), "r"(b0));
}
__device__ __forceinline__ void ldsm4t(uint32_t (&r)[4], uint32_t a, uint32_t& zero) {
    asm volatile("ldmatrix.sync.aligned.m8n8.x4.trans.shared.b16 {%0,%1,%2,%3}, [%4];"
                 : "=r"(r[0]), "=r"(r[1]), "=r"(r[2]), "=r"(r[3]) : "r"(a + zero) : "memory");
    zero &= r[3];
}
__device__ __forceinline__ uint4 ld_pkt(const void* p) {
    uint4 v;
    asm volatile("{\n.reg .b128 t;\nld.relaxed.gpu.global.b128 t, [%4];\nmov.b128 {%0,%1,%2,%3}, t;\n}"
                 : "=r"(v.x), "=r"(v.y), "=r"(v.z), "=r"(v.w) : "l"(p) : "memory");
    return v;
}
__device__ __forceinline__ void st_pkt(const void* p, uint32_t a, uint32_t b, uint32_t c, uint32_t d) {
    asm volatile("{\n.reg .b128 t;\nmov.b128 t, {%1,%2,%3,%4};\nst.relaxed.gpu.global.b128 [%0], t;\n}"
                 ::"l"(p), "r"(a), "r"(b), "r"(c), "r"(d) : "memory");
}
__device__ __forceinline__ uint2 ld_pkt8(const void* p) {
    uint2 v;
    asm volatile("{\n.reg .b64 t;\nld.relaxed.gpu.global.b64 t, [%2];\nmov.b64 {%0,%1}, t;\n}" : "=r"(v.x), "=r"(v.y) : "l"(p) : "memory");
    return v;
}
__device__ __forceinline__ void red_cell(const char* p, float a, float b, float c) {
    asm volatile("red.relaxed.gpu.global.add.v4.f32 [%0], {%1,%2,%3,%4};" ::"l"(p), "f"(a), "f"(b), "f"(c), "f"(1.0f) : "memory");
}
#define PRED(n) "{\n.reg .pred p;\nsetp.ne.u32 p, %" #n ", 0;\n"
__device__ __forceinline__ void red_cell2_if(bool on, const char* p, float a, float b, float c) {
    asm volatile(PRED(5) "@p red.relaxed.gpu.global.add.v4.f32 [%0], {%1,%2,%3,%4};\n@p red.relaxed.gpu.global.add.v4.f32 [%0+4096], {%1,%2,%3,%4};\n}"
                 ::"l"(p), "f"(a), "f"(b), "f"(c), "f"(1.0f), "r"((uint32_t)on) : "memory");
}
__device__ __forceinline__ void st_pkt82_if(bool on, const void* p, uint32_t a, uint32_t b) {
    asm volatile(PRED(3) ".reg .b64 t;\nmov.b64 t, {%1,%2};\n@p st.relaxed.gpu.global.b64 [%0], t;\n@p st.relaxed.gpu.global.b64 [%0+4096], t;\n}"
                 ::"l"(p), "r"(a), "r"(b), "r"((uint32_t)on) : "memory");
}
__device__ __forceinline__ void st_pkt2_if(bool on, const void* p, uint32_t a, uint32_t b, uint32_t c, uint32_t d) {
    asm volatile(PRED(5) ".reg .b128 t;\nmov.b128 t, {%1,%2,%3,%4};\n@p st.relaxed.gpu.global.b128 [%0], t;\n@p st.relaxed.gpu.global.b128 [%0+4096], t;\n}"
                 ::"l"(p), "r"(a), "r"(b), "r"(c), "r"(d), "r"((uint32_t)on) : "memory");
}
__device__ __forceinline__ void mbar_arrive_if(bool on, uint32_t a) {
    asm volatile(PRED(1) "@p mbarrier.arrive.shared::cta.b64 _, [%0];\n}" ::"r"(a), "r"((uint32_t)on) : "memory");
}
__device__ __forceinline__ void sts16_if(bool on, uint32_t a, uint32_t v) {
    asm volatile(PRED(2) "@p st.shared.u16 [%0], %1;\n}" ::"r"(a), "h"((unsigned short)v), "r"((uint32_t)on) : "memory");
}
__device__ __forceinline__ void sts32_if(bool on, uint32_t a, uint32_t v) {
    asm volatile(PRED(2) "@p st.shared.u32 [%0], %1;\n}" ::"r"(a), "r"(v), "r"((uint32_t)on) : "memory");
}
__device__ __forceinline__ void sts128_if(bool on, uint32_t a, uint32_t x, uint32_t y, uint32_t z, uint32_t w) {
    asm volatile(PRED(5) "@p st.shared.v4.u32 [%0], {%1,%2,%3,%4};\n}" ::"r"(a), "r"(x), "r"(y), "r"(z), "r"(w), "r"((uint32_t)on) : "memory");
}
__device__ __forceinline__ float fast_rcp(float x) { float r; asm("rcp.approx.ftz.f32 %0, %1;" : "=f"(r) : "f"(x)); return r; }
__device__ __forceinline__ float fast_sqrt(float x) { float r; asm("sqrt.approx.ftz.f32 %0, %1;" : "=f"(r) : "f"(x)); return r; }
__device__ __forceinline__ float fast_ex2(float x) { float r; asm("ex2.approx.ftz.f32 %0, %1;" : "=f"(r) : "f"(x)); return r; }
__device__ __forceinline__ uint32_t pack2(float lo, float hi) {
    uint32_t r;
    asm("cvt.rn.bf16x2.f32 %0, %1, %2;" : "=r"(r) : "f"(hi), "f"(lo));
    return r;
}
__device__ __forceinline__ float bfr(float x) { return __uint_as_float(pack2(0.f, x)); }
__device__ __forceinline__ uint32_t badd2(uint32_t a, uint32_t b) { uint32_t r; asm("add.rn.bf16x2 %0, %1, %2;" : "=r"(r) : "r"(a), "r"(b)); return r; }
__device__ __forceinline__ uint32_t bsub2(uint32_t a, uint32_t b) { uint32_t r; asm("sub.rn.bf16x2 %0, %1, %2;" : "=r"(r) : "r"(a), "r"(b)); return r; }
__device__ __forceinline__ uint32_t bmul2(uint32_t a, uint32_t b) { uint32_t r; asm("mul.rn.bf16x2 %0, %1, %2;" : "=r"(r) : "r"(a), "r"(b)); return r; }
__device__ __forceinline__ float bf_lo(uint32_t w) { return __uint_as_float(w << 16); }
__device__ __forceinline__ float bf_hi(uint32_t w) { return __uint_as_float(w & 0xffff0000u); }
__device__ __forceinline__ float F(uint32_t t) { return __uint_as_float(t); }
__device__ __forceinline__ uint32_t lds16(uint32_t a) { unsigned short h; asm volatile("ld.shared.u16 %0, [%1];" : "=h"(h) : "r"(a) : "memory"); return h; }
__device__ __forceinline__ uint32_t lds32(uint32_t a) { uint32_t v; asm volatile("ld.shared.u32 %0, [%1];" : "=r"(v) : "r"(a) : "memory"); return v; }
__device__ __forceinline__ uint2 lds64(uint32_t a) {
    uint2 v; asm volatile("ld.shared.v2.u32 {%0,%1}, [%2];" : "=r"(v.x), "=r"(v.y) : "r"(a) : "memory"); return v;
}
__device__ __forceinline__ uint4 lds128(uint32_t a) {
    uint4 v; asm volatile("ld.shared.v4.u32 {%0,%1,%2,%3}, [%4];" : "=r"(v.x), "=r"(v.y), "=r"(v.z), "=r"(v.w) : "r"(a) : "memory"); return v;
}
__device__ __forceinline__ float sum8(const uint4& u, const uint4& v) {
    return ((F(u.x) + F(u.y)) + (F(u.z) + F(u.w))) + ((F(v.x) + F(v.y)) + (F(v.z) + F(v.w)));
}
__device__ __forceinline__ void sts16(uint32_t a, uint32_t v) { asm volatile("st.shared.u16 [%0], %1;" ::"r"(a), "h"((unsigned short)v) : "memory"); }
__device__ __forceinline__ void sts32(uint32_t a, uint32_t v) { asm volatile("st.shared.u32 [%0], %1;" ::"r"(a), "r"(v) : "memory"); }
__device__ __forceinline__ void stsf(uint32_t a, float v) { asm volatile("st.shared.f32 [%0], %1;" ::"r"(a), "f"(v) : "memory"); }
__device__ __forceinline__ void stsf2(uint32_t a, float x, float y) { asm volatile("st.shared.v2.f32 [%0], {%1,%2};" ::"r"(a), "f"(x), "f"(y) : "memory"); }
__device__ __forceinline__ void stsf4(uint32_t a, float x, float y, float z, float w) {
    asm volatile("st.shared.v4.f32 [%0], {%1,%2,%3,%4};" ::"r"(a), "f"(x), "f"(y), "f"(z), "f"(w) : "memory");
}
template <int ID, int N> __device__ __forceinline__ void bar_sync() { asm volatile("bar.sync %0, %1;" ::"n"(ID), "n"(N) : "memory"); }
template <int ID, int N> __device__ __forceinline__ void bar_arrive() { asm volatile("bar.arrive %0, %1;" ::"n"(ID), "n"(N) : "memory"); }
__device__ __forceinline__ void fence_async() { asm volatile("fence.proxy.async.shared::cta;" ::: "memory"); }
__device__ __forceinline__ float shx(float v, int m) { return __shfl_xor_sync(0xffffffffu, v, m); }
__device__ __forceinline__ float shi(float v, int l) { return __shfl_sync(0xffffffffu, v, l); }
__device__ __forceinline__ uint32_t shi(uint32_t v, int l) { return __shfl_sync(0xffffffffu, v, l); }
__device__ __forceinline__ uint32_t opaque(uint32_t x) { asm volatile("mov.u32 %0, %0;" : "+r"(x)); return x; }
__device__ __forceinline__ const char* opaque(const char* x) { asm volatile("mov.u64 %0, %0;" : "+l"(x)); return x; }
constexpr float LOG2E = 1.4426950408889634f;

#define TRACE(idx) do {} while (0)
#define TRACES(slot) do {} while (0)

__device__ __forceinline__ uint32_t probe_near(const Params& p, int w, int lane) {
    const int cta = blockIdx.x;
    const char* pr = p.scr + SCR_PROBE + (cta & 31) * 128 + (cta >> 5) * 16384 + ((w & 1) << 6 | (w & 2) << 17 | (w & 4) << 18);
    st_pkt2_if(lane < 2, pr + lane * 16, 0, 0, 0, 0);
    uint32_t best0 = ~0u, best1 = ~0u;
#pragma unroll 1
    for (int i = w & 1; i < 6 + (w & 1); i++) {
        uint32_t c = clk32(), v = 0;
        if (lane == 0) asm volatile("atom.relaxed.gpu.global.add.u32 %0, [%1], 1;" : "=r"(v) : "l"(pr + (i & 1) * HALF) : "memory");
        c += __shfl_sync(0xffffffffu, v, 0) >> 16;
        c = clk32() - c;
        if (i & 1) best1 = min(best1, c); else best0 = min(best0, c);
    }
    return best0 < best1;
}
__device__ __forceinline__ uint32_t near_half() {
    const uint2 v = lds64(SM_NEAR);
    return (__popc(v.x) + __popc(v.y) > 4) != (CFG(FLIP) != 0) ? HALF : 0;
}

__device__ __forceinline__ int kv_group(int k, int t) {
    const int cta = blockIdx.x;
    return ((k * NHEAD + (cta >> 2)) * SK + (SK - WIN) + (cta & 3) * 256 + t * 32) / 8;
}
__device__ __forceinline__ uint32_t phase_ns() { return (((blockIdx.x >> 2) * 13) & 31) * CFG(STAG) / 32; }

__device__ __forceinline__ void ln_fast(float s, float q, float& mean, float& rstd) {
    mean = s * (1.f / DM);
    asm("rsqrt.approx.ftz.f32 %0, %1;" : "=f"(rstd) : "f"(fmaxf(fmaf(-mean, mean, fmaf(q, 1.f / DM, 1e-5f)), 1e-5f)));
}
__device__ __forceinline__ void q_role(const Params& p, const CUtensorMap* tmV, int lane) {
    const int cta = blockIdx.x;
    mbar_wait(bar_at(B_EP), 0);
    const uint32_t tag0 = lds32(SM_EPOCH) * NB;
    const char* const qbox = p.scr + SCR_Q + head_off(cta >> 2) + lane * 8;
    const uint32_t near = head_near(cta >> 2, near_half());
    float cs0 = 0.f, cs1 = 0.f;
    uint32_t due = now_ns();
#pragma unroll 1
    for (int r = 0; r <= 2 * NB; r++) {
        const int slot = min(r, NB), k = r - NB;
        const uint32_t tag = tag0 + (r < NB ? r : k - 1);
        const char* const dst = qbox + slot * 768 + (cta & 3) * 192;
        const char* const src = qbox + slot * 768 + near;
        bar_sync<3, 288>();
        const uint32_t ra = SM_PQ + lane * 16;
        float S0 = sum8(lds128(ra), lds128(ra + 1024)), S1 = sum8(lds128(ra + 512), lds128(ra + 1536));
        if (k > 0) {
            float mean, rstd;
            ln_fast(shi(S1, 24), shi(S0, 24), mean, rstd);
            S0 = fmaf(-mean, cs0, S0) * rstd;
            S1 = fmaf(-mean, cs1, S1) * rstd;
        } else {
            bar_arrive<7, 288>();
            if (k == 0) { cs0 = S0; cs1 = S1; continue; }
        }
        st_pkt82_if(lane < 24, dst, pack2(S0, S1), tag);
        TRACES(k > 0 ? (k - 1) * 12 + 5 : 95);
        if (r < NB - 1) continue;
        if (k < NB) wait_clk(clk32() + CFG(DLY_QL));
#pragma unroll 1
        for (int back = k < 0 ? NB - 1 : 0; back >= 0; back--) {
            uint2 a, b, c;
            SPIN_DECL;
            do {
                a = ld_pkt8(src - back * 768); b = ld_pkt8(src - back * 768 + 256); c = ld_pkt8(src - back * 768 + 512);
                SPIN_CHECK(slot);
            } while (__any_sync(0xffffffffu, a.y != tag - back || b.y != tag - back || c.y != tag - back));
            const uint32_t qd = SM_Q + (slot - back) * 384 + lane * 4;
            sts32(qd, a.x); sts32(qd + 128, b.x); sts32(qd + 256, c.x);
        }
        fence_async();
        mbar_arrive(bar_at(B_QR));
        if (k < 1 || k == NB) continue;
#pragma unroll 1
        for (int t = 12; t < 16; t++) {
            mbar_wait(bar_at(B_RK + ((t >> 1) & 1)), (k - 1) & 1);
            SPIN_DECL;
            while ((int)lds32(SM_PROG) <= 16 * k + t) SPIN_CHECK(r);
            wait_ns(due);
            due = now_ns() + CFG(VSTEP);
            if (elect_one()) {
                mbar_expect_tx(bar_at(B_F1 + t), TILE);
                tma_tile(SB + slot_at(slots(k), t >> 1) * PAIR + (t & 1) * TILE, tmV, kv_group(k, t & 7), bar_at(B_F1 + t), POL_FIRST);
            }
            TRACE(256 + 16 * k + t);
        }
    }
}

struct WeightMaps { CUtensorMap q, o, g, u; };
__device__ __forceinline__ void load_role(const Params& p, const CUtensorMap* tmK, const CUtensorMap* tmV, uint32_t t0) {
    const int cta = blockIdx.x;
    t0 += phase_ns();
#pragma unroll 1
    for (int i = 0; i < 5; i++) {
        wait_ns(t0 + i * CFG(TICK0));
        if (elect_one()) l2_prefetch(p.wq + (size_t)(128 * i + cta) * 12288, 12288);
    }
    bar_sync<6, 64>();
    wait_ns(t0 + kb_ns(60));
    if (elect_one()) bulk_load(ST_WD, p.wd + cta * 15360, 15360, bar_at(B_W));
#pragma unroll 1
    for (int i = 0; i < 5; i++) {
        wait_ns(t0 + kb_ns(75) + i * kb_ns(6));
        if (elect_one()) { l2_prefetch(p.wg + (128 * i + cta) * 3072, 3072); l2_prefetch(p.wu + (128 * i + cta) * 3072, 3072); }
    }
#pragma unroll 1
    for (int i = 0; i < 6; i++) {
        wait_ns(t0 + kb_ns(105) + i * kb_ns(10));
        if (elect_one()) l2_prefetch(p.wo + (size_t)((cta >> 2) * DH + 32 * i + 8 * (cta & 3)) * 1280, 10240);
    }
    int shift = 0;
#pragma unroll 1
    for (int j = 0; j < 16 * NB; j++) {
        const int k = j >> 4, t = j & 15, u = t >> 1;
        if (j == 0 || j == 8 || j == 14) mbar_wait(bar_at(B_WC + j / 7), 0);
        if (k > 0 && t < 12) {
            if (t >= 4) mbar_wait(bar_at(B_RR + t - 4), k & 1);
            else if (t >= 2) mbar_wait(bar_at(B_RP), (k - 1) & 1);
            else if (k > 1) mbar_wait(bar_at(B_RK + 3), k & 1);
            else mbar_wait(bar_at(B_RR + t), 0);
        }
        const int jw = j - CFG(WIN);
        if (jw >= 0 && (jw < 16 || (jw & 15) < 12)) mbar_wait(bar_at(B_F1 + (jw & 15)), (jw >> 4) & 1);
        const int jv = j - CFG(WIN2);
        if (jv >= 16 && (jv & 15) >= 12 && t < 12) mbar_wait(bar_at(B_F1 + (jv & 15)), (jv >> 4) & 1);
        const uint32_t dst = SB + slot_at(slots(k), t < 8 ? pass_nibble(k, u) : u) * PAIR + (t & 1) * TILE;
        t0 += j ? tick_ns(j) : batch_ns(0);
        shift = max(shift - CFG(GAIN), 0);
        shift = max(shift, (int)(now_ns() - t0) - (j < 12 ? CFG(LMAX0) : CFG(LMAX)));
        wait_ns(t0 + shift);
        if (elect_one()) {
            if (k > 0 && t >= 12) {
                l2_prefetch(p.vc + (size_t)kv_group(k, t & 7) * 3072, TILE);
            } else {
                mbar_expect_tx(bar_at(B_F1 + t), TILE);
                tma_tile(dst, t & 8 ? tmV : tmK, kv_group(k, t & 7), bar_at(B_F1 + t), t < 10 && j >= 8 && j < 56 ? POL_NORMAL : POL_FIRST);
            }
            sts32(SM_PROG, j + 1);
        }
        TRACE(128 + j);
    }
}

__device__ __forceinline__ void reload_role(const Params& p, const CUtensorMap* tmK, const CUtensorMap* tmV, const WeightMaps* tm, uint32_t t0) {
    const int cta = blockIdx.x;
    t0 += CFG(TICK0) + CFG(WLAG) + phase_ns();
#pragma unroll 1
    for (int i = 0; i < 5; i++) {
        wait_ns(t0 + i * CFG(TICK0));
        if (elect_one()) tma2d(ST_WQ + i * 12288, &tm->q, 48 * cta, 128 * i, bar_at(B_W));
        if (i == 1) bar_sync<5, 480>();
    }
#pragma unroll 1
    for (int i = 0, o = 0; i < 10;) {
        const uint32_t now = now_ns() - t0;
        if (o < 6 && (int)now >= kb_ns(105) + o * kb_ns(10)) {
            if (elect_one()) tma2d(ST_WO + o * 10240, &tm->o, 160 * (cta & 3), (cta >> 2) * DH + 32 * o, bar_at(B_W + 1));
            o++;
        } else if ((int)now >= kb_ns(77) + i * CFG(GSTEP) && (i < 9 || o == 6)) {
            if (elect_one()) tma2d(ST_WG + (i & 1) * 20480 + (i >> 1) * 4096, i & 1 ? &tm->u : &tm->g, (12 * cta) & ~7, 128 * (i >> 1), bar_at(B_W + 2));
            i++;
        }
    }
#pragma unroll 1
    for (int k = 0; k < NB - 1; k++) {
        mbar_wait(bar_at(B_RK + 2), k & 1);
        if (elect_one()) {
            const uint32_t dst = SB + slot_at(slots(k), 2) * PAIR;
            mbar_expect_tx(bar_at(B_FL), PAIR);
            tma_tile(dst, tmV, kv_group(k, 0), bar_at(B_FL), POL_FIRST);
            tma_tile(dst + TILE, tmV, kv_group(k, 1), bar_at(B_FL), POL_FIRST);
        }
        mbar_wait(bar_at(B_RV), k & 1);
        uint32_t due = now_ns() + (k == NB - 2 ? 0 : CFG(RLAG));
        if (elect_one()) mbar_expect_tx(bar_at(B_F3), 4 * PAIR);
#pragma unroll 1
        for (int t = 0; t < 8; t++) {
            wait_ns(due);
            due += k == NB - 2 ? CFG(RSTEP3) : CFG(RSTEP);
            if (elect_one())
                tma_tile(SB + slot_at(slots(k + 1), t >> 1) * PAIR + (t & 1) * TILE, tmK, kv_group(k + 1, t), bar_at(B_F3), POL_FIRST);
        }
        TRACE(121 + k);
    }
}

__device__ __forceinline__ void zero_role(const Params& p, int lane, unsigned ticket, uint32_t t0) {
    const int cta = blockIdx.x;
    const uint32_t epoch = __shfl_sync(0xffffffffu, ticket, 0) / NCTA + 1;
    if (lane == 0) { sts32(SM_EPOCH, epoch); mbar_arrive(bar_at(B_EP)); }
#pragma unroll 1
    for (int k = 0; k < NB + 2; k++) {
        lane = opaque(lane);
        const int cl = 2 * (cta & 15) + (lane & 1);
        const int col = 80 * (cta >> 4) + (cl & 2 ? 48 : 0) + (cl >> 2) + (cl & 1 ? 8 : 0);
        const char* own = p.scr + (cl >> 2) * 256 + (cl & 3) * 16;
        if (k < NB) {
            wait_ns(t0 + batch_ns(k) + CFG(ZTILE) * CFG(TICK0));
            const int lg = lane >> 3, ty = (lane & 7) >> 1;
            const char* dst = own + acc_off((k - (lg >> 1)) & 3, lg != 0, cta >> 4) + ty * HALF;
            uint32_t v0 = 0, v1 = 0, v2 = 0, v3 = 0;
            if (lane < 4) {
                const unsigned short* xp = p.x + k * DM + col;
                v0 = __ldg(xp) << 16; v1 = __ldg(xp + 16) << 16; v2 = cl & 2 ? 0 : __ldg(xp + 32) << 16; v3 = 0x3f800000u;
            }
            if (lg == 0 || (lg == 1 && (ty < 2 || k == NB - 1)) || (lg == 2 && k > 0 && ty > 1)) st_pkt(dst, v0, v1, v2, v3);
            asm volatile("fence.acq_rel.gpu;" ::: "memory");
            __syncwarp();
            if (lane == 0) asm volatile("red.relaxed.gpu.global.add.u32 [%0], 1;" ::"l"(&g_init) : "memory");
            const uint32_t target = ((epoch - 1) * NB + k + 1) * NCTA;
            SPIN_DECL;
            while (true) {
                __nanosleep(400);
                uint32_t v;
                asm volatile("ld.acquire.gpu.global.u32 %0, [%1];" : "=r"(v) : "l"(&g_init) : "memory");
                if (__all_sync(0xffffffffu, (int)(v - target) >= 0)) break;
                SPIN_CHECK(v);
            }
        }
        uint4 r;
        if (k == 1) mbar_wait(bar_at(B_RK), 0);
        if (k > 1) {
            mbar_wait(bar_at(B_FIN), k & 1);
            r = lds128(SM_FIN + (lane & 1) * 16);
        }
        __syncwarp();
        if (lane == 0) mbar_arrive(bar_at(B_Z));
        if (k > 1) {
            const int b = k - 2;
            const char* src = own + acc_off(b, 1, cta >> 4) + (2 + ((lane >> 1) & 1)) * HALF;
            unsigned short* o = p.out + b * DM + col;
            wait_clk(clk32() + CFG(DLY_F));
            uint4 v = {};
            SPIN_DECL;
            while (true) {
                v = ld_pkt(src);
                if (__all_sync(0xffffffffu, F(v.w) + shx(F(v.w), 2) == NCTA)) break;
                SPIN_CHECK(k);
            }
            const float y0 = F(v.x) + shx(F(v.x), 2), y1 = F(v.y) + shx(F(v.y), 2), y2 = F(v.z) + shx(F(v.z), 2);
            const uint32_t x01 = badd2(r.x, badd2(r.y, bmul2(pack2(y0, y1), r.w)));
            const uint32_t x2 = badd2(r.z, badd2(r.z >> 16, bmul2(pack2(y2, 0.f), r.w)));
            if (lane < 2) {
                o[0] = x01; o[16] = x01 >> 16;
                if (!(cl & 2)) o[32] = x2;
            }
            TRACES((2 * b + 1) * 6 + 4);
        }
    }
}

__host__ __device__ constexpr uint32_t desc_lo(uint32_t addr) { return ((addr & 0x3FFFFu) >> 4) | (1u << 16); }
constexpr uint32_t DESC_HI_TILE = (3072u >> 4) | (1u << 30);
constexpr uint32_t DESC_HI_VEC = 1u;
template <int TA, int AOFF, int BOFF>
__device__ __forceinline__ void wgmma_n8(float (&d)[4], uint32_t alo, uint32_t blo, int accumulate) {
    asm volatile("{\n.reg .pred p;\n.reg .b32 a, b;\n.reg .b64 da, db;\nsetp.ne.b32 p, %6, 0;\n"
                 "add.u32 a, %4, %8;\nadd.u32 b, %5, %9;\nmov.b64 da, {a, %10};\nmov.b64 db, {b, %11};\n"
                 "wgmma.mma_async.sync.aligned.m64n8k16.f32.bf16.bf16 {%0,%1,%2,%3}, da, db, p, 1, 1, %7, 0;\n}"
                 : "+f"(d[0]), "+f"(d[1]), "+f"(d[2]), "+f"(d[3])
                 : "r"(alo), "r"(blo), "r"(accumulate), "n"(TA), "n"(AOFF >> 4), "n"(BOFF >> 4), "n"(DESC_HI_TILE), "n"(DESC_HI_VEC));
}
template <int KS>
__device__ __forceinline__ void qk_steps(float (&d)[4], uint32_t alo, uint32_t blo) {
    if constexpr (KS < 12) {
        wgmma_n8<0, (KS >> 2) * 1024 + (KS & 3) * 32, KS * 32>(d, alo, blo, KS > 0);
        qk_steps<KS + 1>(d, alo, blo);
    }
}
__device__ __forceinline__ void pv_steps(float (&e)[3][4], uint32_t alo, uint32_t blo, int acc) {
    wgmma_n8<1, 0, 0>(e[0], alo, blo, acc); wgmma_n8<1, 1024, 0>(e[1], alo, blo, acc); wgmma_n8<1, 2048, 0>(e[2], alo, blo, acc);
    wgmma_n8<1, 6144, 32>(e[0], alo, blo, 1); wgmma_n8<1, 7168, 32>(e[1], alo, blo, 1); wgmma_n8<1, 8192, 32>(e[2], alo, blo, 1);
}
__device__ __forceinline__ void wg_fence() { asm volatile("wgmma.fence.sync.aligned;" ::: "memory"); }
__device__ __forceinline__ void wg_commit() { asm volatile("wgmma.commit_group.sync.aligned;" ::: "memory"); }
template <int N> __device__ __forceinline__ void wg_wait() { asm volatile("wgmma.wait_group.sync.aligned %0;" ::"n"(N) : "memory"); }
__device__ __forceinline__ void qk_pair(float (&d)[4], uint32_t slot, uint32_t qslot) {
    wg_fence();
    qk_steps<0>(d, desc_lo(SB) + slot * (PAIR >> 4), desc_lo(SM_Q) + qslot * (384 >> 4));
    wg_commit();
}
__device__ __forceinline__ void acc_ready(float (&d)[4]) { asm volatile("" : "+f"(d[0]), "+f"(d[1]), "+f"(d[2]), "+f"(d[3]) :: "memory"); }
__device__ __forceinline__ uint32_t score_pair(float (&d)[4], int lane) {
    acc_ready(d);
    const float scale = 0.07216878364870322f;
    const uint32_t r = pack2(d[0], d[2]);
    return shi(pack2(bf_lo(r) * scale, bf_hi(r) * scale), lane & 28);
}

__device__ __forceinline__ void attention_role(const Params& p, int w, int lane) {
    const int cta = blockIdx.x, t4 = lane & 3, g = lane >> 2;
    mbar_wait(bar_at(B_EP), 0);
    const uint32_t tag0 = lds32(SM_EPOCH) * NB;
    const char* const odst = p.scr + SCR_O + head_off(cta >> 2) + (2 * w + (g >> 2)) * 256 + (cta & 3) * 64 + (g & 3) * 16;
    const uint32_t pdst = SM_P + t4 * PSTR + (16 * w + g) * 2;
    auto softmax = [&](uint32_t sc, int ps) -> uint32_t {
        const float s0 = bf_lo(sc), s1 = bf_hi(sc);
        int key = __float_as_int(fmaxf(s0, s1));
        key ^= (key >> 31) & 0x7fffffff;
        key = __reduce_max_sync(0xffffffffu, key);
        sts32(SM_MAX + w * 4, key);
        bar_sync<4, 128>();
        const uint4 mx = lds128(SM_MAX);
        key = max(max((int)mx.x, (int)mx.y), max((int)mx.z, (int)mx.w));
        key ^= (key >> 31) & 0x7fffffff;
        const float mb = __int_as_float(key) * LOG2E;
        const uint32_t pp = pack2(fast_ex2(fmaf(s0, LOG2E, -mb)), fast_ex2(fmaf(s1, LOG2E, -mb)));
        sts16(pdst + ps * 4 * PSTR, pp); sts16(pdst + ps * 4 * PSTR + 16, pp >> 16);
        uint32_t fs;
        asm volatile("redux.sync.add.u32 %0, %1, 0xffffffff;" : "=r"(fs) : "r"(__float2uint_rn((bf_lo(pp) + bf_hi(pp)) * 8388608.f)));
        fence_async();
        bar_sync<4, 128>();
        sts32(SM_SUM + ps * 16 + w * 4, fs);
        return key;
    };
    auto aux_word = [&](uint32_t mx, const uint4& u, int k) {
        const float l = __uint2float_rn((u.x + u.y) + (u.z + u.w)) * (1.f / 8388608.f);
        return (g < 4 ? mx : (__float_as_uint(l) + 0x80u) & 0xffffff00u) | ((tag0 + k) & 0xffu);
    };
    auto send = [&](float (&e)[3][4], uint32_t aux, int ps) {
        acc_ready(e[0]); acc_ready(e[1]); acc_ready(e[2]);
        const uint32_t o0 = pack2(e[0][0], e[0][2]), o1 = pack2(e[1][0], e[1][2]), o2 = pack2(e[2][0], e[2][2]);
        st_pkt2_if(t4 == 0, odst + ps * 2048, o0, o1, o2, aux);
        mbar_arrive_if(lane == 0, bar_at(ps ? B_RV : B_PS));
    };
    mbar_wait(bar_at(B_QR), 0);
    TRACES(73);
#pragma unroll 1
    for (int it = 0; it <= NB; it++) {
        uint32_t m1 = 0;
        if (it < NB) {
            const uint32_t tab = slots(it);
            uint32_t sc = 0;
#pragma unroll 1
            for (int t = 0; t < 8; t++) {
                const uint32_t alo = desc_lo(SB) + slot_at(tab, pass_nibble(it, t >> 1)) * (PAIR >> 4), blo = desc_lo(SM_Q) + it * (384 >> 4);
                mbar_wait(bar_at(B_F1 + t), it & 1);
                float d[4] = {};
#pragma unroll 1
                for (int c = 0; c < 3; c++) {
                    wg_fence();
                    wgmma_n8<0, 0, 0>(d, alo + c * 64, blo + c * 8, c > 0); wgmma_n8<0, 32, 32>(d, alo + c * 64, blo + c * 8, 1);
                    wgmma_n8<0, 64, 64>(d, alo + c * 64, blo + c * 8, 1); wgmma_n8<0, 96, 96>(d, alo + c * 64, blo + c * 8, 1);
                    wg_commit();
                    wg_wait<0>();
                }
                if ((t & 1) == (w >> 1)) {
                    mbar_arrive_if(lane == 0, bar_at(B_RR + t));
                    const uint32_t s = score_pair(d, lane);
                    if (t4 == t >> 1) sc = s;
                }
            }
            m1 = softmax(sc, 0);
        }
        if (it > 0) {
            const int k = it - 1;
            const uint32_t tab = slots(k);
            const uint32_t v0 = slot_at(tab, k < NB - 1 ? 2 : 4);
            TRACES(48 + k * 6);
            if (k > 0) mbar_wait(bar_at(B_F3), it & 1);
            mbar_wait(bar_at(B_QR), it & 1);
            TRACES(49 + k * 6);
            float d[4][4] = {};
#pragma unroll
            for (int u = 0; u < 4; u++) {
                qk_pair(d[u], slot_at(tab, u), 4);
                if (u > 0) { wg_wait<1>(); mbar_arrive_if(lane == 0, bar_at(B_RK + u - 1)); }
            }
            uint32_t sc = score_pair(d[0], lane), s = score_pair(d[1], lane);
            if (t4 == 1) sc = s;
            s = score_pair(d[2], lane);
            if (t4 == 2) sc = s;
            wg_wait<0>();
            s = score_pair(d[3], lane);
            mbar_arrive_if(lane == 0, bar_at(B_RK + 3));
            if (t4 == 3) sc = s;
            TRACES(50 + k * 6);
            const uint32_t m2 = softmax(sc, 1);
            TRACES(51 + k * 6);
            float e[3][4] = {};
            uint4 u;
            wg_fence();
#pragma unroll
            for (int t = 0; t < 8; t++) {
                const int pr = ((t >> 1) + 1) & 3;
                if (t == 6 && k < NB - 1) mbar_wait(bar_at(B_FL), k & 1);
                if (t == 7) { bar_sync<4, 128>(); u = lds128(SM_SUM + 16); }
                if (t == 1 || t == 6) wg_fence();
                pv_steps(e, desc_lo(SB + (t & 1) * TILE) + (pr ? slot_at(tab, 4 + pr) : v0) * (PAIR >> 4), desc_lo(SM_P + (4 + pr) * PSTR + (t & 1) * 64), t > 0);
                if (t == 0) st_pkt2_if(t4 == 0, odst + 2048, 0, 0, 0, tag0 + k + 128);
            }
            wg_commit();
            const uint32_t aux = opaque(aux_word(m2, u, k));
            wg_wait<0>();
            send(e, aux, 1);
            TRACES(52 + k * 6);
        }
        if (it < NB) {
            const uint32_t tab = slots(it);
            st_pkt2_if(t4 == 0, odst, 0, 0, 0, tag0 + it + 128);
            bar_sync<4, 128>();
            const uint32_t aux = opaque(aux_word(m1, lds128(SM_SUM), it));
            float e[3][4] = {};
#pragma unroll 1
            for (int u = 0; u < 4; u++) {
                const uint32_t alo = desc_lo(SB) + slot_at(tab, 4 + u) * (PAIR >> 4), blo = desc_lo(SM_P) + u * (PSTR >> 4);
                mbar_wait(bar_at(B_F1 + 8 + 2 * u), it & 1);
                wg_fence();
                pv_steps(e, alo, blo, u > 0);
                wg_commit();
                if (u == 1) { wg_wait<1>(); mbar_arrive_if(lane == 0, bar_at(B_RP)); }
                mbar_wait(bar_at(B_F1 + 9 + 2 * u), it & 1);
                wg_fence();
                pv_steps(e, alo + (TILE >> 4), blo + 4, 1);
                wg_commit();
            }
            wg_wait<0>();
            send(e, aux, 0);
            TRACES(53 + it * 6);
        }
    }
}

__device__ __forceinline__ void ln_finish(float s, float q, float& mean_b, float& rden) {
    const float mean = s * (1.f / DM);
    const float var = fmaxf(fmaf(q, 1.f / DM, -mean * mean), 0.f);
    mean_b = bfr(mean);
    rden = fast_rcp(bfr(fast_sqrt(bfr(bfr(var) + 1e-5f))));
}
__device__ __forceinline__ uint32_t ln_apply(uint32_t w, float mean_b, float rden) {
    const uint32_t d = bsub2(w, __byte_perm(__float_as_uint(mean_b), 0, 0x3232));
    return pack2(bf_lo(d) * rden, bf_hi(d) * rden);
}
__device__ __forceinline__ void spread(uint32_t (&b)[10], uint32_t x01, uint32_t x2, uint32_t wa, uint32_t ra, bool e2) {
    sts16(wa, x01); sts16(wa + 8, x01 >> 16);
    sts16_if(!e2, wa + 16, x2);
    __syncwarp();
    const uint4 u = lds128(ra), v = lds128(ra + 16);
    const uint2 z = lds64(ra + 32);
    b[0] = u.x; b[1] = u.y; b[2] = u.z; b[3] = u.w; b[4] = v.x; b[5] = v.y; b[6] = v.z; b[7] = v.w; b[8] = z.x; b[9] = z.y;
}
__device__ __forceinline__ float fold(float a, float b, bool sel, int m) { return (sel ? b : a) + shx(sel ? a : b, m); }

__device__ __forceinline__ void chain_role(const Params& p, int w, int lane, uint32_t t0) {
    const int cta = blockIdx.x, h = cta >> 2, s = cta & 3;
    const int g = lane >> 2, t4 = lane & 3;
    const bool e1 = t4 & 1, e2 = t4 & 2;
    uint32_t wq[5][3][4], wo[3][5][4], wg[5][4], wh[5][2], wd[4][4];
    const int col0 = 80 * w + (e2 ? 48 : 0) + g + (e1 ? 8 : 0);
    const uint32_t xw = opaque(SM_X + w * 384 + 48 * (g >> 1) + (e2 ? 24 : 0) + (e1 ? 4 : 0) + 2 * (g & 1));
    const uint32_t xr = opaque(g == 1 ? SM_ONES : SM_X + w * 384 + (g == 3 ? 192 : 0) + 48 * t4);
    TRACES(75);
    sts32_if(lane < 12, SM_ONES + lane * 4, 0x3f803f80u);
    uint32_t zero = lane >> 5;
    const int mi = lane >> 3, mr = lane & 7;
    mbar_wait(bar_at(B_W), 0);
    TRACES(74);
    sts16(xw + 192, lds16(ST_X + 5120 + col0 * 2)); sts16(xw + 200, lds16(ST_X + 5120 + col0 * 2 + 32));
    sts16_if(!e2, xw + 208, lds16(ST_X + 5120 + col0 * 2 + 64));
#pragma unroll
    for (int i = 0; i < 5; i++)
#pragma unroll
        for (int mt = 0; mt < 3; mt++) ldsm4t(wq[i][mt], ST_WQ + (80 * w + 16 * i + mr + 8 * (mi >> 1)) * 96 + 32 * mt + 16 * (mi & 1), zero);
    const bool odd = cta & 1;
    const uint32_t lo = ST_WD + (mr + (odd ? 4 : 0)) * 1280 + 160 * w, hi = ST_WD + ((mr & 3) + (odd ? 0 : 8)) * 1280 + 160 * w;
    ldsm4t(wd[0], lo + 16 * mi, zero);
    ldsm4t(wd[1], lo + 64 + 16 * mi, zero);
    ldsm4t(wd[2], hi + 64 * (mi >> 1) + 32 * (mr >> 2) + 16 * (mi & 1), zero);
    ldsm4t(wd[3], (mi < 2 ? lo : hi) + 128 + 16 * (mi & 1), zero);
    fence_async();
    __syncwarp();
    mbar_arrive_if(lane == 0, bar_at(B_WC));
    mbar_wait(bar_at(B_EP), 0);
    const uint32_t near = __shfl_sync(0xffffffffu, near_half(), 0);
    uint32_t x01 = 0, x2 = 0, nx01 = 0, nx2 = 0;
#pragma unroll 1
    for (int n = -5; n < NROUND; n++) {
        const bool last = (ORD_LAST >> (n & 15)) & 1, head = !((ORD_NO_HEAD >> (n & 15)) & 1);
        const int k = (ORD_BATCH >> (2 * (n & 15))) & 3;
        if (n > -5 && n <= 0) bar_sync<7, 288>();
        else if (!last) bar_sync<2, 256>();
        TRACES(n <= 0 ? 83 + n : 95);
        const char* const slice = p.scr + acc_off(k, last, w);
        const char* const cell = opaque(slice + g * 256 + t4 * 16);
        if (n >= 0) {
          if (head) {
            if (!last || n == NROUND - 1) mbar_wait(bar_at(B_Z), (k + last) & 1);
            const char* src = p.scr + SCR_O + head_off(h) + head_near(h, near) + last * 2048 + (w & 6) * 256 + (lane & 15) * 16;
            const uint32_t tag = lds32(SM_EPOCH) * NB + k;
            mbar_wait(bar_at(last ? B_RV : B_PS), k & 1);
            if (n < QUIET) wait_clk(clk32() + (last ? CFG(DLY_PB) : CFG(DLY_PL)));
            if (!last && k < NB - 1) wait_ns(t0 + batch_ns(k + 1) + CFG(START));
            uint4 v, z;
            {
                SPIN_DECL;
                do {
                    v = ld_pkt(src); z = ld_pkt(src + 256);
                    SPIN_CHECK(n);
                } while (__any_sync(0xffffffffu, (((v.w ^ tag) | (z.w ^ tag)) & 0xffu) != 0));
            }
            TRACES(tr + 0);
            float a[3][4] = {};
            const uint32_t bb[3][2] = {{v.x, v.y}, {z.x, z.y}, {v.z, z.z}};
            float sa, sb, rl;
#pragma unroll
            for (int i = 0; i < 3; i++) {
                const uint32_t l0 = g < 4 ? bb[i][0] : 0, l1 = g < 4 ? bb[i][1] : 0, h0 = g < 4 ? 0 : bb[i][0], h1 = g < 4 ? 0 : bb[i][1];
#pragma unroll
                for (int mt = 0; mt < 5; mt++)
                    mma16816(a[mt % 3], wo[i][mt][0], wo[i][mt][1], wo[i][mt][2], wo[i][mt][3], mt < 3 ? l0 : h0, mt < 3 ? l1 : h1);
                if (i == 0) {
                    int key = v.w & 0xffffff00u;
                    key ^= (key >> 31) & 0x7fffffff;
                    key = __reduce_max_sync(0xffffffffu, key);
                    key ^= (key >> 31) & 0x7fffffff;
                    const float ws = fast_ex2((F(v.w & 0xffffff00u) - __int_as_float(key)) * LOG2E);
                    sa = shi(ws, e1 ? 8 : 0); sb = shi(ws, e1 ? 12 : 4);
                    rl = ws * F(z.w & 0xffffff00u);
                    rl += shx(rl, 4);
                }
                if (i == 1) rl += shx(rl, 8);
            }
            float y[3];
#pragma unroll
            for (int j = 2; j < 5; j++) {
                const int mt = j % 3;
                y[mt] = fold(fmaf(a[mt][0], sa, a[mt][1] * sb), fmaf(a[mt][2], sa, a[mt][3] * sb), e1, 1);
            }
            const uint32_t pa = SM_PO + w * 512 + lane * 16;
            if (w < 2) {
                const char* dst = opaque(cell + s * 16384);
                rl = fast_rcp(rl);
                bar_sync<1, 256>();
                const uint4 c1 = lds128(pa), c2 = lds128(pa + 1024), c3 = lds128(pa + 2048);
                red_cell2_if(true, dst, ((y[0] + F(c1.x)) + (F(c2.x) + F(c3.x))) * rl, ((y[1] + F(c1.y)) + (F(c2.y) + F(c3.y))) * rl,
                             ((y[2] + F(c1.z)) + (F(c2.z) + F(c3.z))) * rl);
            } else {
                stsf4(pa - 1024, y[0], y[1], y[2], 0.f);
                bar_sync<1, 256>();
            }
            TRACES(tr + 1);
            if ((ORD_NO_TAIL >> n) & 1) continue;
            wait_clk(clk32() + (w < 2 ? 0 : 60) + (n < QUIET ? CFG(DLY_AL) : CFG(DLY_A)));
            {
                SPIN_DECL;
                do {
                    v = ld_pkt(cell + near);
                    SPIN_CHECK(n);
                } while (__any_sync(0xffffffffu, v.w != FULL_A));
            }
            TRACES(tr + 2);
            x01 = pack2(F(v.x), F(v.y));
            x2 = pack2(F(v.z), 0.f);
          } else { x01 = nx01; x2 = nx2; }
        } else if (n == -1) {
            mbar_wait(bar_at(B_W + 1), 0);
            const uint32_t ln = opaque(lane);
            const int mi = ln >> 3, mr = ln & 7;
            uint32_t zero = ln >> 5;
            TRACES(76);
#pragma unroll
            for (int i = 0; i < 3; i++) {
                const int d = 16 * (w >> 1) + (mr >> 1) + 8 * (mr & 1) + (i < 2 ? 64 * (mi >> 1) + 4 * i : 128 + 4 * (mi >> 1));
#pragma unroll
                for (int mt = 0; mt < 5; mt++) ldsm4t(wo[i][mt], ST_WO + d * 320 + 160 * (w & 1) + 32 * mt + 16 * (mi & 1), zero);
            }
            fence_async();
            __syncwarp();
            mbar_arrive_if(lane == 0, bar_at(B_WC + 1));
            mbar_wait(bar_at(B_W + 2), 0);
            TRACES(77);
#pragma unroll
            for (int i = 0; i < 5; i++) {
                const uint32_t ga = ST_WG + (mi & 1) * 20480 + (80 * w + 16 * i + mr + 8 * (mi >> 1)) * 32;
                uint32_t r[4];
                ldsm4t(wg[i], ga + (odd ? 16 : 0), zero);
                ldsm4t(r, ga + (odd ? 0 : 16), zero);
#pragma unroll
                for (int kh = 0; kh < 2; kh++) {
                    const uint32_t moved = __shfl_xor_sync(0xffffffffu, odd ? r[2 * kh] : r[2 * kh + 1], 16);
                    wh[i][kh] = (g < 4) == odd ? moved : odd ? r[2 * kh + 1] : r[2 * kh];
                }
            }
            fence_async();
            __syncwarp();
            mbar_arrive_if(lane == 0, bar_at(B_WC + 2));
            TRACES(72);
            x01 = 0x3f803f80u; x2 = 0x3f80u;
        } else {
            const uint32_t xa = ST_X + (n + 5) * 1280, ln = opaque(lane);
            const int col0 = 80 * w + (ln & 2 ? 48 : 0) + (ln >> 2) + (ln & 1 ? 8 : 0);
            float sm = 0.f, sq = 0.f;
#pragma unroll
            for (int i = 0; i < 5; i++) {
                const uint2 c = lds64(xa + i * 256 + ln * 8);
                sm += (bf_lo(c.x) + bf_hi(c.x)) + (bf_lo(c.y) + bf_hi(c.y));
                sq = fmaf(bf_lo(c.x), bf_lo(c.x), fmaf(bf_hi(c.x), bf_hi(c.x), fmaf(bf_lo(c.y), bf_lo(c.y), fmaf(bf_hi(c.y), bf_hi(c.y), sq))));
            }
            x01 = lds16(xa + col0 * 2) | lds16(xa + col0 * 2 + 32) << 16;
            x2 = lds16(xa + col0 * 2 + 64);
#pragma unroll
            for (int o = 16; o; o >>= 1) { sm += shx(sm, o); sq += shx(sq, o); }
            float mean_b, rden;
            ln_finish(sm, sq, mean_b, rden);
            x01 = ln_apply(x01, mean_b, rden);
            x2 = ln_apply(x2, mean_b, rden);
        }
        if (n >= -1) {
            uint32_t b[10];
            spread(b, x01, x2, xw, xr, e2);
            float a[2][4] = {};
#pragma unroll
            for (int i = 0; i < 5; i++) {
                mma16816(a[0], wg[i][0], wg[i][1], wg[i][2], wg[i][3], b[2 * i], b[2 * i + 1]);
                mma16816(a[1], wh[i][0], b[2 * i], wh[i][1], b[2 * i + 1], b[2 * i], b[2 * i + 1]);
            }
            stsf(SM_PG + (w >> 2) * 512 + (g + 8 * t4) * 16 + (w & 3) * 4, e2 ? (e1 ? a[1][2] : a[1][0]) : (e1 ? a[0][2] : a[0][0]));
            const uint2 cs = lds64(SM_CSG + lane * 48);
            const char* dst = opaque(cell + 3 * HALF - near);
            bar_sync<2, 256>();
            const float S = sum8(lds128(SM_PG + lane * 16), lds128(SM_PG + 512 + lane * 16));
            const float sx = shi(S, 25), sq = shi(S, 24), Su = shi(S, lane + (lane < 16 ? 8 : 4));
            if (n < 0) {
                if (w == 0) stsf2(SM_CSG + lane * 48, S, Su);
            } else {
                float mean_b, rden;
                ln_fast(sx, sq, mean_b, rden);
                const float gv = bfr(fmaf(-mean_b, F(cs.x), S) * rden), uv = bfr(fmaf(-mean_b, F(cs.y), Su) * rden);
                const float sg = fast_rcp(1.f + fast_ex2(-LOG2E * gv));
                const uint32_t hb = pack2(bfr(gv * sg) * uv, 0.f);
                const uint32_t b0 = __byte_perm(shi(hb, 2 * t4), shi(hb, 2 * t4 + 1), 0x5410);
                const uint32_t b1 = __byte_perm(shi(hb, e1 ? 18 : 16), shi(hb, e1 ? 19 : 17), 0x5410);
                const bool up = g >= 4;
                const uint32_t l0 = up ? 0 : b0, h0 = up ? b0 : 0;
                const uint32_t l1 = up ? 0 : b1, h1 = up ? b1 : 0;
                float d[3][4] = {};
                mma1688(d[0], wd[0][0], wd[0][1], l0); mma1688(d[1], wd[0][2], wd[0][3], l0); mma1688(d[2], wd[1][0], wd[1][1], l0);
                mma1688(d[0], wd[1][2], wd[1][3], h0); mma1688(d[1], wd[3][0], wd[3][1], h0);
                mma1688(d[2], wd[2][2], wd[2][3], e2 ? 0 : l1);
                mma1688(d[0], wd[2][0], wd[2][1], e2 ? 0 : l1); mma1688(d[1], wd[2][0], wd[2][1], e2 ? l1 : 0);
                mma1688(d[0], wd[2][2], wd[2][3], e2 ? h1 : 0); mma1688(d[1], wd[3][2], wd[3][3], e2 ? 0 : h1);
                red_cell(dst, e1 ? d[0][2] : d[0][0], e1 ? d[1][2] : d[1][0], e1 ? d[2][2] : d[2][0]);
                const uint32_t tsend = clk32();
                TRACES(tr + 3);
                if (last && w != cta >> 4) continue;
                if (!last && w == 0) st_pkt82_if(lane < 24, p.scr + SCR_Q + head_off(h) + 4 * 768 + (24 * s + lane) * 8, 0, 0);
                const float sgr = shi(sg, 27);
                const uint32_t sg2 = pack2(sgr, sgr);
                const uint32_t n01 = opaque(pack2((bf_lo(x01) - mean_b) * rden, (bf_hi(x01) - mean_b) * rden));
                const uint32_t n2 = opaque(pack2((bf_lo(x2) - mean_b) * rden, 0.f));
                if (last) {
                    sts128_if(lane >> 1 == (cta & 15), SM_FIN + (lane & 1) * 16, x01, n01, __byte_perm(x2, n2, 0x5410), sg2);
                    mbar_arrive_if(lane >> 1 == (cta & 15), bar_at(B_FIN));
                    __syncwarp();
                    continue;
                }
                if (n > 0) {
                    const char* src = p.scr + acc_off(k - 1, 1, w) + near + g * 256 + t4 * 16;
                    SPIN_DECL;
                    while (true) {
                        const uint4 u = ld_pkt(src);
                        nx01 = pack2(F(u.x), F(u.y)); nx2 = pack2(F(u.z), 0.f);
                        if (__all_sync(0xffffffffu, u.w == FULL_A)) break;
                        SPIN_CHECK(n);
                    }
                }
                wait_clk(tsend + (n < QUIET ? CFG(DLY_BL) : CFG(DLY_B)));
                uint4 v, z;
                {
                    SPIN_DECL;
                    do {
                        v = ld_pkt(cell + 2 * HALF); z = ld_pkt(cell + 3 * HALF);
                        SPIN_CHECK(n);
                    } while (__any_sync(0xffffffffu, F(v.w) + F(z.w) != NCTA));
                }
                x01 = badd2(x01, badd2(n01, bmul2(pack2(F(v.x) + F(z.x), F(v.y) + F(z.y)), sg2)));
                x2 = badd2(x2, badd2(n2, bmul2(pack2(F(v.z) + F(z.z), 0.f), sg2)));
                TRACES(tr + 4);
            }
        }
        {
            uint32_t b[10];
            spread(b, x01, x2, xw, xr, e2);
            float a[3][4] = {};
            const float f0 = bf_lo(x01), f1 = bf_hi(x01), f2 = e2 ? 0.f : bf_lo(x2);
            float st;
#pragma unroll
            for (int i = 0; i < 5; i++) {
#pragma unroll
                for (int mt = 0; mt < 3; mt++) {
                    mma16816(a[mt], wq[i][mt][0], wq[i][mt][1], wq[i][mt][2], wq[i][mt][3], b[2 * i], b[2 * i + 1]);
                    if (i == 0 && mt == 0) st = fold(fmaf(f0, f0, fmaf(f1, f1, f2 * f2)), (f0 + f1) + f2, g & 1, 4);
                }
                if (i < 4) st += shx(st, i < 2 ? 1 << i : 2 << i);
            }
            const uint32_t pa = SM_PQ + (w >> 2) * 1024 + (g & 1) * 512 + ((e2 ? 16 : 0) + (e1 ? 4 : 0) + (g >> 1)) * 16 + (w & 3) * 4;
            stsf(pa + 128, e2 ? st : e1 ? a[1][2] : a[1][0]);
            stsf(pa, e2 ? (e1 ? a[2][2] : a[2][0]) : (e1 ? a[0][2] : a[0][0]));
            bar_arrive<3, 288>();
            if (n >= 0 && w == cta >> 4) {
                red_cell2_if(lane >> 1 == (cta & 15), cell + 128, f0, f1, f2);
                __syncwarp();
            }
        }
    }
}

template <int ID> __device__ __forceinline__ void role_exit() { asm volatile("exit; // %0" ::"n"(ID)); }
constexpr int NTHREADS = 512;
#define STR2(x) #x
#define STR(x) STR2(x)
__global__ void __launch_bounds__(NTHREADS, 1)
decode_kernel(const __grid_constant__ CUtensorMap tmK, const __grid_constant__ CUtensorMap tmV,
              const __grid_constant__ WeightMaps tmW, const Params p) {
    extern __shared__ __align__(1024) unsigned char smem[];
    const uint32_t t0 = now_ns();
    const int lane = threadIdx.x & 31;
    const int warp = __shfl_sync(0xffffffffu, threadIdx.x >> 5, 0);
    if (warp < 8) {
        asm volatile("setmaxnreg.inc.sync.aligned.u32 " STR(CFG_REG_CHAIN) ";");
        bar_arrive<5, 480 + 0>();
        const uint32_t vote = probe_near(p, warp, lane);
        bar_sync<2, 256 + 32>();
        asm volatile("st.shared.u8 [%0], %1;" ::"r"(SM_NEAR + warp), "r"(vote) : "memory");
        mbar_arrive_if(lane == 0, bar_at(B_EP));
        chain_role(p, warp, __shfl_sync(0xffffffffu, lane, lane), t0);
        role_exit<3>();
    } else if (warp < 12) {
        asm volatile("setmaxnreg.dec.sync.aligned.u32 " STR(CFG_REG_ATT) ";");
        if (elect_one()) {
#pragma unroll 1
            for (int i = warp - 8; i < NBAR; i += 4)
                if (i < B_W || i >= B_WC) mbar_init(bar_at(i), i == B_FIN ? 2 : i == B_EP ? 9 : i == B_QR ? 32 : i == B_PS || i == B_RP ? 4 : i >= B_F3 ? 1 : i >= B_WC ? 8 : i < B_RR || i > B_RV ? 1 : i < B_RK ? 2 : 4);
            asm volatile("fence.mbarrier_init.release.cluster;" ::: "memory");
            fence_async();
        }
        bar_sync<5, 480>();
        attention_role(p, warp - 8, lane);
        role_exit<2>();
    } else {
        asm volatile("setmaxnreg.dec.sync.aligned.u32 " STR(CFG_REG_HELP) ";");
        if (warp == 12) {
            TRACE(0);
            load_role(p, &tmK, &tmV, t0);
            role_exit<0>();
        } else {
            if (warp == 14) {
                if (smem_u32(smem) != SB) __trap();
                if (elect_one()) {
                    asm volatile("prefetch.tensormap [%0];" ::"l"(&tmW.q) : "memory");
                    mbar_init(bar_at(B_W), 1); mbar_init(bar_at(B_W + 1), 1); mbar_init(bar_at(B_W + 2), 1);
                    asm volatile("fence.mbarrier_init.release.cluster;" ::: "memory");
                    fence_async();
                    mbar_expect_tx(bar_at(B_W), 61440 + 15360 + 6400); mbar_expect_tx(bar_at(B_W + 1), 61440); mbar_expect_tx(bar_at(B_W + 2), 40960);
                    bulk_load(ST_X, p.x, 5120, bar_at(B_W));
                    bulk_load(ST_X + 5120, p.wr, 1280, bar_at(B_W));
                }
                reload_role(p, &tmK, &tmV, &tmW, t0);
            } else {
                unsigned ticket = 0;
                if (warp == 15 && lane == 0) asm volatile("atom.relaxed.gpu.global.add.u32 %0, [%1], 1;" : "=r"(ticket) : "l"(&g_epoch) : "memory");
                if (warp == 13 && elect_one()) {
                    asm volatile("prefetch.tensormap [%0];" ::"l"(&tmW.g) : "memory");
                    asm volatile("prefetch.tensormap [%0];" ::"l"(&tmW.u) : "memory");
                    asm volatile("prefetch.tensormap [%0];" ::"l"(&tmW.o) : "memory");
                    asm volatile("prefetch.tensormap [%0];" ::"l"(&tmK) : "memory");
                    asm volatile("prefetch.tensormap [%0];" ::"l"(&tmV) : "memory");
                }
                bar_sync<5, 480>();
                if (warp == 13) { sts32(SM_PROG, 0); bar_arrive<6, 64>(); q_role(p, &tmV, lane); }
                else { bar_arrive<2, 256 + 32>(); zero_role(p, lane, ticket, t0); }
            }
            role_exit<1>();
        }
    }
}

typedef CUresult (*EncodeFn)(CUtensorMap*, CUtensorMapDataType, cuuint32_t, void*, const cuuint64_t*, const cuuint64_t*,
                             const cuuint32_t*, const cuuint32_t*, CUtensorMapInterleave, CUtensorMapSwizzle,
                             CUtensorMapL2promotion, CUtensorMapFloatOOBfill);

bool make_map(EncodeFn fn, CUtensorMap* m, const void* ptr, uint64_t cols, uint64_t rows, uint32_t bc, uint32_t br) {
    cuuint64_t dims[2] = {cols, rows};
    cuuint64_t strides[1] = {cols * 2};
    cuuint32_t box[2] = {bc, br};
    cuuint32_t es[2] = {1, 1};
    return fn(m, CU_TENSOR_MAP_DATA_TYPE_BFLOAT16, 2, const_cast<void*>(ptr), dims, strides, box, es, CU_TENSOR_MAP_INTERLEAVE_NONE,
              CU_TENSOR_MAP_SWIZZLE_NONE, CU_TENSOR_MAP_L2_PROMOTION_L2_128B, CU_TENSOR_MAP_FLOAT_OOB_FILL_NONE) == CUDA_SUCCESS;
}

bool make_kv_map(EncodeFn fn, CUtensorMap* m, const void* ptr) {
    cuuint64_t dims[4] = {64, 8, 3, (cuuint64_t)NB * NHEAD * SK / 8};
    cuuint64_t strides[3] = {DH * 2, 128, 8 * DH * 2};
    cuuint32_t box[4] = {64, 8, 3, 4};
    cuuint32_t es[4] = {1, 1, 1, 1};
    return fn(m, CU_TENSOR_MAP_DATA_TYPE_BFLOAT16, 4, const_cast<void*>(ptr), dims, strides, box, es, CU_TENSOR_MAP_INTERLEAVE_NONE,
              CU_TENSOR_MAP_SWIZZLE_128B, CU_TENSOR_MAP_L2_PROMOTION_L2_128B, CU_TENSOR_MAP_FLOAT_OOB_FILL_NONE) == CUDA_SUCCESS;
}

}

extern "C" void kernel_launch(void* const* d_in, const int* in_sizes, int n_in, void* d_out, int out_size) {
    (void)in_sizes; (void)n_in; (void)out_size;
    static EncodeFn fn = nullptr;
    static const char* scr = nullptr;
    if (!fn) {
        void* f = nullptr;
        cudaDriverEntryPointQueryResult qr;
        if (cudaGetDriverEntryPoint("cuTensorMapEncodeTiled", &f, cudaEnableDefault, &qr) != cudaSuccess || !f) return;
        void* sp = nullptr;
        if (cudaGetSymbolAddress(&sp, g_scratch) != cudaSuccess) return;
        scr = (const char*)(((uintptr_t)sp + (2 << 20) - 1) & ~(uintptr_t)((2 << 20) - 1));
        fn = (EncodeFn)f;
        cudaFuncSetAttribute(decode_kernel, cudaFuncAttributeMaxDynamicSharedMemorySize, SMEM_BYTES);
    }
    CUtensorMap tmK, tmV;
    WeightMaps tmW;
    if (!make_kv_map(fn, &tmK, d_in[1]) || !make_kv_map(fn, &tmV, d_in[2])) return;
    if (!make_map(fn, &tmW.q, d_in[3], NHEAD * DH, DM, 48, 128) || !make_map(fn, &tmW.o, d_in[4], DM, NHEAD * DH, 160, 32)) return;
    if (!make_map(fn, &tmW.g, d_in[7], FF, DM, 16, 128) || !make_map(fn, &tmW.u, d_in[8], FF, DM, 16, 128)) return;
    Params p;
    p.x = (const unsigned short*)d_in[0];
    p.kc = (const char*)d_in[1];
    p.vc = (const char*)d_in[2];
    p.wq = (const char*)d_in[3];
    p.wo = (const char*)d_in[4];
    p.wr = (const unsigned short*)d_in[6];
    p.wg = (const char*)d_in[7];
    p.wu = (const char*)d_in[8];
    p.wd = (const char*)d_in[9];
    p.out = (unsigned short*)d_out;
    p.scr = scr;
    decode_kernel<<<NCTA, NTHREADS, SMEM_BYTES>>>(tmK, tmV, tmW, p);
}
```

```cpp
#include <cuda_runtime.h>
#include <cuda_bf16.h>
#include <cuda.h>
#include <stdint.h>

namespace {

constexpr int NB = 4, DM = 640, NHEAD = 32, DH = 192, SK = 4096, WIN = 1024, FF = 1536;
constexpr int NCTA = 128;
constexpr int TILE = 12288, PAIR = 2 * TILE;

#define CFG_LIST(X) \
    X(TICK0, 480)        \
    X(TICK, 500)        \
    X(TICKA, 0) \
    X(TICKB, 0) \
    X(TICKC, 0) \
    X(TICKD, 0) \
    X(LEAD, 100)        \
    X(STAG, 488)        \
    X(WLAG, 300)        \
    X(GSTEP, 700)        \
    X(WIN, 4)        \
    X(PMAX, 4)        \
    X(PGRACE, 50)        \
    X(LMAX0, 150)        \
    X(LMAX, 150) \
    X(GAIN, 10)        \
    X(VSTEP, 250)        \
    X(RLAG, 0)        \
    X(RSTEP, 640) \
    X(RSTEP3, 390) \
    X(ZTILE, 10)        \
    X(START, 1)        \
    X(DLY_A, 400)        \
    X(DLY_AL, 100) \
    X(DLY_B, 600) \
    X(DLY_BL, 900) \
    X(DLY_F, 250) \
    X(DLY_PL, 100)        \
    X(DLY_PB, 300) \
    X(DLY_QL, 200) \
    X(FLIP, 0) \

#define X(n, v) constexpr int CFG_##n = v;
CFG_LIST(X)
#undef X
#define CFG(n) CFG_##n
constexpr int QUIET = 8;
#define CFG_REG_CHAIN 216
#define CFG_REG_ATT 48
#define CFG_REG_HELP 32
constexpr int KB_KV0 = 165;
__device__ __forceinline__ int kb_ns(int kb) { return kb * CFG(TICK0) / 12; }
__device__ __forceinline__ int tick_ns(int j) {
    return j <= 16 ? CFG(TICK0) : CFG(TICK) + (j & 8 ? (j & 4 ? CFG(TICKD) : CFG(TICKC)) : (j & 4 ? CFG(TICKB) : CFG(TICKA)));
}
__device__ __forceinline__ int batch_ns(int k) {
    return kb_ns(KB_KV0) + (k ? 16 * CFG(TICK0) + (k - 1) * 4 * (4 * CFG(TICK) + CFG(TICKA) + CFG(TICKB) + CFG(TICKC) + CFG(TICKD)) : 0);
}

__device__ __forceinline__ uint32_t slots(int k) { return k & 2 ? (k & 1 ? 0x21304768u : 0x76835214u) : (k & 1 ? 0x21480765u : 0x76543210u); }
__device__ __forceinline__ int pass_nibble(int k, int u) { return k > 0 ? 4 + (u & 1) : u; }
__device__ __forceinline__ uint32_t slot_at(uint32_t tab, int u) { return (tab >> (4 * u)) & 15; }

constexpr int NROUND = 11;
constexpr uint32_t ORD_BATCH = 0x3b9910, ORD_LAST = 0x6da, ORD_NO_HEAD = 0x248, ORD_NO_TAIL = 0x092;

constexpr uint32_t SB = 1024;
constexpr uint32_t SM_BAR = SB + 9 * PAIR;
constexpr int B_F1 = 0;
constexpr int B_RR = 24;
constexpr int B_RK = 32;
constexpr int B_RV = 36;
constexpr int B_Z = 37;
constexpr int B_EP = 38;
constexpr int B_W = 39;
constexpr int B_WC = 42;
constexpr int B_FIN = 45;
constexpr int B_F3 = 46;
constexpr int B_PS = 48;
constexpr int B_RP = 49;
constexpr int B_FL = 50;
constexpr int B_QR = 51;
constexpr int NBAR = 52;
__host__ __device__ constexpr uint32_t bar_at(int i) { return SM_BAR + 8 * i; }
constexpr uint32_t SM_EPOCH = SM_BAR + 416;
constexpr uint32_t SM_NEAR = SM_EPOCH + 8;
constexpr uint32_t SM_MAX = SM_EPOCH + 16;
constexpr uint32_t SM_SUM = SM_MAX + 16;
constexpr uint32_t SM_FIN = SM_SUM + 32;
constexpr uint32_t SM_Q = SM_FIN + 32;
constexpr uint32_t PSTR = 144;
constexpr uint32_t SM_P = SM_Q + 5 * 384;
constexpr uint32_t SM_X = SM_P + 8 * PSTR;
constexpr uint32_t SM_CSG = SM_X + 40;
constexpr uint32_t SM_ONES = SM_X + 8 * 384;
constexpr uint32_t SM_PG = SM_ONES + 48;
constexpr uint32_t SM_PO = SM_PG + 1024;
constexpr uint32_t SM_PQ = SM_PO;
constexpr int SMEM_BYTES = SM_PO + 3072 - SB;
static_assert(SMEM_BYTES <= 232448 && SM_Q % 16 == 0 && SM_P % 16 == 0 && SM_X % 16 == 0 && SM_PO % 16 == 0, "smem");
constexpr uint32_t ST_WQ = SB, ST_WD = SB + 3 * PAIR, ST_WO = SB + 4 * PAIR, ST_WG = SB + 7 * PAIR, ST_X = ST_WG + 40960;

__device__ unsigned g_epoch;
__device__ unsigned g_init;
__device__ unsigned char g_scratch[4 << 20];
constexpr uint32_t HALF = 4096, SCR_O = 1 << 16, SCR_Q = 1 << 17, SCR_PROBE = 1 << 19;
__device__ __forceinline__ uint32_t acc_off(int k, int layer, int w) { return (k & 1) << 18 | (k >> 1) << 20 | (w >> 1) << 14 | (w & 1) << 11 | layer << 7; }
__device__ __forceinline__ uint32_t head_off(int h) { return (h & 3) << 14 | (h & 4) << 16 | (h & 8) << 17 | (h & 16) << 9; }
__device__ __forceinline__ uint32_t head_near(int h, uint32_t near) { return near ^ HALF ^ (h & 16) << 8; }
constexpr uint32_t FULL_A = 0x42040000u;

struct Params {
    const char* wq;
    const unsigned short* x;
    const char* kc;
    const char* vc;
    const char* wo;
    const unsigned short* wr;
    const char* wg;
    const char* wu;
    const char* wd;
    unsigned short* out;
    const char* scr;
};

__device__ __forceinline__ uint32_t smem_u32(const void* p) { return (uint32_t)__cvta_generic_to_shared(p); }
__device__ __forceinline__ void mbar_init(uint32_t a, uint32_t c) { asm volatile("mbarrier.init.shared::cta.b64 [%0], %1;" ::"r"(a), "r"(c) : "memory"); }
__device__ __forceinline__ void mbar_expect_tx(uint32_t a, uint32_t b) {
    asm volatile("mbarrier.arrive.expect_tx.shared::cta.b64 _, [%0], %1;" ::"r"(a), "r"(b) : "memory");
}
__device__ __forceinline__ void mbar_arrive(uint32_t a) { asm volatile("mbarrier.arrive.shared::cta.b64 _, [%0];" ::"r"(a) : "memory"); }
constexpr uint32_t SPIN_LIMIT = 1u << 22;
#define SPIN_DECL uint32_t spins = 0
#define SPIN_CHECK(info) { if (++spins > SPIN_LIMIT) __trap(); }
__device__ __forceinline__ void mbar_wait(uint32_t a, uint32_t parity) {
    uint32_t ok;
    SPIN_DECL;
    while (true) {
        asm volatile("{\n.reg .pred p;\nmbarrier.try_wait.parity.shared::cta.b64 p, [%1], %2;\nselp.u32 %0, 1, 0, p;\n}"
                     : "=r"(ok) : "r"(a), "r"(parity) : "memory");
        if (ok) break;
        SPIN_CHECK((a - SM_BAR) / 8 * 10 + parity);
    }
}
__device__ __forceinline__ bool mbar_test(uint32_t a, uint32_t parity) {
    uint32_t ok;
    asm volatile("{\n.reg .pred p;\nmbarrier.test_wait.parity.shared::cta.b64 p, [%1], %2;\nselp.u32 %0, 1, 0, p;\n}"
                 : "=r"(ok) : "r"(a), "r"(parity) : "memory");
    return __all_sync(0xffffffffu, ok);
}
__device__ __forceinline__ uint32_t now_ns() { uint32_t t; asm volatile("mov.u32 %0, %%globaltimer_lo;" : "=r"(t) :: "memory"); return t; }
__device__ __forceinline__ uint32_t clk32() { uint32_t c; asm volatile("mov.u32 %0, %%clock;" : "=r"(c) :: "memory"); return c; }
__device__ __forceinline__ void wait_ns(uint32_t t) { while ((int)(now_ns() - t) < 0) {} }
__device__ __forceinline__ void wait_clk(uint32_t t) { while ((int)(clk32() - t) < 0) {} }
__device__ __forceinline__ bool elect_one() {
    uint32_t e;
    asm volatile("{\n.reg .pred p;\nelect.sync _|p, 0xffffffff;\nselp.u32 %0, 1, 0, p;\n}" : "=r"(e));
    return e;
}
constexpr uint64_t POL_FIRST = 0x12F0000000000000ull, POL_NORMAL = 0x1000000000000000ull;
__device__ __forceinline__ void tma_tile(uint32_t dst, const CUtensorMap* tm, int group, uint32_t bar, uint64_t pol) {
    asm volatile("cp.async.bulk.tensor.4d.shared::cluster.global.mbarrier::complete_tx::bytes.L2::cache_hint"
                 " [%0], [%1, {%3, %3, %3, %4}], [%2], %5;"
                 ::"r"(dst), "l"(tm), "r"(bar), "r"(0), "r"(group), "l"(pol) : "memory");
}
__device__ __forceinline__ void tma2d(uint32_t dst, const CUtensorMap* tm, int x, int y, uint32_t bar) {
    asm volatile("cp.async.bulk.tensor.2d.shared::cluster.global.mbarrier::complete_tx::bytes [%0], [%1, {%3, %4}], [%2];"
                 ::"r"(dst), "l"(tm), "r"(bar), "r"(x), "r"(y) : "memory");
}
__device__ __forceinline__ void bulk_load(uint32_t dst, const void* src, uint32_t bytes, uint32_t bar) {
    asm volatile("cp.async.bulk.shared::cluster.global.mbarrier::complete_tx::bytes [%0], [%1], %2, [%3];"
                 ::"r"(dst), "l"(src), "r"(bytes), "r"(bar) : "memory");
}
__device__ __forceinline__ void l2_prefetch(const void* p, uint32_t bytes) {
    asm volatile("cp.async.bulk.prefetch.L2.global [%0], %1;" ::"l"(p), "r"(bytes) : "memory");
}
__device__ __forceinline__ void mma16816(float (&c)[4], uint32_t a0, uint32_t a1, uint32_t a2, uint32_t a3, uint32_t b0, uint32_t b1) {
    asm volatile("mma.sync.aligned.m16n8k16.row.col.f32.bf16.bf16.f32 {%0,%1,%2,%3}, {%4,%5,%6,%7}, {%8,%9}, {%0,%1,%2,%3};"
                 : "+f"(c[0]), "+f"(c[1]), "+f"(c[2]), "+f"(c[3]) : "r"(a0), "r"(a1), "r"(a2), "r"(a3), "r"(b0), "r"(b1));
}
__device__ __forceinline__ void mma1688(float (&c)[4], uint32_t a0, uint32_t a1, uint32_t b0) {
    asm volatile("mma.sync.aligned.m16n8k8.row.col.f32.bf16.bf16.f32 {%0,%1,%2,%3}, {%4,%5}, {%6}, {%0,%1,%2,%3};"
                 : "+f"(c[0]), "+f"(c[1]), "+f"(c[2]), "+f"(c[3]) : "r"(a0), "r"(a1), "r"(b0));
}
__device__ __forceinline__ void ldsm4t(uint32_t (&r)[4], uint32_t a, uint32_t& zero) {
    asm volatile("ldmatrix.sync.aligned.m8n8.x4.trans.shared.b16 {%0,%1,%2,%3}, [%4];"
                 : "=r"(r[0]), "=r"(r[1]), "=r"(r[2]), "=r"(r[3]) : "r"(a + zero) : "memory");
    zero &= r[3];
}
__device__ __forceinline__ uint4 ld_pkt(const void* p) {
    uint4 v;
    asm volatile("{\n.reg .b128 t;\nld.relaxed.gpu.global.b128 t, [%4];\nmov.b128 {%0,%1,%2,%3}, t;\n}"
                 : "=r"(v.x), "=r"(v.y), "=r"(v.z), "=r"(v.w) : "l"(p) : "memory");
    return v;
}
__device__ __forceinline__ void st_pkt(const void* p, uint32_t a, uint32_t b, uint32_t c, uint32_t d) {
    asm volatile("{\n.reg .b128 t;\nmov.b128 t, {%1,%2,%3,%4};\nst.relaxed.gpu.global.b128 [%0], t;\n}"
                 ::"l"(p), "r"(a), "r"(b), "r"(c), "r"(d) : "memory");
}
__device__ __forceinline__ uint2 ld_pkt8(const void* p) {
    uint2 v;
    asm volatile("{\n.reg .b64 t;\nld.relaxed.gpu.global.b64 t, [%2];\nmov.b64 {%0,%1}, t;\n}" : "=r"(v.x), "=r"(v.y) : "l"(p) : "memory");
    return v;
}
__device__ __forceinline__ void red_cell(const char* p, float a, float b, float c) {
    asm volatile("red.relaxed.gpu.global.add.v4.f32 [%0], {%1,%2,%3,%4};" ::"l"(p), "f"(a), "f"(b), "f"(c), "f"(1.0f) : "memory");
}
#define PRED(n) "{\n.reg .pred p;\nsetp.ne.u32 p, %" #n ", 0;\n"
__device__ __forceinline__ void red_cell2_if(bool on, const char* p, float a, float b, float c) {
    asm volatile(PRED(5) "@p red.relaxed.gpu.global.add.v4.f32 [%0], {%1,%2,%3,%4};\n@p red.relaxed.gpu.global.add.v4.f32 [%0+4096], {%1,%2,%3,%4};\n}"
                 ::"l"(p), "f"(a), "f"(b), "f"(c), "f"(1.0f), "r"((uint32_t)on) : "memory");
}
__device__ __forceinline__ void st_pkt82_if(bool on, const void* p, uint32_t a, uint32_t b) {
    asm volatile(PRED(3) ".reg .b64 t;\nmov.b64 t, {%1,%2};\n@p st.relaxed.gpu.global.b64 [%0], t;\n@p st.relaxed.gpu.global.b64 [%0+4096], t;\n}"
                 ::"l"(p), "r"(a), "r"(b), "r"((uint32_t)on) : "memory");
}
__device__ __forceinline__ void st_pkt2_if(bool on, const void* p, uint32_t a, uint32_t b, uint32_t c, uint32_t d) {
    asm volatile(PRED(5) ".reg .b128 t;\nmov.b128 t, {%1,%2,%3,%4};\n@p st.relaxed.gpu.global.b128 [%0], t;\n@p st.relaxed.gpu.global.b128 [%0+4096], t;\n}"
                 ::"l"(p), "r"(a), "r"(b), "r"(c), "r"(d), "r"((uint32_t)on) : "memory");
}
__device__ __forceinline__ void mbar_arrive_if(bool on, uint32_t a) {
    asm volatile(PRED(1) "@p mbarrier.arrive.shared::cta.b64 _, [%0];\n}" ::"r"(a), "r"((uint32_t)on) : "memory");
}
__device__ __forceinline__ void sts16_if(bool on, uint32_t a, uint32_t v) {
    asm volatile(PRED(2) "@p st.shared.u16 [%0], %1;\n}" ::"r"(a), "h"((unsigned short)v), "r"((uint32_t)on) : "memory");
}
__device__ __forceinline__ void sts32_if(bool on, uint32_t a, uint32_t v) {
    asm volatile(PRED(2) "@p st.shared.u32 [%0], %1;\n}" ::"r"(a), "r"(v), "r"((uint32_t)on) : "memory");
}
__device__ __forceinline__ void sts128_if(bool on, uint32_t a, uint32_t x, uint32_t y, uint32_t z, uint32_t w) {
    asm volatile(PRED(5) "@p st.shared.v4.u32 [%0], {%1,%2,%3,%4};\n}" ::"r"(a), "r"(x), "r"(y), "r"(z), "r"(w), "r"((uint32_t)on) : "memory");
}
__device__ __forceinline__ float fast_rcp(float x) { float r; asm("rcp.approx.ftz.f32 %0, %1;" : "=f"(r) : "f"(x)); return r; }
__device__ __forceinline__ float fast_sqrt(float x) { float r; asm("sqrt.approx.ftz.f32 %0, %1;" : "=f"(r) : "f"(x)); return r; }
__device__ __forceinline__ float fast_ex2(float x) { float r; asm("ex2.approx.ftz.f32 %0, %1;" : "=f"(r) : "f"(x)); return r; }
__device__ __forceinline__ uint32_t pack2(float lo, float hi) {
    uint32_t r;
    asm("cvt.rn.bf16x2.f32 %0, %1, %2;" : "=r"(r) : "f"(hi), "f"(lo));
    return r;
}
__device__ __forceinline__ float bfr(float x) { return __uint_as_float(pack2(0.f, x)); }
__device__ __forceinline__ uint32_t badd2(uint32_t a, uint32_t b) { uint32_t r; asm("add.rn.bf16x2 %0, %1, %2;" : "=r"(r) : "r"(a), "r"(b)); return r; }
__device__ __forceinline__ uint32_t bsub2(uint32_t a, uint32_t b) { uint32_t r; asm("sub.rn.bf16x2 %0, %1, %2;" : "=r"(r) : "r"(a), "r"(b)); return r; }
__device__ __forceinline__ uint32_t bmul2(uint32_t a, uint32_t b) { uint32_t r; asm("mul.rn.bf16x2 %0, %1, %2;" : "=r"(r) : "r"(a), "r"(b)); return r; }
__device__ __forceinline__ float bf_lo(uint32_t w) { return __uint_as_float(w << 16); }
__device__ __forceinline__ float bf_hi(uint32_t w) { return __uint_as_float(w & 0xffff0000u); }
__device__ __forceinline__ float F(uint32_t t) { return __uint_as_float(t); }
__device__ __forceinline__ uint32_t lds16(uint32_t a) { unsigned short h; asm volatile("ld.shared.u16 %0, [%1];" : "=h"(h) : "r"(a) : "memory"); return h; }
__device__ __forceinline__ uint32_t lds32(uint32_t a) { uint32_t v; asm volatile("ld.shared.u32 %0, [%1];" : "=r"(v) : "r"(a) : "memory"); return v; }
__device__ __forceinline__ uint2 lds64(uint32_t a) {
    uint2 v; asm volatile("ld.shared.v2.u32 {%0,%1}, [%2];" : "=r"(v.x), "=r"(v.y) : "r"(a) : "memory"); return v;
}
__device__ __forceinline__ uint4 lds128(uint32_t a) {
    uint4 v; asm volatile("ld.shared.v4.u32 {%0,%1,%2,%3}, [%4];" : "=r"(v.x), "=r"(v.y), "=r"(v.z), "=r"(v.w) : "r"(a) : "memory"); return v;
}
__device__ __forceinline__ float sum8(const uint4& u, const uint4& v) {
    return ((F(u.x) + F(u.y)) + (F(u.z) + F(u.w))) + ((F(v.x) + F(v.y)) + (F(v.z) + F(v.w)));
}
__device__ __forceinline__ void sts16(uint32_t a, uint32_t v) { asm volatile("st.shared.u16 [%0], %1;" ::"r"(a), "h"((unsigned short)v) : "memory"); }
__device__ __forceinline__ void sts32(uint32_t a, uint32_t v) { asm volatile("st.shared.u32 [%0], %1;" ::"r"(a), "r"(v) : "memory"); }
__device__ __forceinline__ void stsf(uint32_t a, float v) { asm volatile("st.shared.f32 [%0], %1;" ::"r"(a), "f"(v) : "memory"); }
__device__ __forceinline__ void stsf2(uint32_t a, float x, float y) { asm volatile("st.shared.v2.f32 [%0], {%1,%2};" ::"r"(a), "f"(x), "f"(y) : "memory"); }
__device__ __forceinline__ void stsf4(uint32_t a, float x, float y, float z, float w) {
    asm volatile("st.shared.v4.f32 [%0], {%1,%2,%3,%4};" ::"r"(a), "f"(x), "f"(y), "f"(z), "f"(w) : "memory");
}
template <int ID, int N> __device__ __forceinline__ void bar_sync() { asm volatile("bar.sync %0, %1;" ::"n"(ID), "n"(N) : "memory"); }
template <int ID, int N> __device__ __forceinline__ void bar_arrive() { asm volatile("bar.arrive %0, %1;" ::"n"(ID), "n"(N) : "memory"); }
__device__ __forceinline__ void fence_async() { asm volatile("fence.proxy.async.shared::cta;" ::: "memory"); }
__device__ __forceinline__ float shx(float v, int m) { return __shfl_xor_sync(0xffffffffu, v, m); }
__device__ __forceinline__ float shi(float v, int l) { return __shfl_sync(0xffffffffu, v, l); }
__device__ __forceinline__ uint32_t shi(uint32_t v, int l) { return __shfl_sync(0xffffffffu, v, l); }
__device__ __forceinline__ uint32_t opaque(uint32_t x) { asm volatile("mov.u32 %0, %0;" : "+r"(x)); return x; }
__device__ __forceinline__ const char* opaque(const char* x) { asm volatile("mov.u64 %0, %0;" : "+l"(x)); return x; }
constexpr float LOG2E = 1.4426950408889634f;

#define TRACE(idx) do {} while (0)
#define TRACES(slot) do {} while (0)

__device__ __forceinline__ uint32_t probe_near(const Params& p, int w, int lane) {
    const int cta = blockIdx.x;
    const char* pr = p.scr + SCR_PROBE + (cta & 31) * 128 + (cta >> 5) * 16384 + ((w & 1) << 6 | (w & 2) << 17 | (w & 4) << 18);
    st_pkt2_if(lane < 2, pr + lane * 16, 0, 0, 0, 0);
    uint32_t best0 = ~0u, best1 = ~0u;
#pragma unroll 1
    for (int i = w & 1; i < 6 + (w & 1); i++) {
        uint32_t c = clk32(), v = 0;
        if (lane == 0) asm volatile("atom.relaxed.gpu.global.add.u32 %0, [%1], 1;" : "=r"(v) : "l"(pr + (i & 1) * HALF) : "memory");
        c += __shfl_sync(0xffffffffu, v, 0) >> 16;
        c = clk32() - c;
        if (i & 1) best1 = min(best1, c); else best0 = min(best0, c);
    }
    return best0 < best1;
}
__device__ __forceinline__ uint32_t near_half() {
    const uint2 v = lds64(SM_NEAR);
    return (__popc(v.x) + __popc(v.y) > 4) != (CFG(FLIP) != 0) ? HALF : 0;
}

__device__ __forceinline__ int kv_group(int k, int t) {
    const int cta = blockIdx.x;
    return ((k * NHEAD + (cta >> 2)) * SK + (SK - WIN) + (cta & 3) * 256 + t * 32) / 8;
}
__device__ __forceinline__ uint32_t phase_ns() { return (((blockIdx.x >> 2) * 13) & 31) * CFG(STAG) / 32; }

__device__ __forceinline__ void ln_fast(float s, float q, float& mean, float& rstd) {
    mean = s * (1.f / DM);
    asm("rsqrt.approx.ftz.f32 %0, %1;" : "=f"(rstd) : "f"(fmaxf(fmaf(-mean, mean, fmaf(q, 1.f / DM, 1e-5f)), 1e-5f)));
}
__device__ __forceinline__ void q_role(const Params& p, int lane) {
    const int cta = blockIdx.x;
    mbar_wait(bar_at(B_EP), 0);
    const uint32_t tag0 = lds32(SM_EPOCH) * NB;
    const char* const qbox = p.scr + SCR_Q + head_off(cta >> 2) + lane * 8;
    const uint32_t near = head_near(cta >> 2, near_half());
    float cs0 = 0.f, cs1 = 0.f;
#pragma unroll 1
    for (int r = 0; r <= 2 * NB; r++) {
        const int slot = min(r, NB), k = r - NB;
        const uint32_t tag = tag0 + (r < NB ? r : k - 1);
        const char* const dst = qbox + slot * 768 + (cta & 3) * 192;
        const char* const src = qbox + slot * 768 + near;
        bar_sync<3, 288>();
        const uint32_t ra = SM_PQ + lane * 16;
        float S0 = sum8(lds128(ra), lds128(ra + 1024)), S1 = sum8(lds128(ra + 512), lds128(ra + 1536));
        if (k > 0) {
            float mean, rstd;
            ln_fast(shi(S1, 24), shi(S0, 24), mean, rstd);
            S0 = fmaf(-mean, cs0, S0) * rstd;
            S1 = fmaf(-mean, cs1, S1) * rstd;
        } else {
            bar_arrive<7, 288>();
            if (k == 0) { cs0 = S0; cs1 = S1; continue; }
        }
        st_pkt82_if(lane < 24, dst, pack2(S0, S1), tag);
        TRACES(k > 0 ? (k - 1) * 12 + 5 : 95);
        if (r < NB - 1) continue;
        if (k < NB) wait_clk(clk32() + CFG(DLY_QL));
#pragma unroll 1
        for (int back = k < 0 ? NB - 1 : 0; back >= 0; back--) {
            uint2 a, b, c;
            SPIN_DECL;
            do {
                a = ld_pkt8(src - back * 768); b = ld_pkt8(src - back * 768 + 256); c = ld_pkt8(src - back * 768 + 512);
                SPIN_CHECK(slot);
            } while (__any_sync(0xffffffffu, a.y != tag - back || b.y != tag - back || c.y != tag - back));
            const uint32_t qd = SM_Q + (slot - back) * 384 + lane * 4;
            sts32(qd, a.x); sts32(qd + 128, b.x); sts32(qd + 256, c.x);
        }
        fence_async();
        mbar_arrive(bar_at(B_QR));
    }
}

struct WeightMaps { CUtensorMap q, o, g, u; };
__device__ __forceinline__ void load_role(const Params& p, const CUtensorMap* tmK, const CUtensorMap* tmV, uint32_t t0) {
    const int cta = blockIdx.x;
    t0 += phase_ns();
#pragma unroll 1
    for (int i = 1; i < 5; i++) {
        wait_ns(t0 + i * CFG(TICK0));
        if (elect_one()) l2_prefetch(p.wq + (size_t)(128 * i + cta) * 12288, 12288);
    }
    bar_sync<6, 64>();
    wait_ns(t0 + kb_ns(60));
    if (elect_one()) bulk_load(ST_WD, p.wd + cta * 15360, 15360, bar_at(B_W));
#pragma unroll 1
    for (int i = 0; i < 5; i++) {
        wait_ns(t0 + kb_ns(75) + i * kb_ns(6));
        if (elect_one()) { l2_prefetch(p.wg + (128 * i + cta) * 3072, 3072); l2_prefetch(p.wu + (128 * i + cta) * 3072, 3072); }
    }
#pragma unroll 1
    for (int i = 0; i < 6; i++) {
        wait_ns(t0 + kb_ns(105) + min(i, 4) * kb_ns(10));
        if (elect_one()) l2_prefetch(p.wo + (size_t)((cta >> 2) * DH + 32 * i + 8 * (cta & 3)) * 1280, 10240);
    }
    t0 += batch_ns(0);
    int jp = 0, shift = 0;
    uint32_t earliest = t0;
    auto requested = [&](uint32_t now) {
        shift = max(max(shift - CFG(GAIN), 0), (int)(now - t0) - (jp < 12 ? CFG(LMAX0) : CFG(LMAX)));
        TRACE(128 + jp);
        t0 += tick_ns(++jp);
    };
#pragma unroll 1
    for (int j = 0; j < 16 * NB; j++) {
        const int k = j >> 4, t = j & 15, u = t >> 1, jw = max(j - CFG(WIN), 0);
        const int sb = k == 0 ? B_WC + (t + 4) / 12 + (t >= 14) : t >= 12 ? B_RK + u - 5 : t >= 4 ? B_RR + t - 4 : t >= 2 ? B_RP : k > 1 ? B_RK + 3 : B_RR + t;
        const uint32_t sp = k == 0 || j < 18 ? 0 : (t >= 12 || (t & 14) == 2 ? k - 1 : k) & 1;
        const uint32_t dst = SB + slot_at(slots(k), t < 8 ? pass_nibble(k, u) : u) * PAIR + (t & 1) * TILE;
        bool slot = false, window = j < CFG(WIN);
        uint32_t now;
        SPIN_DECL;
        while (true) {
            if (!slot) slot = mbar_test(bar_at(sb), sp);
            if (!window) window = mbar_test(bar_at(B_F1 + (jw & 15)), (jw >> 4) & 1);
            now = now_ns();
            const bool due = (int)(now - t0) >= shift;
            if (slot && window && (jp > j ? (int)(now - earliest) >= 0 : due)) break;
            if (due && jp < 16 * NB && jp - j < CFG(PMAX) && (jp > j || (int)(now - t0) >= shift + CFG(PGRACE))) {
                if (elect_one()) l2_prefetch((jp & 8 ? p.vc : p.kc) + (size_t)kv_group(jp >> 4, jp & 7) * 3072, TILE);
                requested(now);
            }
            SPIN_CHECK(j);
        }
        if (elect_one()) {
            mbar_expect_tx(bar_at(B_F1 + t), TILE);
            tma_tile(dst, t & 8 ? tmV : tmK, kv_group(k, t & 7), bar_at(B_F1 + t), t < 10 && j >= 8 && j < 56 ? POL_NORMAL : POL_FIRST);
        }
        TRACE(256 + j);
        earliest = now + CFG(VSTEP);
        if (jp == j) requested(now);
    }
}

__device__ __forceinline__ void reload_role(const Params& p, const CUtensorMap* tmK, const CUtensorMap* tmV, const WeightMaps* tm, uint32_t t0) {
    const int cta = blockIdx.x;
    t0 += CFG(TICK0) + CFG(WLAG) + phase_ns();
#pragma unroll 1
    for (int i = 0; i < 5; i++) {
        wait_ns(t0 + i * CFG(TICK0));
        if (elect_one()) tma2d(ST_WQ + i * 12288, &tm->q, 48 * cta, 128 * i, bar_at(B_W));
        if (i == 1) bar_sync<5, 480>();
    }
#pragma unroll 1
    for (int i = 0, o = 0; i < 10;) {
        const uint32_t now = now_ns() - t0;
        if (o < 6 && (int)now >= kb_ns(105) + o * kb_ns(10)) {
            if (elect_one()) tma2d(ST_WO + o * 10240, &tm->o, 160 * (cta & 3), (cta >> 2) * DH + 32 * o, bar_at(B_W + 1));
            o++;
        } else if ((int)now >= kb_ns(77) + i * CFG(GSTEP) && (i < 9 || o == 6)) {
            if (elect_one()) tma2d(ST_WG + (i & 1) * 20480 + (i >> 1) * 4096, i & 1 ? &tm->u : &tm->g, (12 * cta) & ~7, 128 * (i >> 1), bar_at(B_W + 2));
            i++;
        }
    }
#pragma unroll 1
    for (int k = 0; k < NB - 1; k++) {
        mbar_wait(bar_at(B_RK), k & 1);
        if (elect_one()) {
            const uint32_t dst = SB + slot_at(slots(k), 0) * PAIR;
            mbar_expect_tx(bar_at(B_FL), PAIR);
            tma_tile(dst, tmV, kv_group(k, 0), bar_at(B_FL), POL_FIRST);
            tma_tile(dst + TILE, tmV, kv_group(k, 1), bar_at(B_FL), POL_FIRST);
        }
        mbar_wait(bar_at(B_RV), k & 1);
        uint32_t due = now_ns() + (k == NB - 2 ? 0 : CFG(RLAG));
        if (elect_one()) mbar_expect_tx(bar_at(B_F3), 4 * PAIR);
#pragma unroll 1
        for (int t = 0; t < 8; t++) {
            wait_ns(due);
            due += k == NB - 2 ? CFG(RSTEP3) : CFG(RSTEP);
            if (elect_one())
                tma_tile(SB + slot_at(slots(k + 1), t >> 1) * PAIR + (t & 1) * TILE, tmK, kv_group(k + 1, t), bar_at(B_F3), POL_FIRST);
        }
        TRACE(121 + k);
    }
}

__device__ __forceinline__ void zero_role(const Params& p, int lane, unsigned ticket, uint32_t t0) {
    const int cta = blockIdx.x;
    const uint32_t epoch = __shfl_sync(0xffffffffu, ticket, 0) / NCTA + 1;
    if (lane == 0) { sts32(SM_EPOCH, epoch); mbar_arrive(bar_at(B_EP)); }
#pragma unroll 1
    for (int k = 0; k < NB + 2; k++) {
        lane = opaque(lane);
        const int cl = 2 * (cta & 15) + (lane & 1);
        const int col = 80 * (cta >> 4) + (cl & 2 ? 48 : 0) + (cl >> 2) + (cl & 1 ? 8 : 0);
        const char* own = p.scr + (cl >> 2) * 256 + (cl & 3) * 16;
        if (k < NB) {
            wait_ns(t0 + batch_ns(k) + CFG(ZTILE) * CFG(TICK0));
            const int lg = lane >> 3, ty = (lane & 7) >> 1;
            const char* dst = own + acc_off((k - (lg >> 1)) & 3, lg != 0, cta >> 4) + ty * HALF;
            uint32_t v0 = 0, v1 = 0, v2 = 0, v3 = 0;
            if (lane < 4) {
                const unsigned short* xp = p.x + k * DM + col;
                v0 = __ldg(xp) << 16; v1 = __ldg(xp + 16) << 16; v2 = cl & 2 ? 0 : __ldg(xp + 32) << 16; v3 = 0x3f800000u;
            }
            if (lg == 0 || (lg == 1 && (ty < 2 || k == NB - 1)) || (lg == 2 && k > 0 && ty > 1)) st_pkt(dst, v0, v1, v2, v3);
            asm volatile("fence.acq_rel.gpu;" ::: "memory");
            __syncwarp();
            if (lane == 0) asm volatile("red.relaxed.gpu.global.add.u32 [%0], 1;" ::"l"(&g_init) : "memory");
            const uint32_t target = ((epoch - 1) * NB + k + 1) * NCTA;
            SPIN_DECL;
            while (true) {
                __nanosleep(400);
                uint32_t v;
                asm volatile("ld.acquire.gpu.global.u32 %0, [%1];" : "=r"(v) : "l"(&g_init) : "memory");
                if (__all_sync(0xffffffffu, (int)(v - target) >= 0)) break;
                SPIN_CHECK(v);
            }
        }
        uint4 r;
        if (k == 1) mbar_wait(bar_at(B_RK), 0);
        if (k > 1) {
            mbar_wait(bar_at(B_FIN), k & 1);
            r = lds128(SM_FIN + (lane & 1) * 16);
        }
        __syncwarp();
        if (lane == 0) mbar_arrive(bar_at(B_Z));
        if (k > 1) {
            const int b = k - 2;
            const char* src = own + acc_off(b, 1, cta >> 4) + (2 + ((lane >> 1) & 1)) * HALF;
            unsigned short* o = p.out + b * DM + col;
            wait_clk(clk32() + CFG(DLY_F));
            uint4 v = {};
            SPIN_DECL;
            while (true) {
                v = ld_pkt(src);
                if (__all_sync(0xffffffffu, F(v.w) + shx(F(v.w), 2) == NCTA)) break;
                SPIN_CHECK(k);
            }
            const float y0 = F(v.x) + shx(F(v.x), 2), y1 = F(v.y) + shx(F(v.y), 2), y2 = F(v.z) + shx(F(v.z), 2);
            const uint32_t x01 = badd2(r.x, badd2(r.y, bmul2(pack2(y0, y1), r.w)));
            const uint32_t x2 = badd2(r.z, badd2(r.z >> 16, bmul2(pack2(y2, 0.f), r.w)));
            if (lane < 2) {
                o[0] = x01; o[16] = x01 >> 16;
                if (!(cl & 2)) o[32] = x2;
            }
            TRACES((2 * b + 1) * 6 + 4);
        }
    }
}

__host__ __device__ constexpr uint32_t desc_lo(uint32_t addr) { return ((addr & 0x3FFFFu) >> 4) | (1u << 16); }
constexpr uint32_t DESC_HI_TILE = (3072u >> 4) | (1u << 30);
constexpr uint32_t DESC_HI_VEC = 1u;
template <int TA, int AOFF, int BOFF>
__device__ __forceinline__ void wgmma_n8(float (&d)[4], uint32_t alo, uint32_t blo, int accumulate) {
    asm volatile("{\n.reg .pred p;\n.reg .b32 a, b;\n.reg .b64 da, db;\nsetp.ne.b32 p, %6, 0;\n"
                 "add.u32 a, %4, %8;\nadd.u32 b, %5, %9;\nmov.b64 da, {a, %10};\nmov.b64 db, {b, %11};\n"
                 "wgmma.mma_async.sync.aligned.m64n8k16.f32.bf16.bf16 {%0,%1,%2,%3}, da, db, p, 1, 1, %7, 0;\n}"
                 : "+f"(d[0]), "+f"(d[1]), "+f"(d[2]), "+f"(d[3])
                 : "r"(alo), "r"(blo), "r"(accumulate), "n"(TA), "n"(AOFF >> 4), "n"(BOFF >> 4), "n"(DESC_HI_TILE), "n"(DESC_HI_VEC));
}
template <int KS, int END>
__device__ __forceinline__ void qk_steps(float (&d)[4], uint32_t alo, uint32_t blo) {
    if constexpr (KS < END) {
        wgmma_n8<0, (KS >> 2) * 1024 + (KS & 3) * 32, KS * 32>(d, alo, blo, KS > 0);
        qk_steps<KS + 1, END>(d, alo, blo);
    }
}
__device__ __forceinline__ void pv_steps(float (&e)[3][4], uint32_t alo, uint32_t blo, int acc) {
    wgmma_n8<1, 0, 0>(e[0], alo, blo, acc); wgmma_n8<1, 1024, 0>(e[1], alo, blo, acc); wgmma_n8<1, 2048, 0>(e[2], alo, blo, acc);
    wgmma_n8<1, 6144, 32>(e[0], alo, blo, 1); wgmma_n8<1, 7168, 32>(e[1], alo, blo, 1); wgmma_n8<1, 8192, 32>(e[2], alo, blo, 1);
}
__device__ __forceinline__ void wg_fence() { asm volatile("wgmma.fence.sync.aligned;" ::: "memory"); }
__device__ __forceinline__ void wg_commit() { asm volatile("wgmma.commit_group.sync.aligned;" ::: "memory"); }
template <int N> __device__ __forceinline__ void wg_wait() { asm volatile("wgmma.wait_group.sync.aligned %0;" ::"n"(N) : "memory"); }
__device__ __forceinline__ void acc_ready(float (&d)[4]) { asm volatile("" : "+f"(d[0]), "+f"(d[1]), "+f"(d[2]), "+f"(d[3]) :: "memory"); }
__device__ __forceinline__ uint32_t score_pair(float (&d)[4], int lane) {
    acc_ready(d);
    const float scale = 0.07216878364870322f;
    const uint32_t r = pack2(d[0], d[2]);
    return shi(pack2(bf_lo(r) * scale, bf_hi(r) * scale), lane & 28);
}

__device__ __forceinline__ void attention_role(const Params& p, int w, int lane) {
    const int cta = blockIdx.x, t4 = lane & 3, g = lane >> 2;
    mbar_wait(bar_at(B_EP), 0);
    const uint32_t tag0 = lds32(SM_EPOCH) * NB;
    const char* const odst = p.scr + SCR_O + head_off(cta >> 2) + (2 * w + (g >> 2)) * 256 + (cta & 3) * 64 + (g & 3) * 16;
    const uint32_t pdst = SM_P + t4 * PSTR + (16 * w + g) * 2;
    auto softmax = [&](uint32_t sc, int ps) -> uint32_t {
        const float s0 = bf_lo(sc), s1 = bf_hi(sc);
        int key = __float_as_int(fmaxf(s0, s1));
        key ^= (key >> 31) & 0x7fffffff;
        key = __reduce_max_sync(0xffffffffu, key);
        sts32(SM_MAX + w * 4, key);
        bar_sync<4, 128>();
        const uint4 mx = lds128(SM_MAX);
        key = max(max((int)mx.x, (int)mx.y), max((int)mx.z, (int)mx.w));
        key ^= (key >> 31) & 0x7fffffff;
        const float mb = __int_as_float(key) * LOG2E;
        const uint32_t pp = pack2(fast_ex2(fmaf(s0, LOG2E, -mb)), fast_ex2(fmaf(s1, LOG2E, -mb)));
        sts16(pdst + ps * 4 * PSTR, pp); sts16(pdst + ps * 4 * PSTR + 16, pp >> 16);
        uint32_t fs;
        asm volatile("redux.sync.add.u32 %0, %1, 0xffffffff;" : "=r"(fs) : "r"(__float2uint_rn((bf_lo(pp) + bf_hi(pp)) * 8388608.f)));
        fence_async();
        bar_sync<4, 128>();
        sts32(SM_SUM + ps * 16 + w * 4, fs);
        return key;
    };
    auto aux_word = [&](uint32_t mx, const uint4& u, int k) {
        const float l = __uint2float_rn((u.x + u.y) + (u.z + u.w)) * (1.f / 8388608.f);
        return (g < 4 ? mx : (__float_as_uint(l) + 0x80u) & 0xffffff00u) | ((tag0 + k) & 0xffu);
    };
    auto send = [&](float (&e)[3][4], uint32_t aux, int ps) {
        acc_ready(e[0]); acc_ready(e[1]); acc_ready(e[2]);
        const uint32_t o0 = pack2(e[0][0], e[0][2]), o1 = pack2(e[1][0], e[1][2]), o2 = pack2(e[2][0], e[2][2]);
        st_pkt2_if(t4 == 0, odst + ps * 2048, o0, o1, o2, aux);
        mbar_arrive_if(lane == 0, bar_at(ps ? B_RV : B_PS));
    };
    mbar_wait(bar_at(B_QR), 0);
    TRACES(73);
#pragma unroll 1
    for (int it = 0; it <= NB; it++) {
        uint32_t m1 = 0;
        if (it < NB) {
            const uint32_t tab = slots(it);
            uint32_t sc = 0;
#pragma unroll 1
            for (int t = 0; t < 8; t++) {
                const uint32_t alo = desc_lo(SB) + slot_at(tab, pass_nibble(it, t >> 1)) * (PAIR >> 4), blo = desc_lo(SM_Q) + it * (384 >> 4);
                mbar_wait(bar_at(B_F1 + t), it & 1);
                float d[4] = {};
#pragma unroll 1
                for (int c = 0; c < 3; c++) {
                    wg_fence();
                    wgmma_n8<0, 0, 0>(d, alo + c * 64, blo + c * 8, c > 0); wgmma_n8<0, 32, 32>(d, alo + c * 64, blo + c * 8, 1);
                    wgmma_n8<0, 64, 64>(d, alo + c * 64, blo + c * 8, 1); wgmma_n8<0, 96, 96>(d, alo + c * 64, blo + c * 8, 1);
                    wg_commit();
                    wg_wait<0>();
                }
                if ((t & 1) == (w >> 1)) {
                    mbar_arrive_if(lane == 0, bar_at(B_RR + t));
                    const uint32_t s = score_pair(d, lane);
                    if (t4 == t >> 1) sc = s;
                }
            }
            m1 = softmax(sc, 0);
        }
        if (it > 0) {
            const int k = it - 1;
            const uint32_t tab = slots(k);
            const uint32_t v0 = slot_at(tab, k < NB - 1 ? 0 : 4);
            TRACES(48 + k * 6);
            if (k > 0) mbar_wait(bar_at(B_F3), it & 1);
            mbar_wait(bar_at(B_QR), it & 1);
            TRACES(49 + k * 6);
            float d[4][4] = {};
#pragma unroll
            for (int u = 0; u < 4; u++) {
                const uint32_t alo = desc_lo(SB) + slot_at(tab, u) * (PAIR >> 4), blo = desc_lo(SM_Q + 4 * 384);
                wg_fence();
                qk_steps<0, 6>(d[u], alo, blo);
                wg_commit();
                wg_wait<1>();
                if (u > 0) mbar_arrive_if(lane == 0, bar_at(B_RK + u - 1));
                wg_fence();
                qk_steps<6, 12>(d[u], alo, blo);
                wg_commit();
                if (u < 3) wg_wait<1>();
            }
            uint32_t sc = score_pair(d[0], lane), s = score_pair(d[1], lane);
            if (t4 == 1) sc = s;
            s = score_pair(d[2], lane);
            if (t4 == 2) sc = s;
            wg_wait<0>();
            s = score_pair(d[3], lane);
            mbar_arrive_if(lane == 0, bar_at(B_RK + 3));
            if (t4 == 3) sc = s;
            TRACES(50 + k * 6);
            const uint32_t m2 = softmax(sc, 1);
            TRACES(51 + k * 6);
            float e[3][4] = {};
            uint4 u;
#pragma unroll
            for (int t = 0; t < 8; t++) {
                const int pr = ((t >> 1) + 1) & 3;
                if (t == 6 && k < NB - 1) mbar_wait(bar_at(B_FL), k & 1);
                if (t == 7) { bar_sync<4, 128>(); u = lds128(SM_SUM + 16); }
                wg_fence();
                pv_steps(e, desc_lo(SB + (t & 1) * TILE) + (pr ? slot_at(tab, 4 + pr) : v0) * (PAIR >> 4), desc_lo(SM_P + (4 + pr) * PSTR + (t & 1) * 64), t > 0);
                wg_commit();
                if (t < 7) wg_wait<1>();
                if (t == 0) st_pkt2_if(t4 == 0, odst + 2048, 0, 0, 0, tag0 + k + 128);
            }
            const uint32_t aux = opaque(aux_word(m2, u, k));
            wg_wait<0>();
            send(e, aux, 1);
            TRACES(52 + k * 6);
        }
        if (it < NB) {
            const uint32_t tab = slots(it);
            st_pkt2_if(t4 == 0, odst, 0, 0, 0, tag0 + it + 128);
            bar_sync<4, 128>();
            const uint32_t aux = opaque(aux_word(m1, lds128(SM_SUM), it));
            float e[3][4] = {};
#pragma unroll 1
            for (int u = 0; u < 4; u++) {
                const uint32_t alo = desc_lo(SB) + slot_at(tab, 4 + u) * (PAIR >> 4), blo = desc_lo(SM_P) + u * (PSTR >> 4);
                mbar_wait(bar_at(B_F1 + 8 + 2 * u), it & 1);
                wg_fence();
                pv_steps(e, alo, blo, u > 0);
                wg_commit();
                wg_wait<1>();
                if (u == 1) mbar_arrive_if(lane == 0, bar_at(B_RP));
                mbar_wait(bar_at(B_F1 + 9 + 2 * u), it & 1);
                wg_fence();
                pv_steps(e, alo + (TILE >> 4), blo + 4, 1);
                wg_commit();
                wg_wait<1>();
            }
            wg_wait<0>();
            send(e, aux, 0);
            TRACES(53 + it * 6);
        }
    }
}

__device__ __forceinline__ void ln_finish(float s, float q, float& mean_b, float& rden) {
    const float mean = s * (1.f / DM);
    const float var = fmaxf(fmaf(q, 1.f / DM, -mean * mean), 0.f);
    mean_b = bfr(mean);
    rden = fast_rcp(bfr(fast_sqrt(bfr(bfr(var) + 1e-5f))));
}
__device__ __forceinline__ uint32_t ln_apply(uint32_t w, float mean_b, float rden) {
    const uint32_t d = bsub2(w, __byte_perm(__float_as_uint(mean_b), 0, 0x3232));
    return pack2(bf_lo(d) * rden, bf_hi(d) * rden);
}
__device__ __forceinline__ void spread(uint32_t (&b)[10], uint32_t x01, uint32_t x2, uint32_t wa, uint32_t ra, bool e2) {
    sts16(wa, x01); sts16(wa + 8, x01 >> 16);
    sts16_if(!e2, wa + 16, x2);
    __syncwarp();
    const uint4 u = lds128(ra), v = lds128(ra + 16);
    const uint2 z = lds64(ra + 32);
    b[0] = u.x; b[1] = u.y; b[2] = u.z; b[3] = u.w; b[4] = v.x; b[5] = v.y; b[6] = v.z; b[7] = v.w; b[8] = z.x; b[9] = z.y;
}
__device__ __forceinline__ float fold(float a, float b, bool sel, int m) { return (sel ? b : a) + shx(sel ? a : b, m); }

__device__ __forceinline__ void chain_role(const Params& p, int w, int lane, uint32_t t0) {
    const int cta = blockIdx.x, h = cta >> 2, s = cta & 3;
    const int g = lane >> 2, t4 = lane & 3;
    const bool e1 = t4 & 1, e2 = t4 & 2;
    uint32_t wq[5][3][4], wo[3][5][4], wg[5][4], wh[5][2], wd[4][4];
    const int col0 = 80 * w + (e2 ? 48 : 0) + g + (e1 ? 8 : 0);
    const uint32_t xw = opaque(SM_X + w * 384 + 48 * (g >> 1) + (e2 ? 24 : 0) + (e1 ? 4 : 0) + 2 * (g & 1));
    const uint32_t xr = opaque(g == 1 ? SM_ONES : SM_X + w * 384 + (g == 3 ? 192 : 0) + 48 * t4);
    TRACES(75);
    sts32_if(lane < 12, SM_ONES + lane * 4, 0x3f803f80u);
    uint32_t zero = lane >> 5;
    const int mi = lane >> 3, mr = lane & 7;
    mbar_wait(bar_at(B_W), 0);
    TRACES(74);
    sts16(xw + 192, lds16(ST_X + 5120 + col0 * 2)); sts16(xw + 200, lds16(ST_X + 5120 + col0 * 2 + 32));
    sts16_if(!e2, xw + 208, lds16(ST_X + 5120 + col0 * 2 + 64));
#pragma unroll
    for (int i = 0; i < 5; i++)
#pragma unroll
        for (int mt = 0; mt < 3; mt++) ldsm4t(wq[i][mt], ST_WQ + (80 * w + 16 * i + mr + 8 * (mi >> 1)) * 96 + 32 * mt + 16 * (mi & 1), zero);
    const bool odd = cta & 1;
    const uint32_t lo = ST_WD + (mr + (odd ? 4 : 0)) * 1280 + 160 * w, hi = ST_WD + ((mr & 3) + (odd ? 0 : 8)) * 1280 + 160 * w;
    ldsm4t(wd[0], lo + 16 * mi, zero);
    ldsm4t(wd[1], lo + 64 + 16 * mi, zero);
    ldsm4t(wd[2], hi + 64 * (mi >> 1) + 32 * (mr >> 2) + 16 * (mi & 1), zero);
    ldsm4t(wd[3], (mi < 2 ? lo : hi) + 128 + 16 * (mi & 1), zero);
    fence_async();
    __syncwarp();
    mbar_arrive_if(lane == 0, bar_at(B_WC));
    mbar_wait(bar_at(B_EP), 0);
    const uint32_t near = __shfl_sync(0xffffffffu, near_half(), 0);
    uint32_t x01 = 0, x2 = 0, nx01 = 0, nx2 = 0;
#pragma unroll 1
    for (int n = -5; n < NROUND; n++) {
        const bool last = (ORD_LAST >> (n & 15)) & 1, head = !((ORD_NO_HEAD >> (n & 15)) & 1);
        const int k = (ORD_BATCH >> (2 * (n & 15))) & 3;
        if (n > -5 && n <= 0) bar_sync<7, 288>();
        else if (!last) bar_sync<2, 256>();
        TRACES(n <= 0 ? 83 + n : 95);
        const char* const slice = p.scr + acc_off(k, last, w);
        const char* const cell = opaque(slice + g * 256 + t4 * 16);
        if (n >= 0) {
          if (head) {
            if (!last || n == NROUND - 1) mbar_wait(bar_at(B_Z), (k + last) & 1);
            const char* src = p.scr + SCR_O + head_off(h) + head_near(h, near) + last * 2048 + (w & 6) * 256 + (lane & 15) * 16;
            const uint32_t tag = lds32(SM_EPOCH) * NB + k;
            mbar_wait(bar_at(last ? B_RV : B_PS), k & 1);
            if (n < QUIET) wait_clk(clk32() + (last ? CFG(DLY_PB) : CFG(DLY_PL)));
            if (!last && k < NB - 1) wait_ns(t0 + batch_ns(k + 1) + CFG(START));
            uint4 v, z;
            {
                SPIN_DECL;
                do {
                    v = ld_pkt(src); z = ld_pkt(src + 256);
                    SPIN_CHECK(n);
                } while (__any_sync(0xffffffffu, (((v.w ^ tag) | (z.w ^ tag)) & 0xffu) != 0));
            }
            TRACES(tr + 0);
            float a[3][4] = {};
            const uint32_t bb[3][2] = {{v.x, v.y}, {z.x, z.y}, {v.z, z.z}};
            float sa, sb, rl;
#pragma unroll
            for (int i = 0; i < 3; i++) {
                const uint32_t l0 = g < 4 ? bb[i][0] : 0, l1 = g < 4 ? bb[i][1] : 0, h0 = g < 4 ? 0 : bb[i][0], h1 = g < 4 ? 0 : bb[i][1];
#pragma unroll
                for (int mt = 0; mt < 5; mt++)
                    mma16816(a[mt % 3], wo[i][mt][0], wo[i][mt][1], wo[i][mt][2], wo[i][mt][3], mt < 3 ? l0 : h0, mt < 3 ? l1 : h1);
                if (i == 0) {
                    int key = v.w & 0xffffff00u;
                    key ^= (key >> 31) & 0x7fffffff;
                    key = __reduce_max_sync(0xffffffffu, key);
                    key ^= (key >> 31) & 0x7fffffff;
                    const float ws = fast_ex2((F(v.w & 0xffffff00u) - __int_as_float(key)) * LOG2E);
                    sa = shi(ws, e1 ? 8 : 0); sb = shi(ws, e1 ? 12 : 4);
                    rl = ws * F(z.w & 0xffffff00u);
                    rl += shx(rl, 4);
                }
                if (i == 1) rl += shx(rl, 8);
            }
            float y[3];
#pragma unroll
            for (int j = 2; j < 5; j++) {
                const int mt = j % 3;
                y[mt] = fold(fmaf(a[mt][0], sa, a[mt][1] * sb), fmaf(a[mt][2], sa, a[mt][3] * sb), e1, 1);
            }
            const uint32_t pa = SM_PO + w * 512 + lane * 16;
            if (w < 2) {
                const char* dst = opaque(cell + s * 16384);
                rl = fast_rcp(rl);
                bar_sync<1, 256>();
                const uint4 c1 = lds128(pa), c2 = lds128(pa + 1024), c3 = lds128(pa + 2048);
                red_cell2_if(true, dst, ((y[0] + F(c1.x)) + (F(c2.x) + F(c3.x))) * rl, ((y[1] + F(c1.y)) + (F(c2.y) + F(c3.y))) * rl,
                             ((y[2] + F(c1.z)) + (F(c2.z) + F(c3.z))) * rl);
            } else {
                stsf4(pa - 1024, y[0], y[1], y[2], 0.f);
                bar_sync<1, 256>();
            }
            TRACES(tr + 1);
            if ((ORD_NO_TAIL >> n) & 1) continue;
            wait_clk(clk32() + (w < 2 ? 0 : 60) + (n < QUIET ? CFG(DLY_AL) : CFG(DLY_A)));
            {
                SPIN_DECL;
                do {
                    v = ld_pkt(cell + near);
                    SPIN_CHECK(n);
                } while (__any_sync(0xffffffffu, v.w != FULL_A));
            }
            TRACES(tr + 2);
            x01 = pack2(F(v.x), F(v.y));
            x2 = pack2(F(v.z), 0.f);
          } else { x01 = nx01; x2 = nx2; }
        } else if (n == -1) {
            mbar_wait(bar_at(B_W + 1), 0);
            const uint32_t ln = opaque(lane);
            const int mi = ln >> 3, mr = ln & 7;
            uint32_t zero = ln >> 5;
            TRACES(76);
#pragma unroll
            for (int i = 0; i < 3; i++) {
                const int d = 16 * (w >> 1) + (mr >> 1) + 8 * (mr & 1) + (i < 2 ? 64 * (mi >> 1) + 4 * i : 128 + 4 * (mi >> 1));
#pragma unroll
                for (int mt = 0; mt < 5; mt++) ldsm4t(wo[i][mt], ST_WO + d * 320 + 160 * (w & 1) + 32 * mt + 16 * (mi & 1), zero);
            }
            fence_async();
            __syncwarp();
            mbar_arrive_if(lane == 0, bar_at(B_WC + 1));
            mbar_wait(bar_at(B_W + 2), 0);
            TRACES(77);
#pragma unroll
            for (int i = 0; i < 5; i++) {
                const uint32_t ga = ST_WG + (mi & 1) * 20480 + (80 * w + 16 * i + mr + 8 * (mi >> 1)) * 32;
                uint32_t r[4];
                ldsm4t(wg[i], ga + (odd ? 16 : 0), zero);
                ldsm4t(r, ga + (odd ? 0 : 16), zero);
#pragma unroll
                for (int kh = 0; kh < 2; kh++) {
                    const uint32_t moved = __shfl_xor_sync(0xffffffffu, odd ? r[2 * kh] : r[2 * kh + 1], 16);
                    wh[i][kh] = (g < 4) == odd ? moved : odd ? r[2 * kh + 1] : r[2 * kh];
                }
            }
            fence_async();
            __syncwarp();
            mbar_arrive_if(lane == 0, bar_at(B_WC + 2));
            TRACES(72);
            x01 = 0x3f803f80u; x2 = 0x3f80u;
        } else {
            const uint32_t xa = ST_X + (n + 5) * 1280, ln = opaque(lane);
            const int col0 = 80 * w + (ln & 2 ? 48 : 0) + (ln >> 2) + (ln & 1 ? 8 : 0);
            float sm = 0.f, sq = 0.f;
#pragma unroll
            for (int i = 0; i < 5; i++) {
                const uint2 c = lds64(xa + i * 256 + ln * 8);
                sm += (bf_lo(c.x) + bf_hi(c.x)) + (bf_lo(c.y) + bf_hi(c.y));
                sq = fmaf(bf_lo(c.x), bf_lo(c.x), fmaf(bf_hi(c.x), bf_hi(c.x), fmaf(bf_lo(c.y), bf_lo(c.y), fmaf(bf_hi(c.y), bf_hi(c.y), sq))));
            }
            x01 = lds16(xa + col0 * 2) | lds16(xa + col0 * 2 + 32) << 16;
            x2 = lds16(xa + col0 * 2 + 64);
#pragma unroll
            for (int o = 16; o; o >>= 1) { sm += shx(sm, o); sq += shx(sq, o); }
            float mean_b, rden;
            ln_finish(sm, sq, mean_b, rden);
            x01 = ln_apply(x01, mean_b, rden);
            x2 = ln_apply(x2, mean_b, rden);
        }
        if (n >= -1) {
            uint32_t b[10];
            spread(b, x01, x2, xw, xr, e2);
            float a[2][4] = {};
#pragma unroll
            for (int i = 0; i < 5; i++) {
                mma16816(a[0], wg[i][0], wg[i][1], wg[i][2], wg[i][3], b[2 * i], b[2 * i + 1]);
                mma16816(a[1], wh[i][0], b[2 * i], wh[i][1], b[2 * i + 1], b[2 * i], b[2 * i + 1]);
            }
            stsf(SM_PG + (w >> 2) * 512 + (g + 8 * t4) * 16 + (w & 3) * 4, e2 ? (e1 ? a[1][2] : a[1][0]) : (e1 ? a[0][2] : a[0][0]));
            const uint2 cs = lds64(SM_CSG + lane * 48);
            const char* dst = opaque(cell + 3 * HALF - near);
            bar_sync<2, 256>();
            const float S = sum8(lds128(SM_PG + lane * 16), lds128(SM_PG + 512 + lane * 16));
            const float sx = shi(S, 25), sq = shi(S, 24), Su = shi(S, lane + (lane < 16 ? 8 : 4));
            if (n < 0) {
                if (w == 0) stsf2(SM_CSG + lane * 48, S, Su);
            } else {
                float mean_b, rden;
                ln_fast(sx, sq, mean_b, rden);
                const float gv = bfr(fmaf(-mean_b, F(cs.x), S) * rden), uv = bfr(fmaf(-mean_b, F(cs.y), Su) * rden);
                const float sg = fast_rcp(1.f + fast_ex2(-LOG2E * gv));
                const uint32_t hb = pack2(bfr(gv * sg) * uv, 0.f);
                const uint32_t b0 = __byte_perm(shi(hb, 2 * t4), shi(hb, 2 * t4 + 1), 0x5410);
                const uint32_t b1 = __byte_perm(shi(hb, e1 ? 18 : 16), shi(hb, e1 ? 19 : 17), 0x5410);
                const bool up = g >= 4;
                const uint32_t l0 = up ? 0 : b0, h0 = up ? b0 : 0;
                const uint32_t l1 = up ? 0 : b1, h1 = up ? b1 : 0;
                float d[3][4] = {};
                mma1688(d[0], wd[0][0], wd[0][1], l0); mma1688(d[1], wd[0][2], wd[0][3], l0); mma1688(d[2], wd[1][0], wd[1][1], l0);
                mma1688(d[0], wd[1][2], wd[1][3], h0); mma1688(d[1], wd[3][0], wd[3][1], h0);
                mma1688(d[2], wd[2][2], wd[2][3], e2 ? 0 : l1);
                mma1688(d[0], wd[2][0], wd[2][1], e2 ? 0 : l1); mma1688(d[1], wd[2][0], wd[2][1], e2 ? l1 : 0);
                mma1688(d[0], wd[2][2], wd[2][3], e2 ? h1 : 0); mma1688(d[1], wd[3][2], wd[3][3], e2 ? 0 : h1);
                red_cell(dst, e1 ? d[0][2] : d[0][0], e1 ? d[1][2] : d[1][0], e1 ? d[2][2] : d[2][0]);
                const uint32_t tsend = clk32();
                TRACES(tr + 3);
                if (last && w != cta >> 4) continue;
                if (!last && w == 0) st_pkt82_if(lane < 24, p.scr + SCR_Q + head_off(h) + 4 * 768 + (24 * s + lane) * 8, 0, 0);
                const float sgr = shi(sg, 27);
                const uint32_t sg2 = pack2(sgr, sgr);
                const uint32_t n01 = opaque(pack2((bf_lo(x01) - mean_b) * rden, (bf_hi(x01) - mean_b) * rden));
                const uint32_t n2 = opaque(pack2((bf_lo(x2) - mean_b) * rden, 0.f));
                if (last) {
                    sts128_if(lane >> 1 == (cta & 15), SM_FIN + (lane & 1) * 16, x01, n01, __byte_perm(x2, n2, 0x5410), sg2);
                    mbar_arrive_if(lane >> 1 == (cta & 15), bar_at(B_FIN));
                    __syncwarp();
                    continue;
                }
                if (n > 0) {
                    const char* src = p.scr + acc_off(k - 1, 1, w) + near + g * 256 + t4 * 16;
                    SPIN_DECL;
                    while (true) {
                        const uint4 u = ld_pkt(src);
                        nx01 = pack2(F(u.x), F(u.y)); nx2 = pack2(F(u.z), 0.f);
                        if (__all_sync(0xffffffffu, u.w == FULL_A)) break;
                        SPIN_CHECK(n);
                    }
                }
                wait_clk(tsend + (n < QUIET ? CFG(DLY_BL) : CFG(DLY_B)));
                uint4 v, z;
                {
                    SPIN_DECL;
                    do {
                        v = ld_pkt(cell + 2 * HALF); z = ld_pkt(cell + 3 * HALF);
                        SPIN_CHECK(n);
                    } while (__any_sync(0xffffffffu, F(v.w) + F(z.w) != NCTA));
                }
                x01 = badd2(x01, badd2(n01, bmul2(pack2(F(v.x) + F(z.x), F(v.y) + F(z.y)), sg2)));
                x2 = badd2(x2, badd2(n2, bmul2(pack2(F(v.z) + F(z.z), 0.f), sg2)));
                TRACES(tr + 4);
            }
        }
        {
            uint32_t b[10];
            spread(b, x01, x2, xw, xr, e2);
            float a[3][4] = {};
            const float f0 = bf_lo(x01), f1 = bf_hi(x01), f2 = e2 ? 0.f : bf_lo(x2);
            float st;
#pragma unroll
            for (int i = 0; i < 5; i++) {
#pragma unroll
                for (int mt = 0; mt < 3; mt++) {
                    mma16816(a[mt], wq[i][mt][0], wq[i][mt][1], wq[i][mt][2], wq[i][mt][3], b[2 * i], b[2 * i + 1]);
                    if (i == 0 && mt == 0) st = fold(fmaf(f0, f0, fmaf(f1, f1, f2 * f2)), (f0 + f1) + f2, g & 1, 4);
                }
                if (i < 4) st += shx(st, i < 2 ? 1 << i : 2 << i);
            }
            const uint32_t pa = SM_PQ + (w >> 2) * 1024 + (g & 1) * 512 + ((e2 ? 16 : 0) + (e1 ? 4 : 0) + (g >> 1)) * 16 + (w & 3) * 4;
            stsf(pa + 128, e2 ? st : e1 ? a[1][2] : a[1][0]);
            stsf(pa, e2 ? (e1 ? a[2][2] : a[2][0]) : (e1 ? a[0][2] : a[0][0]));
            bar_arrive<3, 288>();
            if (n >= 0 && w == cta >> 4) {
                red_cell2_if(lane >> 1 == (cta & 15), cell + 128, f0, f1, f2);
                __syncwarp();
            }
        }
    }
}

template <int ID> __device__ __forceinline__ void role_exit() { asm volatile("exit; // %0" ::"n"(ID)); }
constexpr int NTHREADS = 512;
#define STR2(x) #x
#define STR(x) STR2(x)
__global__ void __launch_bounds__(NTHREADS, 1)
decode_kernel(const Params p, const __grid_constant__ CUtensorMap tmK, const __grid_constant__ CUtensorMap tmV,
              const __grid_constant__ WeightMaps tmW) {
    extern __shared__ __align__(1024) unsigned char smem[];
    if (threadIdx.x == 0) l2_prefetch(p.wq + (size_t)blockIdx.x * 12288, 12288);
    const uint32_t t0 = now_ns() - CFG(LEAD);
    const int lane = threadIdx.x & 31;
    const int warp = __shfl_sync(0xffffffffu, threadIdx.x >> 5, 0);
    if (warp < 8) {
        asm volatile("setmaxnreg.inc.sync.aligned.u32 " STR(CFG_REG_CHAIN) ";");
        bar_arrive<5, 480 + 0>();
        const uint32_t vote = probe_near(p, warp, lane);
        bar_sync<2, 256 + 32>();
        asm volatile("st.shared.u8 [%0], %1;" ::"r"(SM_NEAR + warp), "r"(vote) : "memory");
        mbar_arrive_if(lane == 0, bar_at(B_EP));
        chain_role(p, warp, __shfl_sync(0xffffffffu, lane, lane), t0);
        role_exit<3>();
    } else if (warp < 12) {
        asm volatile("setmaxnreg.dec.sync.aligned.u32 " STR(CFG_REG_ATT) ";");
        if (elect_one()) {
#pragma unroll 1
            for (int i = warp - 8; i < NBAR; i += 4)
                if (i < B_W || i >= B_WC) mbar_init(bar_at(i), i == B_FIN ? 2 : i == B_EP ? 9 : i == B_QR ? 32 : i == B_PS || i == B_RP ? 4 : i >= B_F3 ? 1 : i >= B_WC ? 8 : i < B_RR || i > B_RV ? 1 : i < B_RK ? 2 : 4);
            asm volatile("fence.mbarrier_init.release.cluster;" ::: "memory");
            fence_async();
        }
        bar_sync<5, 480>();
        attention_role(p, warp - 8, lane);
        role_exit<2>();
    } else {
        asm volatile("setmaxnreg.dec.sync.aligned.u32 " STR(CFG_REG_HELP) ";");
        if (warp == 12) {
            load_role(p, &tmK, &tmV, t0);
            role_exit<0>();
        } else {
            if (warp == 14) {
                if (smem_u32(smem) != SB) __trap();
                if (elect_one()) {
                    asm volatile("prefetch.tensormap [%0];" ::"l"(&tmW.q) : "memory");
                    mbar_init(bar_at(B_W), 1); mbar_init(bar_at(B_W + 1), 1); mbar_init(bar_at(B_W + 2), 1);
                    asm volatile("fence.mbarrier_init.release.cluster;" ::: "memory");
                    fence_async();
                    mbar_expect_tx(bar_at(B_W), 61440 + 15360 + 6400); mbar_expect_tx(bar_at(B_W + 1), 61440); mbar_expect_tx(bar_at(B_W + 2), 40960);
                    bulk_load(ST_X, p.x, 5120, bar_at(B_W));
                    bulk_load(ST_X + 5120, p.wr, 1280, bar_at(B_W));
                }
                reload_role(p, &tmK, &tmV, &tmW, t0);
            } else {
                unsigned ticket = 0;
                if (warp == 15 && lane == 0) asm volatile("atom.relaxed.gpu.global.add.u32 %0, [%1], 1;" : "=r"(ticket) : "l"(&g_epoch) : "memory");
                if (warp == 13 && elect_one()) {
                    asm volatile("prefetch.tensormap [%0];" ::"l"(&tmW.g) : "memory");
                    asm volatile("prefetch.tensormap [%0];" ::"l"(&tmW.u) : "memory");
                    asm volatile("prefetch.tensormap [%0];" ::"l"(&tmW.o) : "memory");
                    asm volatile("prefetch.tensormap [%0];" ::"l"(&tmK) : "memory");
                    asm volatile("prefetch.tensormap [%0];" ::"l"(&tmV) : "memory");
                }
                bar_sync<5, 480>();
                if (warp == 13) { bar_arrive<6, 64>(); q_role(p, lane); }
                else { bar_arrive<2, 256 + 32>(); zero_role(p, lane, ticket, t0); }
            }
            role_exit<1>();
        }
    }
}

typedef CUresult (*EncodeFn)(CUtensorMap*, CUtensorMapDataType, cuuint32_t, void*, const cuuint64_t*, const cuuint64_t*,
                             const cuuint32_t*, const cuuint32_t*, CUtensorMapInterleave, CUtensorMapSwizzle,
                             CUtensorMapL2promotion, CUtensorMapFloatOOBfill);

bool make_map(EncodeFn fn, CUtensorMap* m, const void* ptr, uint64_t cols, uint64_t rows, uint32_t bc, uint32_t br) {
    cuuint64_t dims[2] = {cols, rows};
    cuuint64_t strides[1] = {cols * 2};
    cuuint32_t box[2] = {bc, br};
    cuuint32_t es[2] = {1, 1};
    return fn(m, CU_TENSOR_MAP_DATA_TYPE_BFLOAT16, 2, const_cast<void*>(ptr), dims, strides, box, es, CU_TENSOR_MAP_INTERLEAVE_NONE,
              CU_TENSOR_MAP_SWIZZLE_NONE, CU_TENSOR_MAP_L2_PROMOTION_L2_128B, CU_TENSOR_MAP_FLOAT_OOB_FILL_NONE) == CUDA_SUCCESS;
}

bool make_kv_map(EncodeFn fn, CUtensorMap* m, const void* ptr) {
    cuuint64_t dims[4] = {64, 8, 3, (cuuint64_t)NB * NHEAD * SK / 8};
    cuuint64_t strides[3] = {DH * 2, 128, 8 * DH * 2};
    cuuint32_t box[4] = {64, 8, 3, 4};
    cuuint32_t es[4] = {1, 1, 1, 1};
    return fn(m, CU_TENSOR_MAP_DATA_TYPE_BFLOAT16, 4, const_cast<void*>(ptr), dims, strides, box, es, CU_TENSOR_MAP_INTERLEAVE_NONE,
              CU_TENSOR_MAP_SWIZZLE_128B, CU_TENSOR_MAP_L2_PROMOTION_L2_128B, CU_TENSOR_MAP_FLOAT_OOB_FILL_NONE) == CUDA_SUCCESS;
}

}

extern "C" void kernel_launch(void* const* d_in, const int* in_sizes, int n_in, void* d_out, int out_size) {
    (void)in_sizes; (void)n_in; (void)out_size;
    static EncodeFn fn = nullptr;
    static const char* scr = nullptr;
    if (!fn) {
        void* f = nullptr;
        cudaDriverEntryPointQueryResult qr;
        if (cudaGetDriverEntryPoint("cuTensorMapEncodeTiled", &f, cudaEnableDefault, &qr) != cudaSuccess || !f) return;
        void* sp = nullptr;
        if (cudaGetSymbolAddress(&sp, g_scratch) != cudaSuccess) return;
        scr = (const char*)(((uintptr_t)sp + (2 << 20) - 1) & ~(uintptr_t)((2 << 20) - 1));
        fn = (EncodeFn)f;
        cudaFuncSetAttribute(decode_kernel, cudaFuncAttributeMaxDynamicSharedMemorySize, SMEM_BYTES);
    }
    CUtensorMap tmK, tmV;
    WeightMaps tmW;
    if (!make_kv_map(fn, &tmK, d_in[1]) || !make_kv_map(fn, &tmV, d_in[2])) return;
    if (!make_map(fn, &tmW.q, d_in[3], NHEAD * DH, DM, 48, 128) || !make_map(fn, &tmW.o, d_in[4], DM, NHEAD * DH, 160, 32)) return;
    if (!make_map(fn, &tmW.g, d_in[7], FF, DM, 16, 128) || !make_map(fn, &tmW.u, d_in[8], FF, DM, 16, 128)) return;
    Params p;
    p.x = (const unsigned short*)d_in[0];
    p.kc = (const char*)d_in[1];
    p.vc = (const char*)d_in[2];
    p.wq = (const char*)d_in[3];
    p.wo = (const char*)d_in[4];
    p.wr = (const unsigned short*)d_in[6];
    p.wg = (const char*)d_in[7];
    p.wu = (const char*)d_in[8];
    p.wd = (const char*)d_in[9];
    p.out = (unsigned short*)d_out;
    p.scr = scr;
    decode_kernel<<<NCTA, NTHREADS, SMEM_BYTES>>>(p, tmK, tmV, tmW);
}
```

```cpp
#include <cuda_runtime.h>
#include <cuda_bf16.h>
#include <cuda.h>
#include <stdint.h>

namespace {

constexpr int NB = 4, DM = 640, NHEAD = 32, DH = 192, SK = 4096, WIN = 1024, FF = 1536;
constexpr int NCTA = 128;
constexpr int TILE = 12288, PAIR = 2 * TILE;

#define CFG_LIST(X) \
    X(TICK0, 480)        \
    X(TICK, 506)        \
    X(LEAD, 350)        \
    X(STAG, 560)        \
    X(WLAG, 300)        \
    X(GSTEP, 700)        \
    X(WIN, 4)        \
    X(PMAX, 4)        \
    X(PGRACE, 50)        \
    X(LMAX0, 100)        \
    X(LMAX, 150) \
    X(GAIN, 10)        \
    X(VSTEP, 250)        \
    X(RLAG, 0)        \
    X(RSTEP, 640) \
    X(RSTEP3, 390) \
    X(ZTILE, 11)        \
    X(START, 1)        \
    X(DLY_A, 400)        \
    X(DLY_AL, 100) \
    X(DLY_B, 600) \
    X(DLY_BL, 900) \
    X(DLY_F, 250) \
    X(FLIP, 0) \

#define X(n, v) constexpr int CFG_##n = v;
CFG_LIST(X)
#undef X
#define CFG(n) CFG_##n
constexpr int QUIET = 8;
#define CFG_REG_CHAIN 216
#define CFG_REG_ATT 48
#define CFG_REG_HELP 32
constexpr int KB_KV0 = 165;
__device__ __forceinline__ int kb_ns(int kb) { return kb * CFG(TICK0) / 12; }
__device__ __forceinline__ int tick_ns(int j) { return j <= 16 ? CFG(TICK0) : CFG(TICK); }
__device__ __forceinline__ int batch_ns(int k) { return kb_ns(KB_KV0) + (k ? 16 * (CFG(TICK0) + (k - 1) * CFG(TICK)) : 0); }

__device__ __forceinline__ uint32_t slots(int k) { return k & 2 ? (k & 1 ? 0x21304768u : 0x76835214u) : (k & 1 ? 0x21480765u : 0x76543210u); }
__device__ __forceinline__ int pass_nibble(int k, int u) { return k > 0 ? 4 + (u & 1) : u; }
__device__ __forceinline__ uint32_t slot_at(uint32_t tab, int u) { return (tab >> (4 * u)) & 15; }

constexpr int NROUND = 11;
constexpr uint32_t ORD_BATCH = 0x3b9910, ORD_LAST = 0x6da, ORD_NO_HEAD = 0x248, ORD_NO_TAIL = 0x092;

constexpr uint32_t SB = 1024;
constexpr uint32_t SM_BAR = SB + 9 * PAIR;
constexpr int B_F1 = 0;
constexpr int B_RR = 24;
constexpr int B_RK = 32;
constexpr int B_RV = 36;
constexpr int B_Z = 37;
constexpr int B_EP = 38;
constexpr int B_W = 39;
constexpr int B_WC = 42;
constexpr int B_FIN = 45;
constexpr int B_F3 = 46;
constexpr int B_PS = 48;
constexpr int B_RP = 49;
constexpr int B_FL = 50;
constexpr int B_QR = 51;
constexpr int NBAR = 52;
__host__ __device__ constexpr uint32_t bar_at(int i) { return SM_BAR + 8 * i; }
constexpr uint32_t SM_EPOCH = SM_BAR + 416;
constexpr uint32_t SM_MAX = SM_EPOCH + 16;
constexpr uint32_t SM_SUM = SM_MAX + 16;
constexpr uint32_t SM_NEAR = SM_SUM + 32;
constexpr uint32_t SM_FIN = SM_NEAR + 32;
constexpr uint32_t SM_Q = SM_FIN + 32;
constexpr uint32_t PSTR = 144;
constexpr uint32_t SM_P = SM_Q + 5 * 384;
constexpr uint32_t SM_X = SM_P + 8 * PSTR;
constexpr uint32_t SM_CSG = SM_X + 40;
constexpr uint32_t SM_ONES = SM_X + 8 * 384;
constexpr uint32_t SM_PG = SM_ONES + 48;
constexpr uint32_t SM_PO = SM_PG + 1024;
constexpr uint32_t SM_PQ = SM_PO;
constexpr int SMEM_BYTES = SM_PO + 3072 - SB;
static_assert(SMEM_BYTES <= 232448 && SM_Q % 16 == 0 && SM_P % 16 == 0 && SM_X % 16 == 0 && SM_PO % 16 == 0, "smem");
constexpr uint32_t ST_WQ = SB, ST_WD = SB + 3 * PAIR, ST_WO = SB + 4 * PAIR, ST_WG = SB + 7 * PAIR, ST_X = ST_WG + 40960;

__device__ unsigned g_epoch;
__device__ unsigned char g_scratch[4 << 20];
constexpr uint32_t HALF = 4096, SCR_O = 1 << 16, SCR_Q = 1 << 17, SCR_PROBE = 1 << 19, SCR_COUNT = 3 << 16;
__device__ __forceinline__ uint32_t acc_off(int k, int layer, int w) { return (k & 1) << 18 | (k >> 1) << 20 | (w >> 1) << 14 | (w & 1) << 11 | layer << 7; }
__device__ __forceinline__ uint32_t head_off(int h) { return (h & 3) << 14 | (h & 4) << 16 | (h & 8) << 17 | (h & 16) << 9; }
__device__ __forceinline__ uint32_t head_near(int h, uint32_t near) { return near ^ HALF ^ (h & 16) << 8; }
constexpr uint32_t FULL_A = 0x42040000u;

struct Params {
    const char* wq;
    const unsigned short* x;
    const char* wo;
    const unsigned short* wr;
    const char* wg;
    const char* wu;
    const char* wd;
    unsigned short* out;
    const char* scr;
};

__device__ __forceinline__ uint32_t smem_u32(const void* p) { return (uint32_t)__cvta_generic_to_shared(p); }
__device__ __forceinline__ void mbar_init(uint32_t a, uint32_t c) { asm volatile("mbarrier.init.shared::cta.b64 [%0], %1;" ::"r"(a), "r"(c) : "memory"); }
__device__ __forceinline__ void mbar_expect_tx(uint32_t a, uint32_t b) {
    asm volatile("mbarrier.arrive.expect_tx.shared::cta.b64 _, [%0], %1;" ::"r"(a), "r"(b) : "memory");
}
__device__ __forceinline__ void mbar_arrive(uint32_t a) { asm volatile("mbarrier.arrive.shared::cta.b64 _, [%0];" ::"r"(a) : "memory"); }
constexpr uint32_t SPIN_LIMIT = 1u << 22;
#define SPIN_DECL uint32_t spins = 0
#define SPIN_CHECK(info) { if (++spins > SPIN_LIMIT) __trap(); }
__device__ __forceinline__ void mbar_wait(uint32_t a, uint32_t parity) {
    uint32_t ok;
    SPIN_DECL;
    while (true) {
        asm volatile("{\n.reg .pred p;\nmbarrier.try_wait.parity.shared::cta.b64 p, [%1], %2;\nselp.u32 %0, 1, 0, p;\n}"
                     : "=r"(ok) : "r"(a), "r"(parity) : "memory");
        if (ok) break;
        SPIN_CHECK((a - SM_BAR) / 8 * 10 + parity);
    }
}
__device__ __forceinline__ bool mbar_test2(uint32_t a, uint32_t pa, uint32_t b, uint32_t pb) {
    uint32_t ok;
    asm volatile("{\n.reg .pred p, q;\nmbarrier.test_wait.parity.shared::cta.b64 p, [%1], %2;\n"
                 "mbarrier.test_wait.parity.shared::cta.b64 q, [%3], %4;\nand.pred p, p, q;\nvote.sync.all.pred p, p, 0xffffffff;\nselp.u32 %0, 1, 0, p;\n}"
                 : "=r"(ok) : "r"(a), "r"(pa), "r"(b), "r"(pb) : "memory");
    return ok;
}
__device__ __forceinline__ uint32_t now_ns() { uint32_t t; asm volatile("mov.u32 %0, %%globaltimer_lo;" : "=r"(t) :: "memory"); return t; }
__device__ __forceinline__ uint32_t clk32() { uint32_t c; asm volatile("mov.u32 %0, %%clock;" : "=r"(c) :: "memory"); return c; }
__device__ __forceinline__ void wait_ns(uint32_t t) { while ((int)(now_ns() - t) < 0) {} }
__device__ __forceinline__ void wait_clk(uint32_t t) { while ((int)(clk32() - t) < 0) {} }
__device__ __forceinline__ bool elect_one() {
    uint32_t e;
    asm volatile("{\n.reg .pred p;\nelect.sync _|p, 0xffffffff;\nselp.u32 %0, 1, 0, p;\n}" : "=r"(e));
    return e;
}
constexpr uint64_t POL_FIRST = 0x12F0000000000000ull, POL_NORMAL = 0x1000000000000000ull;
__device__ __forceinline__ void tma_tile(uint32_t dst, const CUtensorMap* tm, int group, uint32_t bar, uint64_t pol) {
    asm volatile("cp.async.bulk.tensor.4d.shared::cluster.global.mbarrier::complete_tx::bytes.L2::cache_hint"
                 " [%0], [%1, {%3, %3, %3, %4}], [%2], %5;"
                 ::"r"(dst), "l"(tm), "r"(bar), "r"(0), "r"(group), "l"(pol) : "memory");
}
__device__ __forceinline__ void tma2d(uint32_t dst, const CUtensorMap* tm, int x, int y, uint32_t bar) {
    asm volatile("cp.async.bulk.tensor.2d.shared::cluster.global.mbarrier::complete_tx::bytes [%0], [%1, {%3, %4}], [%2];"
                 ::"r"(dst), "l"(tm), "r"(bar), "r"(x), "r"(y) : "memory");
}
__device__ __forceinline__ void bulk_load(uint32_t dst, const void* src, uint32_t bytes, uint32_t bar) {
    asm volatile("cp.async.bulk.shared::cluster.global.mbarrier::complete_tx::bytes [%0], [%1], %2, [%3];"
                 ::"r"(dst), "l"(src), "r"(bytes), "r"(bar) : "memory");
}
__device__ __forceinline__ void l2_prefetch(const void* p, uint32_t bytes) {
    asm volatile("cp.async.bulk.prefetch.L2.global [%0], %1;" ::"l"(p), "r"(bytes) : "memory");
}
__device__ __forceinline__ void mma16816(float (&c)[4], uint32_t a0, uint32_t a1, uint32_t a2, uint32_t a3, uint32_t b0, uint32_t b1) {
    asm volatile("mma.sync.aligned.m16n8k16.row.col.f32.bf16.bf16.f32 {%0,%1,%2,%3}, {%4,%5,%6,%7}, {%8,%9}, {%0,%1,%2,%3};"
                 : "+f"(c[0]), "+f"(c[1]), "+f"(c[2]), "+f"(c[3]) : "r"(a0), "r"(a1), "r"(a2), "r"(a3), "r"(b0), "r"(b1));
}
__device__ __forceinline__ void mma1688(float (&c)[4], uint32_t a0, uint32_t a1, uint32_t b0) {
    asm volatile("mma.sync.aligned.m16n8k8.row.col.f32.bf16.bf16.f32 {%0,%1,%2,%3}, {%4,%5}, {%6}, {%0,%1,%2,%3};"
                 : "+f"(c[0]), "+f"(c[1]), "+f"(c[2]), "+f"(c[3]) : "r"(a0), "r"(a1), "r"(b0));
}
__device__ __forceinline__ void ldsm4t(uint32_t (&r)[4], uint32_t a, uint32_t& zero) {
    asm volatile("ldmatrix.sync.aligned.m8n8.x4.trans.shared.b16 {%0,%1,%2,%3}, [%4];"
                 : "=r"(r[0]), "=r"(r[1]), "=r"(r[2]), "=r"(r[3]) : "r"(a + zero) : "memory");
    zero &= r[3];
}
__device__ __forceinline__ uint4 ld_pkt(const void* p) {
    uint4 v;
    asm volatile("{\n.reg .b128 t;\nld.relaxed.gpu.global.b128 t, [%4];\nmov.b128 {%0,%1,%2,%3}, t;\n}"
                 : "=r"(v.x), "=r"(v.y), "=r"(v.z), "=r"(v.w) : "l"(p) : "memory");
    return v;
}
__device__ __forceinline__ void st_pkt(const void* p, uint32_t a, uint32_t b, uint32_t c, uint32_t d) {
    asm volatile("{\n.reg .b128 t;\nmov.b128 t, {%1,%2,%3,%4};\nst.relaxed.gpu.global.b128 [%0], t;\n}"
                 ::"l"(p), "r"(a), "r"(b), "r"(c), "r"(d) : "memory");
}
__device__ __forceinline__ uint2 ld_pkt8(const void* p) {
    uint2 v;
    asm volatile("{\n.reg .b64 t;\nld.relaxed.gpu.global.b64 t, [%2];\nmov.b64 {%0,%1}, t;\n}" : "=r"(v.x), "=r"(v.y) : "l"(p) : "memory");
    return v;
}
__device__ __forceinline__ void red_cell(const char* p, float a, float b, float c) {
    asm volatile("red.relaxed.gpu.global.add.v4.f32 [%0], {%1,%2,%3,%4};" ::"l"(p), "f"(a), "f"(b), "f"(c), "f"(1.0f) : "memory");
}
#define PRED(n) "{\n.reg .pred p;\nsetp.ne.u32 p, %" #n ", 0;\n"
__device__ __forceinline__ void red_cell2_if(bool on, const char* p, float a, float b, float c) {
    asm volatile(PRED(5) "@p red.relaxed.gpu.global.add.v4.f32 [%0], {%1,%2,%3,%4};\n@p red.relaxed.gpu.global.add.v4.f32 [%0+4096], {%1,%2,%3,%4};\n}"
                 ::"l"(p), "f"(a), "f"(b), "f"(c), "f"(1.0f), "r"((uint32_t)on) : "memory");
}
__device__ __forceinline__ void st_pkt82_if(bool on, const void* p, uint32_t a, uint32_t b) {
    asm volatile(PRED(3) ".reg .b64 t;\nmov.b64 t, {%1,%2};\n@p st.relaxed.gpu.global.b64 [%0], t;\n@p st.relaxed.gpu.global.b64 [%0+4096], t;\n}"
                 ::"l"(p), "r"(a), "r"(b), "r"((uint32_t)on) : "memory");
}
__device__ __forceinline__ void st_pkt2_if(bool on, const void* p, uint32_t a, uint32_t b, uint32_t c, uint32_t d) {
    asm volatile(PRED(5) ".reg .b128 t;\nmov.b128 t, {%1,%2,%3,%4};\n@p st.relaxed.gpu.global.b128 [%0], t;\n@p st.relaxed.gpu.global.b128 [%0+4096], t;\n}"
                 ::"l"(p), "r"(a), "r"(b), "r"(c), "r"(d), "r"((uint32_t)on) : "memory");
}
__device__ __forceinline__ void mbar_arrive_if(bool on, uint32_t a) {
    asm volatile(PRED(1) "@p mbarrier.arrive.shared::cta.b64 _, [%0];\n}" ::"r"(a), "r"((uint32_t)on) : "memory");
}
__device__ __forceinline__ void sts16_if(bool on, uint32_t a, uint32_t v) {
    asm volatile(PRED(2) "@p st.shared.u16 [%0], %1;\n}" ::"r"(a), "h"((unsigned short)v), "r"((uint32_t)on) : "memory");
}
__device__ __forceinline__ void sts32_if(bool on, uint32_t a, uint32_t v) {
    asm volatile(PRED(2) "@p st.shared.u32 [%0], %1;\n}" ::"r"(a), "r"(v), "r"((uint32_t)on) : "memory");
}
__device__ __forceinline__ void sts128_if(bool on, uint32_t a, uint32_t x, uint32_t y, uint32_t z, uint32_t w) {
    asm volatile(PRED(5) "@p st.shared.v4.u32 [%0], {%1,%2,%3,%4};\n}" ::"r"(a), "r"(x), "r"(y), "r"(z), "r"(w), "r"((uint32_t)on) : "memory");
}
__device__ __forceinline__ float fast_rcp(float x) { float r; asm("rcp.approx.ftz.f32 %0, %1;" : "=f"(r) : "f"(x)); return r; }
__device__ __forceinline__ float fast_sqrt(float x) { float r; asm("sqrt.approx.ftz.f32 %0, %1;" : "=f"(r) : "f"(x)); return r; }
__device__ __forceinline__ float fast_ex2(float x) { float r; asm("ex2.approx.ftz.f32 %0, %1;" : "=f"(r) : "f"(x)); return r; }
__device__ __forceinline__ uint32_t pack2(float lo, float hi) {
    uint32_t r;
    asm("cvt.rn.bf16x2.f32 %0, %1, %2;" : "=r"(r) : "f"(hi), "f"(lo));
    return r;
}
__device__ __forceinline__ float bfr(float x) { return __uint_as_float(pack2(0.f, x)); }
__device__ __forceinline__ uint32_t badd2(uint32_t a, uint32_t b) { uint32_t r; asm("add.rn.bf16x2 %0, %1, %2;" : "=r"(r) : "r"(a), "r"(b)); return r; }
__device__ __forceinline__ uint32_t bsub2(uint32_t a, uint32_t b) { uint32_t r; asm("sub.rn.bf16x2 %0, %1, %2;" : "=r"(r) : "r"(a), "r"(b)); return r; }
__device__ __forceinline__ uint32_t bmul2(uint32_t a, uint32_t b) { uint32_t r; asm("mul.rn.bf16x2 %0, %1, %2;" : "=r"(r) : "r"(a), "r"(b)); return r; }
__device__ __forceinline__ float bf_lo(uint32_t w) { return __uint_as_float(w << 16); }
__device__ __forceinline__ float bf_hi(uint32_t w) { return __uint_as_float(w & 0xffff0000u); }
__device__ __forceinline__ float F(uint32_t t) { return __uint_as_float(t); }
__device__ __forceinline__ uint32_t lds16(uint32_t a) { unsigned short h; asm volatile("ld.shared.u16 %0, [%1];" : "=h"(h) : "r"(a) : "memory"); return h; }
__device__ __forceinline__ uint32_t lds32(uint32_t a) { uint32_t v; asm volatile("ld.shared.u32 %0, [%1];" : "=r"(v) : "r"(a) : "memory"); return v; }
__device__ __forceinline__ uint2 lds64(uint32_t a) {
    uint2 v; asm volatile("ld.shared.v2.u32 {%0,%1}, [%2];" : "=r"(v.x), "=r"(v.y) : "r"(a) : "memory"); return v;
}
__device__ __forceinline__ uint4 lds128(uint32_t a) {
    uint4 v; asm volatile("ld.shared.v4.u32 {%0,%1,%2,%3}, [%4];" : "=r"(v.x), "=r"(v.y), "=r"(v.z), "=r"(v.w) : "r"(a) : "memory"); return v;
}
__device__ __forceinline__ float sum8(const uint4& u, const uint4& v) {
    return ((F(u.x) + F(u.y)) + (F(u.z) + F(u.w))) + ((F(v.x) + F(v.y)) + (F(v.z) + F(v.w)));
}
__device__ __forceinline__ void sts16(uint32_t a, uint32_t v) { asm volatile("st.shared.u16 [%0], %1;" ::"r"(a), "h"((unsigned short)v) : "memory"); }
__device__ __forceinline__ void sts32(uint32_t a, uint32_t v) { asm volatile("st.shared.u32 [%0], %1;" ::"r"(a), "r"(v) : "memory"); }
__device__ __forceinline__ void stsf(uint32_t a, float v) { asm volatile("st.shared.f32 [%0], %1;" ::"r"(a), "f"(v) : "memory"); }
__device__ __forceinline__ void stsf2(uint32_t a, float x, float y) { asm volatile("st.shared.v2.f32 [%0], {%1,%2};" ::"r"(a), "f"(x), "f"(y) : "memory"); }
__device__ __forceinline__ void stsf4(uint32_t a, float x, float y, float z, float w) {
    asm volatile("st.shared.v4.f32 [%0], {%1,%2,%3,%4};" ::"r"(a), "f"(x), "f"(y), "f"(z), "f"(w) : "memory");
}
template <int ID, int N> __device__ __forceinline__ void bar_sync() { asm volatile("bar.sync %0, %1;" ::"n"(ID), "n"(N) : "memory"); }
template <int ID, int N> __device__ __forceinline__ void bar_arrive() { asm volatile("bar.arrive %0, %1;" ::"n"(ID), "n"(N) : "memory"); }
__device__ __forceinline__ void fence_async() { asm volatile("fence.proxy.async.shared::cta;" ::: "memory"); }
__device__ __forceinline__ float shx(float v, int m) { return __shfl_xor_sync(0xffffffffu, v, m); }
__device__ __forceinline__ float shi(float v, int l) { return __shfl_sync(0xffffffffu, v, l); }
__device__ __forceinline__ uint32_t shi(uint32_t v, int l) { return __shfl_sync(0xffffffffu, v, l); }
__device__ __forceinline__ uint32_t opaque(uint32_t x) { asm volatile("mov.u32 %0, %0;" : "+r"(x)); return x; }
__device__ __forceinline__ const char* opaque(const char* x) { asm volatile("mov.u64 %0, %0;" : "+l"(x)); return x; }
constexpr float LOG2E = 1.4426950408889634f;

#define TRACE(idx) do {} while (0)
#define TRACES(slot) do {} while (0)

__device__ __forceinline__ uint32_t probe_near(const Params& p, int w, int lane) {
    const int cta = blockIdx.x;
    const char* pr = p.scr + SCR_PROBE + (cta & 31) * 128 + (cta >> 5) * 16384 + ((w & 1) << 6 | (w & 2) << 17 | (w & 4) << 18);
    st_pkt2_if(lane < 2, pr + lane * 16, 0, 0, 0, 0);
    uint32_t best0 = ~0u, best1 = ~0u;
#pragma unroll 1
    for (int i = w & 1; i < 6 + (w & 1); i++) {
        uint32_t c = clk32(), v = 0;
        if (lane == 0) asm volatile("atom.relaxed.gpu.global.add.u32 %0, [%1], 1;" : "=r"(v) : "l"(pr + (i & 1) * HALF) : "memory");
        c += __shfl_sync(0xffffffffu, v, 0) >> 16;
        c = clk32() - c;
        if (i & 1) best1 = min(best1, c); else best0 = min(best0, c);
    }
    return min(best0, 0xffffu) | min(best1, 0xffffu) << 16;
}
__device__ __forceinline__ uint32_t near_half() {
    const uint4 a = lds128(SM_NEAR), b = lds128(SM_NEAR + 16);
    const uint32_t m = __vminu2(__vminu2(__vminu2(a.x, a.y), __vminu2(a.z, a.w)), __vminu2(__vminu2(b.x, b.y), __vminu2(b.z, b.w)));
    return ((m & 0xffffu) < m >> 16) != (CFG(FLIP) != 0) ? HALF : 0;
}

__device__ __forceinline__ int kv_group(int k, int t) {
    const int cta = blockIdx.x;
    return ((k * NHEAD + (cta >> 2)) * SK + (SK - WIN) + (cta & 3) * 256 + t * 32) / 8;
}
__device__ __forceinline__ uint32_t phase_ns() { return (((blockIdx.x >> 2) * 13) & 31) * CFG(STAG) / 32; }

__device__ __forceinline__ void ln_fast(float s, float q, float& mean, float& rstd) {
    mean = s * (1.f / DM);
    asm("rsqrt.approx.ftz.f32 %0, %1;" : "=f"(rstd) : "f"(fmaxf(fmaf(-mean, mean, fmaf(q, 1.f / DM, 1e-5f)), 1e-5f)));
}
__device__ __forceinline__ void q_role(const Params& p, int lane) {
    const int cta = blockIdx.x;
    mbar_wait(bar_at(B_EP), 0);
    const uint32_t tag0 = lds32(SM_EPOCH) * NB;
    const char* const qbox = p.scr + SCR_Q + head_off(cta >> 2) + lane * 8;
    const uint32_t near = head_near(cta >> 2, near_half());
    float cs0 = 0.f, cs1 = 0.f;
#pragma unroll 1
    for (int r = 0; r <= 2 * NB; r++) {
        const int slot = min(r, NB), k = r - NB;
        const uint32_t tag = tag0 + (r < NB ? r : k - 1);
        const char* const dst = qbox + slot * 768 + (cta & 3) * 192;
        const char* const src = qbox + slot * 768 + near;
        bar_sync<3, 288>();
        const uint32_t ra = SM_PQ + lane * 16;
        float S0 = sum8(lds128(ra), lds128(ra + 1024)), S1 = sum8(lds128(ra + 512), lds128(ra + 1536));
        if (k > 0) {
            float mean, rstd;
            ln_fast(shi(S1, 24), shi(S0, 24), mean, rstd);
            S0 = fmaf(-mean, cs0, S0) * rstd;
            S1 = fmaf(-mean, cs1, S1) * rstd;
        } else {
            bar_arrive<7, 288>();
            if (k == 0) { cs0 = S0; cs1 = S1; continue; }
        }
        st_pkt82_if(lane < 24, dst, pack2(S0, S1), tag);
        TRACES(k > 0 ? (k - 1) * 12 + 5 : 95);
        if (r < NB - 1) continue;
#pragma unroll 1
        for (int back = k < 0 ? NB - 1 : 0; back >= 0; back--) {
            const char* const from = src - back * 768;
            const uint32_t want = tag - back, qd = SM_Q + (slot - back) * 384 + lane * 4;
            uint2 a, b, c;
            SPIN_DECL;
            do {
                a = ld_pkt8(from); b = ld_pkt8(from + 256); c = ld_pkt8(from + 512);
                SPIN_CHECK(slot);
                sts32(qd, a.x); sts32(qd + 128, b.x); sts32(qd + 256, c.x);
            } while (__any_sync(0xffffffffu, a.y != want || b.y != want || c.y != want));
        }
        mbar_arrive(bar_at(B_QR));
    }
}

struct Maps { CUtensorMap k, v, q, o, g, u; };
__device__ __forceinline__ void load_role(const Params& p, const CUtensorMap* tmKV, int lane, uint32_t t0) {
    const int cta = blockIdx.x;
    t0 += phase_ns();
#pragma unroll 1
    for (int i = 1; i < 5; i++) {
        wait_ns(t0 + i * CFG(TICK0));
        if (elect_one()) l2_prefetch(p.wq + (size_t)(128 * i + cta) * 12288, 12288);
    }
    uint32_t plan[2];
#pragma unroll
    for (int i = 0; i < 2; i++) {
        const int j = lane + 32 * i, k = j >> 4, t = j & 15, u = t >> 1, jw = j - CFG(WIN);
        const int sb = k == 0 ? B_WC + (t >= 8) + (t >= 14) : t >= 12 ? B_RK + u - 5 : t >= 4 ? B_RR + t - 4 : t >= 2 ? B_RP : k > 1 ? B_RK + 3 : B_RR + t;
        const uint32_t sw = sb * 8 | (j < 18 ? 0 : (t >= 12 || u == 1 ? k - 1 : k) & 1) << 9;
        plan[i] = sw | (jw < 0 ? sw : (B_F1 + (jw & 15)) * 8 | ((jw >> 4) & 1) << 9) << 10 |
                  (slot_at(slots(k), t < 8 ? pass_nibble(k, u) : u) * 2 + (t & 1)) << 20 | (t < 10 && j >= 8 && j < 56) << 25;
    }
    bar_sync<6, 64>();
    wait_ns(t0 + kb_ns(60));
    if (elect_one()) bulk_load(ST_WD, p.wd + cta * 15360, 15360, bar_at(B_W));
#pragma unroll 1
    for (int i = 0; i < 5; i++) {
        wait_ns(t0 + kb_ns(75) + i * kb_ns(6));
        if (elect_one()) { l2_prefetch(p.wg + (128 * i + cta) * 3072, 3072); l2_prefetch(p.wu + (128 * i + cta) * 3072, 3072); }
    }
#pragma unroll 1
    for (int i = 0; i < 6; i++) {
        wait_ns(t0 + kb_ns(105) + min(i, 4) * kb_ns(10));
        if (elect_one()) l2_prefetch(p.wo + (size_t)((cta >> 2) * DH + 32 * i + 8 * (cta & 3)) * 1280, 10240);
    }
    t0 += batch_ns(0);
    int jp = 0, shift = 0;
    uint32_t earliest = t0;
    auto requested = [&](uint32_t now) {
        shift = max(max(shift - CFG(GAIN), 0), (int)(now - t0) - (jp < 12 ? CFG(LMAX0) : CFG(LMAX)));
        TRACE(128 + jp);
        t0 += tick_ns(++jp);
    };
    const int grp0 = kv_group(0, 0);
    auto group = [&](int j) { return grp0 + (j >> 4) * (NHEAD * SK / 8) + (j & 7) * 4; };
#pragma unroll 1
    for (int j = 0; j < 16 * NB; j++) {
        const uint32_t pl = __shfl_sync(0xffffffffu, j & 32 ? plan[1] : plan[0], j);
        const int jmax = min(j + CFG(PMAX), 16 * NB);
        uint32_t now;
        SPIN_DECL;
        while (true) {
            const bool ok = mbar_test2(SM_BAR + (pl & 511), (pl >> 9) & 1, SM_BAR + ((pl >> 10) & 511), (pl >> 19) & 1);
            now = now_ns();
            const int late = now - t0 - shift;
            if (ok && (jp > j ? (int)(now - earliest) : late) >= 0) break;
            if (late >= (jp > j ? 0 : CFG(PGRACE)) && jp < jmax) {
                if (elect_one())
                    asm volatile("cp.async.bulk.prefetch.tensor.4d.L2.global [%0, {%1, %1, %1, %2}];" ::"l"(tmKV + ((jp >> 3) & 1)), "r"(0), "r"(group(jp)) : "memory");
                requested(now);
            }
            SPIN_CHECK(j);
        }
        if (elect_one()) {
            mbar_expect_tx(bar_at(B_F1 + (j & 15)), TILE);
            tma_tile(SB + ((pl >> 20) & 31) * TILE, tmKV + ((j >> 3) & 1), group(j), bar_at(B_F1 + (j & 15)), pl >> 25 ? POL_NORMAL : POL_FIRST);
        }
        TRACE(256 + j);
        earliest = now + CFG(VSTEP);
        if (jp == j) requested(now);
    }
}

__device__ __forceinline__ void reload_role(const Params& p, const Maps* tm, uint32_t t0) {
    const CUtensorMap* const tmK = &tm->k;
    const CUtensorMap* const tmV = &tm->v;
    const int cta = blockIdx.x;
    t0 += CFG(TICK0) + CFG(WLAG) + phase_ns();
#pragma unroll 1
    for (int i = 0; i < 5; i++) {
        wait_ns(t0 + i * CFG(TICK0));
        if (elect_one()) tma2d(ST_WQ + i * 12288, &tm->q, 48 * cta, 128 * i, bar_at(B_W));
        if (i == 1) bar_sync<5, 480>();
    }
#pragma unroll 1
    for (int i = 0, o = 0; i < 10;) {
        const uint32_t now = now_ns() - t0;
        if (o < 6 && (int)now >= kb_ns(105) + o * kb_ns(10)) {
            if (elect_one()) tma2d(ST_WO + o * 10240, &tm->o, 160 * (cta & 3), (cta >> 2) * DH + 32 * o, bar_at(B_W + 1));
            o++;
        } else if ((int)now >= kb_ns(77) + i * CFG(GSTEP) && (i < 9 || o == 6)) {
            if (elect_one()) tma2d(ST_WG + (i & 1) * 20480 + (i >> 1) * 4096, i & 1 ? &tm->u : &tm->g, (12 * cta) & ~7, 128 * (i >> 1), bar_at(B_W + 2));
            i++;
        }
    }
#pragma unroll 1
    for (int k = 0; k < NB - 1; k++) {
        mbar_wait(bar_at(B_RK), k & 1);
        if (elect_one()) {
            const uint32_t dst = SB + slot_at(slots(k), 0) * PAIR;
            mbar_expect_tx(bar_at(B_FL), PAIR);
            tma_tile(dst, tmV, kv_group(k, 0), bar_at(B_FL), POL_FIRST);
            tma_tile(dst + TILE, tmV, kv_group(k, 1), bar_at(B_FL), POL_FIRST);
        }
        mbar_wait(bar_at(B_RV), k & 1);
        uint32_t due = now_ns() + (k == NB - 2 ? 0 : CFG(RLAG));
        if (elect_one()) mbar_expect_tx(bar_at(B_F3), 4 * PAIR);
#pragma unroll 1
        for (int t = 0; t < 8; t++) {
            wait_ns(due);
            due += k == NB - 2 ? CFG(RSTEP3) : CFG(RSTEP);
            if (elect_one())
                tma_tile(SB + slot_at(slots(k + 1), t >> 1) * PAIR + (t & 1) * TILE, tmK, kv_group(k + 1, t), bar_at(B_F3), POL_FIRST);
        }
        TRACE(121 + k);
    }
}

__device__ __forceinline__ void zero_role(const Params& p, int lane, unsigned ticket, uint32_t t0) {
    const int cta = blockIdx.x;
    const uint32_t epoch = __shfl_sync(0xffffffffu, ticket, 0) / NCTA + 1;
    if (lane == 0) { sts32(SM_EPOCH, epoch); mbar_arrive(bar_at(B_EP)); }
    mbar_wait(bar_at(B_EP), 0);
#pragma unroll 1
    for (int k = 0; k < NB + 2; k++) {
        lane = opaque(lane);
        const int cl = 2 * (cta & 15) + (lane & 1);
        const int col = 80 * (cta >> 4) + (cl & 2 ? 48 : 0) + (cl >> 2) + (cl & 1 ? 8 : 0);
        const char* own = p.scr + (cl >> 2) * 256 + (cl & 3) * 16;
        if (k < NB) {
            const int lg = lane >> 3, ty = (lane & 7) >> 1;
            const char* dst = own + acc_off((k - (lg >> 1)) & 3, lg != 0, cta >> 4) + ty * HALF;
            uint32_t v0 = 0, v1 = 0, v2 = 0;
            if (lane < 4) {
                const unsigned short* xp = p.x + k * DM + col;
                v0 = __ldg(xp) << 16; v1 = __ldg(xp + 16) << 16; v2 = cl & 2 ? 0 : __ldg(xp + 32) << 16;
            }
            wait_ns(t0 + batch_ns(k) + CFG(ZTILE) * CFG(TICK0));
            if (lg == 0 || (lg == 1 && (ty < 2 || k == NB - 1)) || (lg == 2 && k > 0 && ty > 1)) {
                st_pkt(dst, v0, v1, v2, 0);
                asm volatile("atom.relaxed.gpu.global.add.f32 %0, [%1+12], %2;" : "=r"(v0) : "l"(dst), "f"(lane < 4 ? 1.f : 0.f) : "memory");
            }
            if (__any_sync(0xffffffffu, v0 != 0)) __trap();
            const char* cnt = p.scr + SCR_COUNT;
            if (lane < 2) asm volatile("red.relaxed.gpu.global.add.u32 [%0], 1;" ::"l"(cnt + lane * HALF) : "memory");
            const uint32_t target = ((epoch - 1) * NB + k + 1) * NCTA;
            cnt += near_half();
            SPIN_DECL;
            uint32_t v;
            do {
                __nanosleep(100);
                asm volatile("ld.relaxed.gpu.global.u32 %0, [%1];" : "=r"(v) : "l"(cnt) : "memory");
                SPIN_CHECK(v);
            } while (__any_sync(0xffffffffu, (int)(v - target) < 0));
        }
        uint4 r;
        if (k == 1) mbar_wait(bar_at(B_RK), 0);
        if (k > 1) {
            mbar_wait(bar_at(B_FIN), k & 1);
            r = lds128(SM_FIN + (lane & 1) * 16);
        }
        __syncwarp();
        if (lane == 0) mbar_arrive(bar_at(B_Z));
        if (k > 1) {
            const int b = k - 2;
            const char* src = own + acc_off(b, 1, cta >> 4) + (2 + ((lane >> 1) & 1)) * HALF;
            unsigned short* o = p.out + b * DM + col + (lane >> 2) * 16;
            const bool on = !(lane & 2) && lane < (cl & 2 ? 8 : 12);
            wait_clk(clk32() + CFG(DLY_F));
            float cnt;
            SPIN_DECL;
            do {
                const uint4 v = ld_pkt(src);
                SPIN_CHECK(k);
                cnt = F(v.w) + shx(F(v.w), 2);
                const float y0 = F(v.x) + shx(F(v.x), 2), y1 = F(v.y) + shx(F(v.y), 2), y2 = F(v.z) + shx(F(v.z), 2);
                const uint32_t x01 = badd2(r.x, badd2(r.y, bmul2(pack2(y0, y1), r.w)));
                const uint32_t x2 = badd2(r.z, badd2(r.z >> 16, bmul2(pack2(y2, 0.f), r.w)));
                if (cnt == NCTA && on) *o = lane < 4 ? x01 : lane < 8 ? x01 >> 16 : x2;
            } while (__any_sync(0xffffffffu, cnt != NCTA));
            TRACES((2 * b + 1) * 6 + 4);
        }
    }
}

__host__ __device__ constexpr uint32_t desc_lo(uint32_t addr) { return ((addr & 0x3FFFFu) >> 4) | (1u << 16); }
constexpr uint32_t DESC_HI_TILE = (3072u >> 4) | (1u << 30);
constexpr uint32_t DESC_HI_VEC = 1u;
template <int TA, int AOFF, int BOFF>
__device__ __forceinline__ void wgmma_n8(float (&d)[4], uint32_t alo, uint32_t blo, int accumulate) {
    asm volatile("{\n.reg .pred p;\n.reg .b32 a, b;\n.reg .b64 da, db;\nsetp.ne.b32 p, %6, 0;\n"
                 "add.u32 a, %4, %8;\nadd.u32 b, %5, %9;\nmov.b64 da, {a, %10};\nmov.b64 db, {b, %11};\n"
                 "wgmma.mma_async.sync.aligned.m64n8k16.f32.bf16.bf16 {%0,%1,%2,%3}, da, db, p, 1, 1, %7, 0;\n}"
                 : "+f"(d[0]), "+f"(d[1]), "+f"(d[2]), "+f"(d[3])
                 : "r"(alo), "r"(blo), "r"(accumulate), "n"(TA), "n"(AOFF >> 4), "n"(BOFF >> 4), "n"(DESC_HI_TILE), "n"(DESC_HI_VEC));
}
template <int KS, int END>
__device__ __forceinline__ void qk_steps(float (&d)[4], uint32_t alo, uint32_t blo) {
    if constexpr (KS < END) {
        wgmma_n8<0, (KS >> 2) * 1024 + (KS & 3) * 32, KS * 32>(d, alo, blo, KS > 0);
        qk_steps<KS + 1, END>(d, alo, blo);
    }
}
__device__ __forceinline__ void pv_steps(float (&e)[3][4], uint32_t alo, uint32_t blo, int acc) {
    wgmma_n8<1, 0, 0>(e[0], alo, blo, acc); wgmma_n8<1, 1024, 0>(e[1], alo, blo, acc); wgmma_n8<1, 2048, 0>(e[2], alo, blo, acc);
    wgmma_n8<1, 6144, 32>(e[0], alo, blo, 1); wgmma_n8<1, 7168, 32>(e[1], alo, blo, 1); wgmma_n8<1, 8192, 32>(e[2], alo, blo, 1);
}
__device__ __forceinline__ void wg_fence() { asm volatile("wgmma.fence.sync.aligned;" ::: "memory"); }
__device__ __forceinline__ void wg_commit() { asm volatile("wgmma.commit_group.sync.aligned;" ::: "memory"); }
template <int N> __device__ __forceinline__ void wg_wait() { asm volatile("wgmma.wait_group.sync.aligned %0;" ::"n"(N) : "memory"); }
__device__ __forceinline__ void acc_ready(float (&d)[4]) { asm volatile("" : "+f"(d[0]), "+f"(d[1]), "+f"(d[2]), "+f"(d[3]) :: "memory"); }
__device__ __forceinline__ uint32_t score_pair(float (&d)[4], int lane) {
    acc_ready(d);
    const float scale = 0.07216878364870322f;
    const uint32_t r = pack2(d[0], d[2]);
    return shi(pack2(bf_lo(r) * scale, bf_hi(r) * scale), lane & 28);
}

__device__ __forceinline__ void attention_role(const Params& p, int w, int lane) {
    const int cta = blockIdx.x, t4 = lane & 3, g = lane >> 2;
    mbar_wait(bar_at(B_EP), 0);
    const uint32_t tag0 = lds32(SM_EPOCH) * NB;
    const char* const odst = p.scr + SCR_O + head_off(cta >> 2) + (2 * w + (g >> 2)) * 256 + (cta & 3) * 64 + (g & 3) * 16;
    const uint32_t pdst = SM_P + t4 * PSTR + (16 * w + g) * 2;
    auto softmax = [&](uint32_t sc, int ps) -> uint32_t {
        const float s0 = bf_lo(sc), s1 = bf_hi(sc);
        int key = __float_as_int(fmaxf(s0, s1));
        key ^= (key >> 31) & 0x7fffffff;
        key = __reduce_max_sync(0xffffffffu, key);
        sts32(SM_MAX + w * 4, key);
        bar_sync<4, 128>();
        const uint4 mx = lds128(SM_MAX);
        key = max(max((int)mx.x, (int)mx.y), max((int)mx.z, (int)mx.w));
        key ^= (key >> 31) & 0x7fffffff;
        const float mb = __int_as_float(key) * LOG2E;
        const uint32_t pp = pack2(fast_ex2(fmaf(s0, LOG2E, -mb)), fast_ex2(fmaf(s1, LOG2E, -mb)));
        sts16(pdst + ps * 4 * PSTR, pp); sts16(pdst + ps * 4 * PSTR + 16, pp >> 16);
        uint32_t fs;
        asm volatile("redux.sync.add.u32 %0, %1, 0xffffffff;" : "=r"(fs) : "r"(__float2uint_rn((bf_lo(pp) + bf_hi(pp)) * 8388608.f)));
        fence_async();
        bar_sync<4, 128>();
        sts32(SM_SUM + ps * 16 + w * 4, fs);
        return key;
    };
    auto aux_word = [&](uint32_t mx, const uint4& u, int k) {
        const float l = __uint2float_rn((u.x + u.y) + (u.z + u.w)) * (1.f / 8388608.f);
        return (g < 4 ? mx : (__float_as_uint(l) + 0x80u) & 0xffffff00u) | ((tag0 + k) & 0xffu);
    };
    auto send = [&](float (&e)[3][4], uint32_t aux, int ps) {
        acc_ready(e[0]); acc_ready(e[1]); acc_ready(e[2]);
        const uint32_t o0 = pack2(e[0][0], e[0][2]), o1 = pack2(e[1][0], e[1][2]), o2 = pack2(e[2][0], e[2][2]);
        st_pkt2_if(t4 == 0, odst + ps * 2048, o0, o1, o2, aux);
        mbar_arrive_if(lane == 0, bar_at(ps ? B_RV : B_PS));
    };
    mbar_wait(bar_at(B_QR), 0);
    fence_async();
    TRACES(73);
#pragma unroll 1
    for (int it = 0; it <= NB; it++) {
        uint32_t m1 = 0;
        if (it < NB) {
            const uint32_t tab = slots(it);
            uint32_t sc = 0;
#pragma unroll 1
            for (int t = 0; t < 8; t++) {
                const uint32_t alo = desc_lo(SB) + slot_at(tab, pass_nibble(it, t >> 1)) * (PAIR >> 4), blo = desc_lo(SM_Q) + it * (384 >> 4);
                mbar_wait(bar_at(B_F1 + t), it & 1);
                float d[4] = {};
#pragma unroll 1
                for (int c = 0; c < 3; c++) {
                    wg_fence();
                    wgmma_n8<0, 0, 0>(d, alo + c * 64, blo + c * 8, c > 0); wgmma_n8<0, 32, 32>(d, alo + c * 64, blo + c * 8, 1);
                    wgmma_n8<0, 64, 64>(d, alo + c * 64, blo + c * 8, 1); wgmma_n8<0, 96, 96>(d, alo + c * 64, blo + c * 8, 1);
                    wg_commit();
                    wg_wait<0>();
                }
                if ((t & 1) == (w >> 1)) {
                    mbar_arrive_if(lane == 0, bar_at(B_RR + t));
                    const uint32_t s = score_pair(d, lane);
                    if (t4 == t >> 1) sc = s;
                }
            }
            m1 = softmax(sc, 0);
        }
        if (it > 0) {
            const int k = it - 1;
            const uint32_t tab = slots(k);
            const uint32_t v0 = slot_at(tab, k < NB - 1 ? 0 : 4);
            TRACES(48 + k * 6);
            if (k > 0) mbar_wait(bar_at(B_F3), it & 1);
            mbar_wait(bar_at(B_QR), it & 1);
            fence_async();
            TRACES(49 + k * 6);
            float d[4][4] = {};
#pragma unroll
            for (int u = 0; u < 4; u++) {
                const uint32_t alo = desc_lo(SB) + slot_at(tab, u) * (PAIR >> 4), blo = desc_lo(SM_Q + 4 * 384);
                wg_fence();
                qk_steps<0, 6>(d[u], alo, blo);
                wg_commit();
                wg_wait<1>();
                if (u > 0) mbar_arrive_if(lane == 0, bar_at(B_RK + u - 1));
                wg_fence();
                qk_steps<6, 12>(d[u], alo, blo);
                wg_commit();
                if (u < 3) wg_wait<1>();
            }
            uint32_t sc = score_pair(d[0], lane), s = score_pair(d[1], lane);
            if (t4 == 1) sc = s;
            s = score_pair(d[2], lane);
            if (t4 == 2) sc = s;
            wg_wait<0>();
            s = score_pair(d[3], lane);
            mbar_arrive_if(lane == 0, bar_at(B_RK + 3));
            if (t4 == 3) sc = s;
            TRACES(50 + k * 6);
            const uint32_t m2 = softmax(sc, 1);
            TRACES(51 + k * 6);
            float e[3][4] = {};
            uint4 u;
#pragma unroll
            for (int t = 0; t < 8; t++) {
                const int pr = ((t >> 1) + 1) & 3;
                if (t == 6 && k < NB - 1) mbar_wait(bar_at(B_FL), k & 1);
                if (t == 7) { bar_sync<4, 128>(); u = lds128(SM_SUM + 16); }
                wg_fence();
                pv_steps(e, desc_lo(SB + (t & 1) * TILE) + (pr ? slot_at(tab, 4 + pr) : v0) * (PAIR >> 4), desc_lo(SM_P + (4 + pr) * PSTR + (t & 1) * 64), t > 0);
                wg_commit();
                if (t < 7) wg_wait<1>();
                if (t == 0) st_pkt2_if(t4 == 0, odst + 2048, 0, 0, 0, tag0 + k + 128);
            }
            const uint32_t aux = opaque(aux_word(m2, u, k));
            wg_wait<0>();
            send(e, aux, 1);
            TRACES(52 + k * 6);
        }
        if (it < NB) {
            const uint32_t tab = slots(it);
            st_pkt2_if(t4 == 0, odst, 0, 0, 0, tag0 + it + 128);
            bar_sync<4, 128>();
            const uint32_t aux = opaque(aux_word(m1, lds128(SM_SUM), it));
            float e[3][4] = {};
#pragma unroll 1
            for (int u = 0; u < 4; u++) {
                const uint32_t alo = desc_lo(SB) + slot_at(tab, 4 + u) * (PAIR >> 4), blo = desc_lo(SM_P) + u * (PSTR >> 4);
                mbar_wait(bar_at(B_F1 + 8 + 2 * u), it & 1);
                wg_fence();
                pv_steps(e, alo, blo, u > 0);
                wg_commit();
                wg_wait<1>();
                if (u == 1) mbar_arrive_if(lane == 0, bar_at(B_RP));
                mbar_wait(bar_at(B_F1 + 9 + 2 * u), it & 1);
                wg_fence();
                pv_steps(e, alo + (TILE >> 4), blo + 4, 1);
                wg_commit();
                wg_wait<1>();
            }
            wg_wait<0>();
            send(e, aux, 0);
            TRACES(53 + it * 6);
        }
    }
}

__device__ __forceinline__ void ln_finish(float s, float q, float& mean_b, float& rden) {
    const float mean = s * (1.f / DM);
    const float var = fmaxf(fmaf(q, 1.f / DM, -mean * mean), 0.f);
    mean_b = bfr(mean);
    rden = fast_rcp(bfr(fast_sqrt(bfr(bfr(var) + 1e-5f))));
}
__device__ __forceinline__ uint32_t ln_apply(uint32_t w, float mean_b, float rden) {
    const uint32_t d = bsub2(w, __byte_perm(__float_as_uint(mean_b), 0, 0x3232));
    return pack2(bf_lo(d) * rden, bf_hi(d) * rden);
}
__device__ __forceinline__ void spread(uint32_t (&b)[10], uint32_t x01, uint32_t x2, uint32_t wa, uint32_t ra, bool e2) {
    sts16(wa, x01); sts16(wa + 8, x01 >> 16);
    sts16_if(!e2, wa + 16, x2);
    __syncwarp();
    const uint4 u = lds128(ra), v = lds128(ra + 16);
    const uint2 z = lds64(ra + 32);
    b[0] = u.x; b[1] = u.y; b[2] = u.z; b[3] = u.w; b[4] = v.x; b[5] = v.y; b[6] = v.z; b[7] = v.w; b[8] = z.x; b[9] = z.y;
}
__device__ __forceinline__ float fold(float a, float b, bool sel, int m) { return (sel ? b : a) + shx(sel ? a : b, m); }

__device__ __forceinline__ void chain_role(const Params& p, int w, int lane, uint32_t t0) {
    const int cta = blockIdx.x, h = cta >> 2, s = cta & 3;
    const int g = lane >> 2, t4 = lane & 3;
    const bool e1 = t4 & 1, e2 = t4 & 2;
    uint32_t wq[5][3][4], wo[3][5][4], wg[5][4], wh[5][2], wd[4][4];
    const int col0 = 80 * w + (e2 ? 48 : 0) + g + (e1 ? 8 : 0);
    const uint32_t xw = opaque(SM_X + w * 384 + 48 * (g >> 1) + (e2 ? 24 : 0) + (e1 ? 4 : 0) + 2 * (g & 1));
    const uint32_t xr = opaque(g == 1 ? SM_ONES : SM_X + w * 384 + (g == 3 ? 192 : 0) + 48 * t4);
    TRACES(75);
    sts32_if(lane < 12, SM_ONES + lane * 4, 0x3f803f80u);
    uint32_t zero = lane >> 5;
    const int mi = lane >> 3, mr = lane & 7;
    mbar_wait(bar_at(B_W), 0);
    TRACES(74);
    sts16(xw + 192, lds16(ST_X + 5120 + col0 * 2)); sts16(xw + 200, lds16(ST_X + 5120 + col0 * 2 + 32));
    sts16_if(!e2, xw + 208, lds16(ST_X + 5120 + col0 * 2 + 64));
#pragma unroll
    for (int i = 0; i < 5; i++)
#pragma unroll
        for (int mt = 0; mt < 3; mt++) ldsm4t(wq[i][mt], ST_WQ + (80 * w + 16 * i + mr + 8 * (mi >> 1)) * 96 + 32 * mt + 16 * (mi & 1), zero);
    const bool odd = cta & 1;
    const uint32_t lo = ST_WD + (mr + (odd ? 4 : 0)) * 1280 + 160 * w, hi = ST_WD + ((mr & 3) + (odd ? 0 : 8)) * 1280 + 160 * w;
    ldsm4t(wd[0], lo + 16 * mi, zero);
    ldsm4t(wd[1], lo + 64 + 16 * mi, zero);
    ldsm4t(wd[2], hi + 64 * (mi >> 1) + 32 * (mr >> 2) + 16 * (mi & 1), zero);
    ldsm4t(wd[3], (mi < 2 ? lo : hi) + 128 + 16 * (mi & 1), zero);
    fence_async();
    __syncwarp();
    mbar_arrive_if(lane == 0, bar_at(B_WC));
    mbar_wait(bar_at(B_EP), 0);
    const uint32_t near = __shfl_sync(0xffffffffu, near_half(), 0);
    uint32_t x01 = 0, x2 = 0, nx01 = 0, nx2 = 0;
#pragma unroll 1
    for (int n = -5; n < NROUND; n++) {
        const bool last = (ORD_LAST >> (n & 15)) & 1, head = !((ORD_NO_HEAD >> (n & 15)) & 1);
        const int k = (ORD_BATCH >> (2 * (n & 15))) & 3;
        if (n > -5 && n <= 0) bar_sync<7, 288>();
        else if (!last) bar_sync<2, 256>();
        TRACES(n <= 0 ? 83 + n : 95);
        const char* const slice = p.scr + acc_off(k, last, w);
        const char* const cell = opaque(slice + g * 256 + t4 * 16);
        if (n >= 0) {
          if (head) {
            if (!last || n == NROUND - 1) mbar_wait(bar_at(B_Z), (k + last) & 1);
            const char* src = p.scr + SCR_O + head_off(h) + head_near(h, near) + last * 2048 + (w & 6) * 256 + (lane & 15) * 16;
            const uint32_t tag = lds32(SM_EPOCH) * NB + k;
            mbar_wait(bar_at(last ? B_RV : B_PS), k & 1);
            if (!last && k < NB - 1) wait_ns(t0 + batch_ns(k + 1) + CFG(START));
            uint4 v, z;
            {
                SPIN_DECL;
                do {
                    v = ld_pkt(src); z = ld_pkt(src + 256);
                    SPIN_CHECK(n);
                } while (__any_sync(0xffffffffu, (((v.w ^ tag) | (z.w ^ tag)) & 0xffu) != 0));
            }
            TRACES(tr + 0);
            float a[3][4] = {};
            const uint32_t bb[3][2] = {{v.x, v.y}, {z.x, z.y}, {v.z, z.z}};
            float sa, sb, rl;
#pragma unroll
            for (int i = 0; i < 3; i++) {
                const uint32_t l0 = g < 4 ? bb[i][0] : 0, l1 = g < 4 ? bb[i][1] : 0, h0 = g < 4 ? 0 : bb[i][0], h1 = g < 4 ? 0 : bb[i][1];
#pragma unroll
                for (int mt = 0; mt < 5; mt++)
                    mma16816(a[mt % 3], wo[i][mt][0], wo[i][mt][1], wo[i][mt][2], wo[i][mt][3], mt < 3 ? l0 : h0, mt < 3 ? l1 : h1);
                if (i == 0) {
                    int key = v.w & 0xffffff00u;
                    key ^= (key >> 31) & 0x7fffffff;
                    key = __reduce_max_sync(0xffffffffu, key);
                    key ^= (key >> 31) & 0x7fffffff;
                    const float ws = fast_ex2((F(v.w & 0xffffff00u) - __int_as_float(key)) * LOG2E);
                    sa = shi(ws, e1 ? 8 : 0); sb = shi(ws, e1 ? 12 : 4);
                    rl = ws * F(z.w & 0xffffff00u);
                    rl += shx(rl, 4);
                }
                if (i == 1) rl += shx(rl, 8);
            }
            float y[3];
#pragma unroll
            for (int j = 2; j < 5; j++) {
                const int mt = j % 3;
                y[mt] = fold(fmaf(a[mt][0], sa, a[mt][1] * sb), fmaf(a[mt][2], sa, a[mt][3] * sb), e1, 1);
            }
            const uint32_t pa = SM_PO + w * 512 + lane * 16;
            if (w < 2) {
                const char* dst = opaque(cell + s * 16384);
                rl = fast_rcp(rl);
                bar_sync<1, 256>();
                const uint4 c1 = lds128(pa), c2 = lds128(pa + 1024), c3 = lds128(pa + 2048);
                red_cell2_if(true, dst, ((y[0] + F(c1.x)) + (F(c2.x) + F(c3.x))) * rl, ((y[1] + F(c1.y)) + (F(c2.y) + F(c3.y))) * rl,
                             ((y[2] + F(c1.z)) + (F(c2.z) + F(c3.z))) * rl);
            } else {
                stsf4(pa - 1024, y[0], y[1], y[2], 0.f);
                bar_sync<1, 256>();
            }
            TRACES(tr + 1);
            if ((ORD_NO_TAIL >> n) & 1) continue;
            wait_clk(clk32() + (w < 2 ? 0 : 60) + (n < QUIET ? CFG(DLY_AL) : CFG(DLY_A)));
            {
                SPIN_DECL;
                do {
                    v = ld_pkt(cell + near);
                    SPIN_CHECK(n);
                } while (__any_sync(0xffffffffu, v.w != FULL_A));
            }
            TRACES(tr + 2);
            x01 = pack2(F(v.x), F(v.y));
            x2 = pack2(F(v.z), 0.f);
          } else { x01 = nx01; x2 = nx2; }
        } else if (n == -1) {
            mbar_wait(bar_at(B_W + 1), 0);
            const uint32_t ln = opaque(lane);
            const int mi = ln >> 3, mr = ln & 7;
            uint32_t zero = ln >> 5;
            TRACES(76);
#pragma unroll
            for (int i = 0; i < 3; i++) {
                const int d = 16 * (w >> 1) + (mr >> 1) + 8 * (mr & 1) + (i < 2 ? 64 * (mi >> 1) + 4 * i : 128 + 4 * (mi >> 1));
#pragma unroll
                for (int mt = 0; mt < 5; mt++) ldsm4t(wo[i][mt], ST_WO + d * 320 + 160 * (w & 1) + 32 * mt + 16 * (mi & 1), zero);
            }
            fence_async();
            __syncwarp();
            mbar_arrive_if(lane == 0, bar_at(B_WC + 1));
            mbar_wait(bar_at(B_W + 2), 0);
            TRACES(77);
#pragma unroll
            for (int i = 0; i < 5; i++) {
                const uint32_t ga = ST_WG + (mi & 1) * 20480 + (80 * w + 16 * i + mr + 8 * (mi >> 1)) * 32;
                uint32_t r[4];
                ldsm4t(wg[i], ga + (odd ? 16 : 0), zero);
                ldsm4t(r, ga + (odd ? 0 : 16), zero);
#pragma unroll
                for (int kh = 0; kh < 2; kh++) {
                    const uint32_t moved = __shfl_xor_sync(0xffffffffu, odd ? r[2 * kh] : r[2 * kh + 1], 16);
                    wh[i][kh] = (g < 4) == odd ? moved : odd ? r[2 * kh + 1] : r[2 * kh];
                }
            }
            fence_async();
            __syncwarp();
            mbar_arrive_if(lane == 0, bar_at(B_WC + 2));
            TRACES(72);
            x01 = 0x3f803f80u; x2 = 0x3f80u;
        } else {
            const uint32_t xa = ST_X + (n + 5) * 1280, ln = opaque(lane);
            const int col0 = 80 * w + (ln & 2 ? 48 : 0) + (ln >> 2) + (ln & 1 ? 8 : 0);
            float sm = 0.f, sq = 0.f;
#pragma unroll
            for (int i = 0; i < 5; i++) {
                const uint2 c = lds64(xa + i * 256 + ln * 8);
                sm += (bf_lo(c.x) + bf_hi(c.x)) + (bf_lo(c.y) + bf_hi(c.y));
                sq = fmaf(bf_lo(c.x), bf_lo(c.x), fmaf(bf_hi(c.x), bf_hi(c.x), fmaf(bf_lo(c.y), bf_lo(c.y), fmaf(bf_hi(c.y), bf_hi(c.y), sq))));
            }
            x01 = lds16(xa + col0 * 2) | lds16(xa + col0 * 2 + 32) << 16;
            x2 = lds16(xa + col0 * 2 + 64);
#pragma unroll
            for (int o = 16; o; o >>= 1) { sm += shx(sm, o); sq += shx(sq, o); }
            float mean_b, rden;
            ln_finish(sm, sq, mean_b, rden);
            x01 = ln_apply(x01, mean_b, rden);
            x2 = ln_apply(x2, mean_b, rden);
        }
        if (n >= -1) {
            uint32_t b[10];
            spread(b, x01, x2, xw, xr, e2);
            float a[2][4] = {};
#pragma unroll
            for (int i = 0; i < 5; i++) {
                mma16816(a[0], wg[i][0], wg[i][1], wg[i][2], wg[i][3], b[2 * i], b[2 * i + 1]);
                mma16816(a[1], wh[i][0], b[2 * i], wh[i][1], b[2 * i + 1], b[2 * i], b[2 * i + 1]);
            }
            stsf(SM_PG + (w >> 2) * 512 + (g + 8 * t4) * 16 + (w & 3) * 4, e2 ? (e1 ? a[1][2] : a[1][0]) : (e1 ? a[0][2] : a[0][0]));
            const uint2 cs = lds64(SM_CSG + lane * 48);
            const char* dst = opaque(cell + 3 * HALF - near);
            bar_sync<2, 256>();
            const float S = sum8(lds128(SM_PG + lane * 16), lds128(SM_PG + 512 + lane * 16));
            const float sx = shi(S, 25), sq = shi(S, 24), Su = shi(S, lane + (lane < 16 ? 8 : 4));
            if (n < 0) {
                if (w == 0) stsf2(SM_CSG + lane * 48, S, Su);
            } else {
                float mean_b, rden;
                ln_fast(sx, sq, mean_b, rden);
                const float gv = bfr(fmaf(-mean_b, F(cs.x), S) * rden), uv = bfr(fmaf(-mean_b, F(cs.y), Su) * rden);
                const float sg = fast_rcp(1.f + fast_ex2(-LOG2E * gv));
                const uint32_t hb = pack2(bfr(gv * sg) * uv, 0.f);
                const uint32_t b0 = __byte_perm(shi(hb, 2 * t4), shi(hb, 2 * t4 + 1), 0x5410);
                const uint32_t b1 = __byte_perm(shi(hb, e1 ? 18 : 16), shi(hb, e1 ? 19 : 17), 0x5410);
                const bool up = g >= 4;
                const uint32_t l0 = up ? 0 : b0, h0 = up ? b0 : 0;
                const uint32_t l1 = up ? 0 : b1, h1 = up ? b1 : 0;
                float d[3][4] = {};
                mma1688(d[0], wd[0][0], wd[0][1], l0); mma1688(d[1], wd[0][2], wd[0][3], l0); mma1688(d[2], wd[1][0], wd[1][1], l0);
                mma1688(d[0], wd[1][2], wd[1][3], h0); mma1688(d[1], wd[3][0], wd[3][1], h0);
                mma1688(d[2], wd[2][2], wd[2][3], e2 ? 0 : l1);
                mma1688(d[0], wd[2][0], wd[2][1], e2 ? 0 : l1); mma1688(d[1], wd[2][0], wd[2][1], e2 ? l1 : 0);
                mma1688(d[0], wd[2][2], wd[2][3], e2 ? h1 : 0); mma1688(d[1], wd[3][2], wd[3][3], e2 ? 0 : h1);
                red_cell(dst, e1 ? d[0][2] : d[0][0], e1 ? d[1][2] : d[1][0], e1 ? d[2][2] : d[2][0]);
                const uint32_t tsend = clk32();
                TRACES(tr + 3);
                if (last && w != cta >> 4) continue;
                if (!last && w == 0) st_pkt82_if(lane < 24, p.scr + SCR_Q + head_off(h) + 4 * 768 + (24 * s + lane) * 8, 0, 0);
                const float sgr = shi(sg, 27);
                const uint32_t sg2 = pack2(sgr, sgr);
                const uint32_t n01 = opaque(pack2((bf_lo(x01) - mean_b) * rden, (bf_hi(x01) - mean_b) * rden));
                const uint32_t n2 = opaque(pack2((bf_lo(x2) - mean_b) * rden, 0.f));
                if (last) {
                    sts128_if(lane >> 1 == (cta & 15), SM_FIN + (lane & 1) * 16, x01, n01, __byte_perm(x2, n2, 0x5410), sg2);
                    mbar_arrive_if(lane >> 1 == (cta & 15), bar_at(B_FIN));
                    __syncwarp();
                    continue;
                }
                if (n > 0) {
                    const char* src = p.scr + acc_off(k - 1, 1, w) + near + g * 256 + t4 * 16;
                    SPIN_DECL;
                    while (true) {
                        const uint4 u = ld_pkt(src);
                        nx01 = pack2(F(u.x), F(u.y)); nx2 = pack2(F(u.z), 0.f);
                        if (__all_sync(0xffffffffu, u.w == FULL_A)) break;
                        SPIN_CHECK(n);
                    }
                }
                wait_clk(tsend + (n < QUIET ? CFG(DLY_BL) : CFG(DLY_B)));
                uint4 v, z;
                {
                    SPIN_DECL;
                    do {
                        v = ld_pkt(cell + 2 * HALF); z = ld_pkt(cell + 3 * HALF);
                        SPIN_CHECK(n);
                    } while (__any_sync(0xffffffffu, F(v.w) + F(z.w) != NCTA));
                }
                x01 = badd2(x01, badd2(n01, bmul2(pack2(F(v.x) + F(z.x), F(v.y) + F(z.y)), sg2)));
                x2 = badd2(x2, badd2(n2, bmul2(pack2(F(v.z) + F(z.z), 0.f), sg2)));
                TRACES(tr + 4);
            }
        }
        {
            uint32_t b[10];
            spread(b, x01, x2, xw, xr, e2);
            float a[3][4] = {};
            const float f0 = bf_lo(x01), f1 = bf_hi(x01), f2 = e2 ? 0.f : bf_lo(x2);
            float st;
#pragma unroll
            for (int i = 0; i < 5; i++) {
#pragma unroll
                for (int mt = 0; mt < 3; mt++) {
                    mma16816(a[mt], wq[i][mt][0], wq[i][mt][1], wq[i][mt][2], wq[i][mt][3], b[2 * i], b[2 * i + 1]);
                    if (i == 0 && mt == 0) st = fold(fmaf(f0, f0, fmaf(f1, f1, f2 * f2)), (f0 + f1) + f2, g & 1, 4);
                }
                if (i < 4) st += shx(st, i < 2 ? 1 << i : 2 << i);
            }
            const uint32_t pa = SM_PQ + (w >> 2) * 1024 + (g & 1) * 512 + ((e2 ? 16 : 0) + (e1 ? 4 : 0) + (g >> 1)) * 16 + (w & 3) * 4;
            stsf(pa + 128, e2 ? st : e1 ? a[1][2] : a[1][0]);
            stsf(pa, e2 ? (e1 ? a[2][2] : a[2][0]) : (e1 ? a[0][2] : a[0][0]));
            bar_arrive<3, 288>();
            if (n >= 0 && w == cta >> 4) {
                red_cell2_if(lane >> 1 == (cta & 15), cell + 128, f0, f1, f2);
                __syncwarp();
            }
        }
    }
}

template <int ID> __device__ __forceinline__ void role_exit() { asm volatile("exit; // %0" ::"n"(ID)); }
constexpr int NTHREADS = 512;
#define STR2(x) #x
#define STR(x) STR2(x)
__global__ void __launch_bounds__(NTHREADS, 1)
decode_kernel(const Params p, const __grid_constant__ Maps tm) {
    extern __shared__ __align__(1024) unsigned char smem[];
    if (threadIdx.x == 0) l2_prefetch(p.wq + (size_t)blockIdx.x * 12288, 12288);
    const uint32_t t0 = now_ns() - CFG(LEAD);
    const int lane = threadIdx.x & 31;
    const int warp = __shfl_sync(0xffffffffu, threadIdx.x >> 5, 0);
    if (warp < 8) {
        asm volatile("setmaxnreg.inc.sync.aligned.u32 " STR(CFG_REG_CHAIN) ";");
        bar_arrive<5, 480 + 0>();
        const uint32_t vote = probe_near(p, warp, lane);
        bar_sync<2, 256 + 32>();
        sts32(SM_NEAR + warp * 4, vote);
        mbar_arrive_if(lane == 0, bar_at(B_EP));
        chain_role(p, warp, __shfl_sync(0xffffffffu, lane, lane), t0);
        role_exit<3>();
    } else if (warp < 12) {
        asm volatile("setmaxnreg.dec.sync.aligned.u32 " STR(CFG_REG_ATT) ";");
        if (elect_one()) {
#pragma unroll 1
            for (int i = warp - 8; i < NBAR; i += 4)
                if (i < B_W || i >= B_WC) mbar_init(bar_at(i), i == B_FIN ? 2 : i == B_EP ? 9 : i == B_QR ? 32 : i == B_PS || i == B_RP ? 4 : i >= B_F3 ? 1 : i >= B_WC ? 8 : i < B_RR || i > B_RV ? 1 : i < B_RK ? 2 : 4);
            asm volatile("fence.mbarrier_init.release.cluster;" ::: "memory");
            fence_async();
        }
        bar_sync<5, 480>();
        attention_role(p, warp - 8, lane);
        role_exit<2>();
    } else {
        asm volatile("setmaxnreg.dec.sync.aligned.u32 " STR(CFG_REG_HELP) ";");
        if (warp == 12) {
            load_role(p, &tm.k, lane, t0);
            role_exit<0>();
        } else {
            if (warp == 14) {
                if (smem_u32(smem) != SB) __trap();
                if (elect_one()) {
                    asm volatile("prefetch.tensormap [%0];" ::"l"(&tm.q) : "memory");
                    mbar_init(bar_at(B_W), 1); mbar_init(bar_at(B_W + 1), 1); mbar_init(bar_at(B_W + 2), 1);
                    asm volatile("fence.mbarrier_init.release.cluster;" ::: "memory");
                    fence_async();
                    mbar_expect_tx(bar_at(B_W), 61440 + 15360 + 6400); mbar_expect_tx(bar_at(B_W + 1), 61440); mbar_expect_tx(bar_at(B_W + 2), 40960);
                    bulk_load(ST_X, p.x, 5120, bar_at(B_W));
                    bulk_load(ST_X + 5120, p.wr, 1280, bar_at(B_W));
                }
                reload_role(p, &tm, t0);
            } else {
                unsigned ticket = 0;
                if (warp == 15 && lane == 0) asm volatile("atom.relaxed.gpu.global.add.u32 %0, [%1], 1;" : "=r"(ticket) : "l"(&g_epoch) : "memory");
                if (warp == 13 && elect_one()) {
                    asm volatile("prefetch.tensormap [%0];" ::"l"(&tm.g) : "memory");
                    asm volatile("prefetch.tensormap [%0];" ::"l"(&tm.u) : "memory");
                    asm volatile("prefetch.tensormap [%0];" ::"l"(&tm.o) : "memory");
                    asm volatile("prefetch.tensormap [%0];" ::"l"(&tm.k) : "memory");
                    asm volatile("prefetch.tensormap [%0];" ::"l"(&tm.v) : "memory");
                }
                bar_sync<5, 480>();
                if (warp == 13) { bar_arrive<6, 64>(); q_role(p, lane); }
                else { bar_arrive<2, 256 + 32>(); zero_role(p, lane, ticket, t0); }
            }
            role_exit<1>();
        }
    }
}

typedef CUresult (*EncodeFn)(CUtensorMap*, CUtensorMapDataType, cuuint32_t, void*, const cuuint64_t*, const cuuint64_t*,
                             const cuuint32_t*, const cuuint32_t*, CUtensorMapInterleave, CUtensorMapSwizzle,
                             CUtensorMapL2promotion, CUtensorMapFloatOOBfill);

bool make_map(EncodeFn fn, CUtensorMap* m, const void* ptr, uint64_t cols, uint64_t rows, uint32_t bc, uint32_t br) {
    cuuint64_t dims[2] = {cols, rows};
    cuuint64_t strides[1] = {cols * 2};
    cuuint32_t box[2] = {bc, br};
    cuuint32_t es[2] = {1, 1};
    return fn(m, CU_TENSOR_MAP_DATA_TYPE_BFLOAT16, 2, const_cast<void*>(ptr), dims, strides, box, es, CU_TENSOR_MAP_INTERLEAVE_NONE,
              CU_TENSOR_MAP_SWIZZLE_NONE, CU_TENSOR_MAP_L2_PROMOTION_L2_128B, CU_TENSOR_MAP_FLOAT_OOB_FILL_NONE) == CUDA_SUCCESS;
}

bool make_kv_map(EncodeFn fn, CUtensorMap* m, const void* ptr) {
    cuuint64_t dims[4] = {64, 8, 3, (cuuint64_t)NB * NHEAD * SK / 8};
    cuuint64_t strides[3] = {DH * 2, 128, 8 * DH * 2};
    cuuint32_t box[4] = {64, 8, 3, 4};
    cuuint32_t es[4] = {1, 1, 1, 1};
    return fn(m, CU_TENSOR_MAP_DATA_TYPE_BFLOAT16, 4, const_cast<void*>(ptr), dims, strides, box, es, CU_TENSOR_MAP_INTERLEAVE_NONE,
              CU_TENSOR_MAP_SWIZZLE_128B, CU_TENSOR_MAP_L2_PROMOTION_L2_128B, CU_TENSOR_MAP_FLOAT_OOB_FILL_NONE) == CUDA_SUCCESS;
}

}

extern "C" void kernel_launch(void* const* d_in, const int* in_sizes, int n_in, void* d_out, int out_size) {
    (void)in_sizes; (void)n_in; (void)out_size;
    static EncodeFn fn = nullptr;
    static const char* scr = nullptr;
    if (!fn) {
        void* f = nullptr;
        cudaDriverEntryPointQueryResult qr;
        if (cudaGetDriverEntryPoint("cuTensorMapEncodeTiled", &f, cudaEnableDefault, &qr) != cudaSuccess || !f) return;
        void* sp = nullptr;
        if (cudaGetSymbolAddress(&sp, g_scratch) != cudaSuccess) return;
        scr = (const char*)(((uintptr_t)sp + (2 << 20) - 1) & ~(uintptr_t)((2 << 20) - 1));
        fn = (EncodeFn)f;
        cudaFuncSetAttribute(decode_kernel, cudaFuncAttributeMaxDynamicSharedMemorySize, SMEM_BYTES);
    }
    Maps tm;
    if (!make_kv_map(fn, &tm.k, d_in[1]) || !make_kv_map(fn, &tm.v, d_in[2])) return;
    if (!make_map(fn, &tm.q, d_in[3], NHEAD * DH, DM, 48, 128) || !make_map(fn, &tm.o, d_in[4], DM, NHEAD * DH, 160, 32)) return;
    if (!make_map(fn, &tm.g, d_in[7], FF, DM, 16, 128) || !make_map(fn, &tm.u, d_in[8], FF, DM, 16, 128)) return;
    Params p;
    p.x = (const unsigned short*)d_in[0];
    p.wq = (const char*)d_in[3];
    p.wo = (const char*)d_in[4];
    p.wr = (const unsigned short*)d_in[6];
    p.wg = (const char*)d_in[7];
    p.wu = (const char*)d_in[8];
    p.wd = (const char*)d_in[9];
    p.out = (unsigned short*)d_out;
    p.scr = scr;
    decode_kernel<<<NCTA, NTHREADS, SMEM_BYTES>>>(p, tm);
}
```

```cpp
#include <cuda_runtime.h>
#include <cuda_bf16.h>
#include <cuda.h>
#include <stdint.h>

namespace {

constexpr int NB = 4, DM = 640, NHEAD = 32, DH = 192, SK = 4096, WIN = 1024, FF = 1536;
constexpr int NCTA = 128;
constexpr int TILE = 12288, PAIR = 2 * TILE;

#define CFG_LIST(X) \
    X(TICK0, 480)        \
    X(TICK, 506)        \
    X(LEAD, 350)        \
    X(STAG, 560)        \
    X(WLAG, 300)        \
    X(GSTEP, 700)        \
    X(WIN, 4)        \
    X(PMAX, 4)        \
    X(PGRACE, 50)        \
    X(LMAX0, 100)        \
    X(LMAX, 150) \
    X(GAIN, 10)        \
    X(VSTEP, 250)        \
    X(RLAG, 0)        \
    X(RSTEP, 640) \
    X(RSTEP3, 390) \
    X(ZTILE, 11)        \
    X(START, 1)        \
    X(DLY_A, 450)        \
    X(DLY_AL, 100) \
    X(DLY_B, 600) \
    X(DLY_BL, 900) \
    X(DLY_F, 250) \
    X(FLIP, 0) \

#define X(n, v) constexpr int CFG_##n = v;
CFG_LIST(X)
#undef X
#define CFG(n) CFG_##n
constexpr int QUIET = 8;
#define CFG_REG_CHAIN 216
#define CFG_REG_ATT 48
#define CFG_REG_HELP 32
constexpr int KB_KV0 = 165;
__device__ __forceinline__ int kb_ns(int kb) { return kb * CFG(TICK0) / 12; }
__device__ __forceinline__ int tick_ns(int j) { return j <= 16 ? CFG(TICK0) : CFG(TICK); }
__device__ __forceinline__ int batch_ns(int k) { return kb_ns(KB_KV0) + (k ? 16 * (CFG(TICK0) + (k - 1) * CFG(TICK)) : 0); }

__device__ __forceinline__ uint32_t slots(int k) { return k & 2 ? (k & 1 ? 0x21304768u : 0x76835214u) : (k & 1 ? 0x21480765u : 0x76543210u); }
__device__ __forceinline__ int pass_nibble(int k, int u) { return k > 0 ? 4 + (u & 1) : u; }
__device__ __forceinline__ uint32_t slot_at(uint32_t tab, int u) { return (tab >> (4 * u)) & 15; }

constexpr int NROUND = 11;
constexpr uint32_t ORD_BATCH = 0x3b9910, ORD_LAST = 0x6da, ORD_NO_HEAD = 0x248, ORD_NO_TAIL = 0x092;

constexpr uint32_t SB = 1024;
constexpr uint32_t SM_BAR = SB + 9 * PAIR;
constexpr int B_F1 = 0;
constexpr int B_RR = 24;
constexpr int B_RK = 32;
constexpr int B_RV = 36;
constexpr int B_Z = 37;
constexpr int B_EP = 38;
constexpr int B_W = 39;
constexpr int B_WC = 42;
constexpr int B_FIN = 45;
constexpr int B_F3 = 46;
constexpr int B_PS = 48;
constexpr int B_RP = 49;
constexpr int B_FL = 50;
constexpr int B_QR = 51;
constexpr int NBAR = 52;
__host__ __device__ constexpr uint32_t bar_at(int i) { return SM_BAR + 8 * i; }
constexpr uint32_t SM_EPOCH = SM_BAR + 416;
constexpr uint32_t SM_MAX = SM_EPOCH + 16;
constexpr uint32_t SM_SUM = SM_MAX + 16;
constexpr uint32_t SM_NEAR = SM_SUM + 32;
constexpr uint32_t SM_FIN = SM_NEAR + 32;
constexpr uint32_t SM_Q = SM_FIN + 32;
constexpr uint32_t PSTR = 144;
constexpr uint32_t SM_P = SM_Q + 5 * 384;
constexpr uint32_t SM_X = SM_P + 8 * PSTR;
constexpr uint32_t SM_CSG = SM_X + 40;
constexpr uint32_t SM_ONES = SM_X + 8 * 384;
constexpr uint32_t SM_PG = SM_ONES + 48;
constexpr uint32_t SM_PO = SM_PG + 1024;
constexpr uint32_t SM_PQ = SM_PO;
constexpr int SMEM_BYTES = SM_PO + 3072 - SB;
static_assert(SMEM_BYTES <= 232448 && SM_Q % 16 == 0 && SM_P % 16 == 0 && SM_X % 16 == 0 && SM_PO % 16 == 0, "smem");
constexpr uint32_t ST_WQ = SB, ST_WD = SB + 3 * PAIR, ST_WO = SB + 4 * PAIR, ST_WG = SB + 7 * PAIR, ST_X = ST_WG + 40960;

__device__ unsigned g_epoch;
__device__ unsigned char g_scratch[4 << 20];
constexpr uint32_t HALF = 4096, SCR_O = 1 << 16, SCR_Q = 1 << 17, SCR_PROBE = 1 << 19, SCR_COUNT = 3 << 16;
__device__ __forceinline__ uint32_t acc_off(int k, int layer, int w) { return (k & 1) << 18 | (k >> 1) << 20 | (w >> 1) << 14 | (w & 1) << 11 | layer << 7; }
__device__ __forceinline__ uint32_t head_off(int h) { return (h & 3) << 14 | (h & 4) << 16 | (h & 8) << 17 | (h & 16) << 9; }
__device__ __forceinline__ uint32_t head_near(int h, uint32_t near) { return near ^ HALF ^ (h & 16) << 8; }
constexpr uint32_t FULL_A = 0x42040000u;

struct Params {
    const char* wq;
    const unsigned short* x;
    const char* wo;
    const unsigned short* wr;
    const char* wg;
    const char* wu;
    const char* wd;
    unsigned short* out;
    const char* scr;
};

__device__ __forceinline__ uint32_t smem_u32(const void* p) { return (uint32_t)__cvta_generic_to_shared(p); }
__device__ __forceinline__ void mbar_init(uint32_t a, uint32_t c) { asm volatile("mbarrier.init.shared::cta.b64 [%0], %1;" ::"r"(a), "r"(c) : "memory"); }
__device__ __forceinline__ void mbar_expect_tx(uint32_t a, uint32_t b) {
    asm volatile("mbarrier.arrive.expect_tx.shared::cta.b64 _, [%0], %1;" ::"r"(a), "r"(b) : "memory");
}
__device__ __forceinline__ void mbar_arrive(uint32_t a) { asm volatile("mbarrier.arrive.shared::cta.b64 _, [%0];" ::"r"(a) : "memory"); }
constexpr uint32_t SPIN_LIMIT = 1u << 22;
#define SPIN_DECL uint32_t spins = 0
#define SPIN_CHECK(info) { if (++spins > SPIN_LIMIT) __trap(); }
__device__ __forceinline__ void mbar_wait(uint32_t a, uint32_t parity) {
    uint32_t ok;
    SPIN_DECL;
    while (true) {
        asm volatile("{\n.reg .pred p;\nmbarrier.try_wait.parity.shared::cta.b64 p, [%1], %2;\nselp.u32 %0, 1, 0, p;\n}"
                     : "=r"(ok) : "r"(a), "r"(parity) : "memory");
        if (ok) break;
        SPIN_CHECK((a - SM_BAR) / 8 * 10 + parity);
    }
}
__device__ __forceinline__ bool mbar_test2(uint32_t a, uint32_t pa, uint32_t b, uint32_t pb) {
    uint32_t ok;
    asm volatile("{\n.reg .pred p, q;\nmbarrier.test_wait.parity.shared::cta.b64 p, [%1], %2;\n"
                 "mbarrier.test_wait.parity.shared::cta.b64 q, [%3], %4;\nand.pred p, p, q;\nvote.sync.all.pred p, p, 0xffffffff;\nselp.u32 %0, 1, 0, p;\n}"
                 : "=r"(ok) : "r"(a), "r"(pa), "r"(b), "r"(pb) : "memory");
    return ok;
}
__device__ __forceinline__ uint32_t now_ns() { uint32_t t; asm volatile("mov.u32 %0, %%globaltimer_lo;" : "=r"(t) :: "memory"); return t; }
__device__ __forceinline__ uint32_t clk32() { uint32_t c; asm volatile("mov.u32 %0, %%clock;" : "=r"(c) :: "memory"); return c; }
__device__ __forceinline__ void wait_ns(uint32_t t) { while ((int)(now_ns() - t) < 0) {} }
__device__ __forceinline__ void wait_clk(uint32_t t) { while ((int)(clk32() - t) < 0) {} }
__device__ __forceinline__ bool elect_one() {
    uint32_t e;
    asm volatile("{\n.reg .pred p;\nelect.sync _|p, 0xffffffff;\nselp.u32 %0, 1, 0, p;\n}" : "=r"(e));
    return e;
}
constexpr uint64_t POL_FIRST = 0x12F0000000000000ull, POL_NORMAL = 0x1000000000000000ull;
__device__ __forceinline__ void tma_tile(uint32_t dst, const CUtensorMap* tm, int group, uint32_t bar, uint64_t pol) {
    asm volatile("cp.async.bulk.tensor.4d.shared::cluster.global.mbarrier::complete_tx::bytes.L2::cache_hint"
                 " [%0], [%1, {%3, %3, %3, %4}], [%2], %5;"
                 ::"r"(dst), "l"(tm), "r"(bar), "r"(0), "r"(group), "l"(pol) : "memory");
}
__device__ __forceinline__ void tma2d(uint32_t dst, const CUtensorMap* tm, int x, int y, uint32_t bar) {
    asm volatile("cp.async.bulk.tensor.2d.shared::cluster.global.mbarrier::complete_tx::bytes [%0], [%1, {%3, %4}], [%2];"
                 ::"r"(dst), "l"(tm), "r"(bar), "r"(x), "r"(y) : "memory");
}
__device__ __forceinline__ void bulk_load(uint32_t dst, const void* src, uint32_t bytes, uint32_t bar) {
    asm volatile("cp.async.bulk.shared::cluster.global.mbarrier::complete_tx::bytes [%0], [%1], %2, [%3];"
                 ::"r"(dst), "l"(src), "r"(bytes), "r"(bar) : "memory");
}
__device__ __forceinline__ void l2_prefetch(const void* p, uint32_t bytes) {
    asm volatile("cp.async.bulk.prefetch.L2.global [%0], %1;" ::"l"(p), "r"(bytes) : "memory");
}
__device__ __forceinline__ void mma16816(float (&c)[4], uint32_t a0, uint32_t a1, uint32_t a2, uint32_t a3, uint32_t b0, uint32_t b1) {
    asm volatile("mma.sync.aligned.m16n8k16.row.col.f32.bf16.bf16.f32 {%0,%1,%2,%3}, {%4,%5,%6,%7}, {%8,%9}, {%0,%1,%2,%3};"
                 : "+f"(c[0]), "+f"(c[1]), "+f"(c[2]), "+f"(c[3]) : "r"(a0), "r"(a1), "r"(a2), "r"(a3), "r"(b0), "r"(b1));
}
__device__ __forceinline__ void mma1688(float (&c)[4], uint32_t a0, uint32_t a1, uint32_t b0) {
    asm volatile("mma.sync.aligned.m16n8k8.row.col.f32.bf16.bf16.f32 {%0,%1,%2,%3}, {%4,%5}, {%6}, {%0,%1,%2,%3};"
                 : "+f"(c[0]), "+f"(c[1]), "+f"(c[2]), "+f"(c[3]) : "r"(a0), "r"(a1), "r"(b0));
}
__device__ __forceinline__ void ldsm4(uint32_t (&r)[4], uint32_t a) {
    asm volatile("ldmatrix.sync.aligned.m8n8.x4.shared.b16 {%0,%1,%2,%3}, [%4];"
                 : "=r"(r[0]), "=r"(r[1]), "=r"(r[2]), "=r"(r[3]) : "r"(a) : "memory");
}
__device__ __forceinline__ void ldsm4t(uint32_t (&r)[4], uint32_t a, uint32_t& zero) {
    asm volatile("ldmatrix.sync.aligned.m8n8.x4.trans.shared.b16 {%0,%1,%2,%3}, [%4];"
                 : "=r"(r[0]), "=r"(r[1]), "=r"(r[2]), "=r"(r[3]) : "r"(a + zero) : "memory");
    zero &= r[3];
}
__device__ __forceinline__ uint4 ld_pkt(const void* p) {
    uint4 v;
    asm volatile("{\n.reg .b128 t;\nld.relaxed.gpu.global.b128 t, [%4];\nmov.b128 {%0,%1,%2,%3}, t;\n}"
                 : "=r"(v.x), "=r"(v.y), "=r"(v.z), "=r"(v.w) : "l"(p) : "memory");
    return v;
}
__device__ __forceinline__ void st_pkt(const void* p, uint32_t a, uint32_t b, uint32_t c, uint32_t d) {
    asm volatile("{\n.reg .b128 t;\nmov.b128 t, {%1,%2,%3,%4};\nst.relaxed.gpu.global.b128 [%0], t;\n}"
                 ::"l"(p), "r"(a), "r"(b), "r"(c), "r"(d) : "memory");
}
__device__ __forceinline__ uint2 ld_pkt8(const void* p) {
    uint2 v;
    asm volatile("{\n.reg .b64 t;\nld.relaxed.gpu.global.b64 t, [%2];\nmov.b64 {%0,%1}, t;\n}" : "=r"(v.x), "=r"(v.y) : "l"(p) : "memory");
    return v;
}
__device__ __forceinline__ void red_cell(const char* p, float a, float b, float c) {
    asm volatile("red.relaxed.gpu.global.add.v4.f32 [%0], {%1,%2,%3,%4};" ::"l"(p), "f"(a), "f"(b), "f"(c), "f"(1.0f) : "memory");
}
#define PRED(n) "{\n.reg .pred p;\nsetp.ne.u32 p, %" #n ", 0;\n"
__device__ __forceinline__ void red_cell2_if(bool on, const char* p, float a, float b, float c) {
    asm volatile(PRED(5) "@p red.relaxed.gpu.global.add.v4.f32 [%0], {%1,%2,%3,%4};\n@p red.relaxed.gpu.global.add.v4.f32 [%0+4096], {%1,%2,%3,%4};\n}"
                 ::"l"(p), "f"(a), "f"(b), "f"(c), "f"(1.0f), "r"((uint32_t)on) : "memory");
}
__device__ __forceinline__ void st_pkt82_if(bool on, const void* p, uint32_t a, uint32_t b) {
    asm volatile(PRED(3) ".reg .b64 t;\nmov.b64 t, {%1,%2};\n@p st.relaxed.gpu.global.b64 [%0], t;\n@p st.relaxed.gpu.global.b64 [%0+4096], t;\n}"
                 ::"l"(p), "r"(a), "r"(b), "r"((uint32_t)on) : "memory");
}
__device__ __forceinline__ void st_pkt2_if(bool on, const void* p, uint32_t a, uint32_t b, uint32_t c, uint32_t d) {
    asm volatile(PRED(5) ".reg .b128 t;\nmov.b128 t, {%1,%2,%3,%4};\n@p st.relaxed.gpu.global.b128 [%0], t;\n@p st.relaxed.gpu.global.b128 [%0+4096], t;\n}"
                 ::"l"(p), "r"(a), "r"(b), "r"(c), "r"(d), "r"((uint32_t)on) : "memory");
}
__device__ __forceinline__ void mbar_arrive_if(bool on, uint32_t a) {
    asm volatile(PRED(1) "@p mbarrier.arrive.shared::cta.b64 _, [%0];\n}" ::"r"(a), "r"((uint32_t)on) : "memory");
}
__device__ __forceinline__ void sts16_if(bool on, uint32_t a, uint32_t v) {
    asm volatile(PRED(2) "@p st.shared.u16 [%0], %1;\n}" ::"r"(a), "h"((unsigned short)v), "r"((uint32_t)on) : "memory");
}
__device__ __forceinline__ void sts32_if(bool on, uint32_t a, uint32_t v) {
    asm volatile(PRED(2) "@p st.shared.u32 [%0], %1;\n}" ::"r"(a), "r"(v), "r"((uint32_t)on) : "memory");
}
__device__ __forceinline__ void sts128_if(bool on, uint32_t a, uint32_t x, uint32_t y, uint32_t z, uint32_t w) {
    asm volatile(PRED(5) "@p st.shared.v4.u32 [%0], {%1,%2,%3,%4};\n}" ::"r"(a), "r"(x), "r"(y), "r"(z), "r"(w), "r"((uint32_t)on) : "memory");
}
__device__ __forceinline__ float fast_rcp(float x) { float r; asm("rcp.approx.ftz.f32 %0, %1;" : "=f"(r) : "f"(x)); return r; }
__device__ __forceinline__ float fast_sqrt(float x) { float r; asm("sqrt.approx.ftz.f32 %0, %1;" : "=f"(r) : "f"(x)); return r; }
__device__ __forceinline__ float fast_ex2(float x) { float r; asm("ex2.approx.ftz.f32 %0, %1;" : "=f"(r) : "f"(x)); return r; }
__device__ __forceinline__ uint32_t pack2(float lo, float hi) {
    uint32_t r;
    asm("cvt.rn.bf16x2.f32 %0, %1, %2;" : "=r"(r) : "f"(hi), "f"(lo));
    return r;
}
__device__ __forceinline__ float bfr(float x) { return __uint_as_float(pack2(0.f, x)); }
__device__ __forceinline__ uint32_t badd2(uint32_t a, uint32_t b) { uint32_t r; asm("add.rn.bf16x2 %0, %1, %2;" : "=r"(r) : "r"(a), "r"(b)); return r; }
__device__ __forceinline__ uint32_t bsub2(uint32_t a, uint32_t b) { uint32_t r; asm("sub.rn.bf16x2 %0, %1, %2;" : "=r"(r) : "r"(a), "r"(b)); return r; }
__device__ __forceinline__ uint32_t bmul2(uint32_t a, uint32_t b) { uint32_t r; asm("mul.rn.bf16x2 %0, %1, %2;" : "=r"(r) : "r"(a), "r"(b)); return r; }
__device__ __forceinline__ float bf_lo(uint32_t w) { return __uint_as_float(w << 16); }
__device__ __forceinline__ float bf_hi(uint32_t w) { return __uint_as_float(w & 0xffff0000u); }
__device__ __forceinline__ float F(uint32_t t) { return __uint_as_float(t); }
__device__ __forceinline__ uint32_t lds16(uint32_t a) { unsigned short h; asm volatile("ld.shared.u16 %0, [%1];" : "=h"(h) : "r"(a) : "memory"); return h; }
__device__ __forceinline__ uint32_t lds32(uint32_t a) { uint32_t v; asm volatile("ld.shared.u32 %0, [%1];" : "=r"(v) : "r"(a) : "memory"); return v; }
__device__ __forceinline__ uint2 lds64(uint32_t a) {
    uint2 v; asm volatile("ld.shared.v2.u32 {%0,%1}, [%2];" : "=r"(v.x), "=r"(v.y) : "r"(a) : "memory"); return v;
}
__device__ __forceinline__ uint4 lds128(uint32_t a) {
    uint4 v; asm volatile("ld.shared.v4.u32 {%0,%1,%2,%3}, [%4];" : "=r"(v.x), "=r"(v.y), "=r"(v.z), "=r"(v.w) : "r"(a) : "memory"); return v;
}
__device__ __forceinline__ float sum8(const uint4& u, const uint4& v) {
    return ((F(u.x) + F(u.y)) + (F(u.z) + F(u.w))) + ((F(v.x) + F(v.y)) + (F(v.z) + F(v.w)));
}
__device__ __forceinline__ void sts16(uint32_t a, uint32_t v) { asm volatile("st.shared.u16 [%0], %1;" ::"r"(a), "h"((unsigned short)v) : "memory"); }
__device__ __forceinline__ void sts32(uint32_t a, uint32_t v) { asm volatile("st.shared.u32 [%0], %1;" ::"r"(a), "r"(v) : "memory"); }
__device__ __forceinline__ void stsf(uint32_t a, float v) { asm volatile("st.shared.f32 [%0], %1;" ::"r"(a), "f"(v) : "memory"); }
__device__ __forceinline__ void stsf2(uint32_t a, float x, float y) { asm volatile("st.shared.v2.f32 [%0], {%1,%2};" ::"r"(a), "f"(x), "f"(y) : "memory"); }
__device__ __forceinline__ void stsf4(uint32_t a, float x, float y, float z, float w) {
    asm volatile("st.shared.v4.f32 [%0], {%1,%2,%3,%4};" ::"r"(a), "f"(x), "f"(y), "f"(z), "f"(w) : "memory");
}
template <int ID, int N> __device__ __forceinline__ void bar_sync() { asm volatile("bar.sync %0, %1;" ::"n"(ID), "n"(N) : "memory"); }
template <int ID, int N> __device__ __forceinline__ void bar_arrive() { asm volatile("bar.arrive %0, %1;" ::"n"(ID), "n"(N) : "memory"); }
__device__ __forceinline__ void fence_async() { asm volatile("fence.proxy.async.shared::cta;" ::: "memory"); }
__device__ __forceinline__ float shx(float v, int m) { return __shfl_xor_sync(0xffffffffu, v, m); }
__device__ __forceinline__ float shi(float v, int l) { return __shfl_sync(0xffffffffu, v, l); }
__device__ __forceinline__ uint32_t shi(uint32_t v, int l) { return __shfl_sync(0xffffffffu, v, l); }
__device__ __forceinline__ uint32_t opaque(uint32_t x) { asm volatile("mov.u32 %0, %0;" : "+r"(x)); return x; }
__device__ __forceinline__ const char* opaque(const char* x) { asm volatile("mov.u64 %0, %0;" : "+l"(x)); return x; }
constexpr float LOG2E = 1.4426950408889634f, SCALE = 0.07216878364870322f;

#define TRACE(idx) do {} while (0)
#define TRACES(slot) do {} while (0)

__device__ __forceinline__ uint32_t probe_near(const Params& p, int w, int lane) {
    const int cta = blockIdx.x;
    const char* pr = p.scr + SCR_PROBE + (cta & 31) * 128 + (cta >> 5) * 16384 + ((w & 1) << 6 | (w & 2) << 17 | (w & 4) << 18);
    st_pkt2_if(lane < 2, pr + lane * 16, 0, 0, 0, 0);
    uint32_t best0 = ~0u, best1 = ~0u;
#pragma unroll 1
    for (int i = w & 1; i < 6 + (w & 1); i++) {
        uint32_t c = clk32(), v = 0;
        if (lane == 0) asm volatile("atom.relaxed.gpu.global.add.u32 %0, [%1], 1;" : "=r"(v) : "l"(pr + (i & 1) * HALF) : "memory");
        c += __shfl_sync(0xffffffffu, v, 0) >> 16;
        c = clk32() - c;
        if (i & 1) best1 = min(best1, c); else best0 = min(best0, c);
    }
    return min(best0, 0xffffu) | min(best1, 0xffffu) << 16;
}
__device__ __forceinline__ uint32_t near_half() {
    const uint4 a = lds128(SM_NEAR), b = lds128(SM_NEAR + 16);
    const uint32_t m = __vminu2(__vminu2(__vminu2(a.x, a.y), __vminu2(a.z, a.w)), __vminu2(__vminu2(b.x, b.y), __vminu2(b.z, b.w)));
    return ((m & 0xffffu) < m >> 16) != (CFG(FLIP) != 0) ? HALF : 0;
}

__device__ __forceinline__ int kv_group(int k, int t) {
    const int cta = blockIdx.x;
    return ((k * NHEAD + (cta >> 2)) * SK + (SK - WIN) + (cta & 3) * 256 + t * 32) / 8;
}
__device__ __forceinline__ uint32_t phase_ns() { return (((blockIdx.x >> 2) * 13) & 31) * CFG(STAG) / 32; }

__device__ __forceinline__ void ln_fast(float s, float q, float& mean, float& rstd) {
    mean = s * (1.f / DM);
    asm("rsqrt.approx.ftz.f32 %0, %1;" : "=f"(rstd) : "f"(fmaxf(fmaf(-mean, mean, fmaf(q, 1.f / DM, 1e-5f)), 1e-5f)));
}
__device__ __forceinline__ void q_role(const Params& p, int lane) {
    const int cta = blockIdx.x;
    mbar_wait(bar_at(B_EP), 0);
    const uint32_t tag0 = lds32(SM_EPOCH) * NB;
    const char* const qbox = p.scr + SCR_Q + head_off(cta >> 2) + lane * 8;
    const uint32_t near = head_near(cta >> 2, near_half());
    float cs0 = 0.f, cs1 = 0.f;
#pragma unroll 1
    for (int r = 0; r <= 2 * NB; r++) {
        const int slot = min(r, NB), k = r - NB;
        const uint32_t tag = tag0 + (r < NB ? r : k - 1);
        const char* const dst = qbox + slot * 768 + (cta & 3) * 192;
        const char* const src = qbox + slot * 768 + near;
        bar_sync<3, 288>();
        const uint32_t ra = SM_PQ + lane * 16;
        float S0 = sum8(lds128(ra), lds128(ra + 1024)), S1 = sum8(lds128(ra + 512), lds128(ra + 1536));
        if (k > 0) {
            float mean, rstd;
            ln_fast(shi(S1, 24), shi(S0, 24), mean, rstd);
            S0 = fmaf(-mean, cs0, S0) * rstd;
            S1 = fmaf(-mean, cs1, S1) * rstd;
        } else {
            bar_arrive<7, 288>();
            if (k == 0) { cs0 = S0; cs1 = S1; continue; }
        }
        st_pkt82_if(lane < 24, dst, pack2(S0, S1), tag);
        TRACES(k > 0 ? (k - 1) * 12 + 5 : 95);
        if (r < NB - 1) continue;
#pragma unroll 1
        for (int back = k < 0 ? NB - 1 : 0; back >= 0; back--) {
            const char* const from = src - back * 768;
            const uint32_t want = tag - back, qd = SM_Q + (slot - back) * 384 + lane * 4;
            uint2 a, b, c;
            SPIN_DECL;
            do {
                a = ld_pkt8(from); b = ld_pkt8(from + 256); c = ld_pkt8(from + 512);
                SPIN_CHECK(slot);
                sts32(qd, a.x); sts32(qd + 128, b.x); sts32(qd + 256, c.x);
            } while (__any_sync(0xffffffffu, a.y != want || b.y != want || c.y != want));
        }
        mbar_arrive(bar_at(B_QR));
    }
}

struct Maps { CUtensorMap k, v, q, o, g, u; };
__device__ __forceinline__ void load_role(const Params& p, const CUtensorMap* tmKV, int lane, uint32_t t0) {
    const int cta = blockIdx.x;
    t0 += phase_ns();
#pragma unroll 1
    for (int i = 1; i < 5; i++) {
        wait_ns(t0 + i * CFG(TICK0));
        if (elect_one()) l2_prefetch(p.wq + (size_t)(128 * i + cta) * 12288, 12288);
    }
    uint32_t plan[2];
#pragma unroll
    for (int i = 0; i < 2; i++) {
        const int j = lane + 32 * i, k = j >> 4, t = j & 15, u = t >> 1, jw = j - CFG(WIN);
        const int sb = k == 0 ? B_WC + (t >= 8) + (t >= 14) : t >= 12 ? B_RK + u - 5 : t >= 4 ? B_RR + t - 4 : t >= 2 ? B_RP : k > 1 ? B_RK + 3 : B_RR + t;
        const uint32_t sw = sb * 8 | (j < 18 ? 0 : (t >= 12 || u == 1 ? k - 1 : k) & 1) << 9;
        plan[i] = sw | (jw < 0 ? sw : (B_F1 + (jw & 15)) * 8 | ((jw >> 4) & 1) << 9) << 10 |
                  (slot_at(slots(k), t < 8 ? pass_nibble(k, u) : u) * 2 + (t & 1)) << 20 | (t < 10 && j >= 8 && j < 56) << 25;
    }
    bar_sync<6, 64>();
    wait_ns(t0 + kb_ns(60));
    if (elect_one()) bulk_load(ST_WD, p.wd + cta * 15360, 15360, bar_at(B_W));
#pragma unroll 1
    for (int i = 0; i < 5; i++) {
        wait_ns(t0 + kb_ns(75) + i * kb_ns(6));
        if (elect_one()) { l2_prefetch(p.wg + (128 * i + cta) * 3072, 3072); l2_prefetch(p.wu + (128 * i + cta) * 3072, 3072); }
    }
#pragma unroll 1
    for (int i = 0; i < 6; i++) {
        wait_ns(t0 + kb_ns(105) + min(i, 4) * kb_ns(10));
        if (elect_one()) l2_prefetch(p.wo + (size_t)((cta >> 2) * DH + 32 * i + 8 * (cta & 3)) * 1280, 10240);
    }
    t0 += batch_ns(0);
    int jp = 0, shift = 0;
    uint32_t earliest = t0;
    auto requested = [&](uint32_t now) {
        shift = max(max(shift - CFG(GAIN), 0), (int)(now - t0) - (jp < 12 ? CFG(LMAX0) : CFG(LMAX)));
        TRACE(128 + jp);
        t0 += tick_ns(++jp);
    };
    const int grp0 = kv_group(0, 0);
    auto group = [&](int j) { return grp0 + (j >> 4) * (NHEAD * SK / 8) + (j & 7) * 4; };
#pragma unroll 1
    for (int j = 0; j < 16 * NB; j++) {
        const uint32_t pl = __shfl_sync(0xffffffffu, j & 32 ? plan[1] : plan[0], j);
        const int jmax = min(j + CFG(PMAX), 16 * NB);
        uint32_t now;
        SPIN_DECL;
        while (true) {
            const bool ok = mbar_test2(SM_BAR + (pl & 511), (pl >> 9) & 1, SM_BAR + ((pl >> 10) & 511), (pl >> 19) & 1);
            now = now_ns();
            const int late = now - t0 - shift;
            if (ok && (jp > j ? (int)(now - earliest) : late) >= 0) break;
            if (late >= (jp > j ? 0 : CFG(PGRACE)) && jp < jmax) {
                if (elect_one())
                    asm volatile("cp.async.bulk.prefetch.tensor.4d.L2.global [%0, {%1, %1, %1, %2}];" ::"l"(tmKV + ((jp >> 3) & 1)), "r"(0), "r"(group(jp)) : "memory");
                requested(now);
            }
            SPIN_CHECK(j);
        }
        if (elect_one()) {
            mbar_expect_tx(bar_at(B_F1 + (j & 15)), TILE);
            tma_tile(SB + ((pl >> 20) & 31) * TILE, tmKV + ((j >> 3) & 1), group(j), bar_at(B_F1 + (j & 15)), pl >> 25 ? POL_NORMAL : POL_FIRST);
        }
        TRACE(256 + j);
        earliest = now + CFG(VSTEP);
        if (jp == j) requested(now);
    }
}

__device__ __forceinline__ void reload_role(const Params& p, const Maps* tm, uint32_t t0) {
    const CUtensorMap* const tmK = &tm->k;
    const CUtensorMap* const tmV = &tm->v;
    const int cta = blockIdx.x;
    t0 += CFG(TICK0) + CFG(WLAG) + phase_ns();
#pragma unroll 1
    for (int i = 0; i < 5; i++) {
        wait_ns(t0 + i * CFG(TICK0));
        if (elect_one()) tma2d(ST_WQ + i * 12288, &tm->q, 48 * cta, 128 * i, bar_at(B_W));
        if (i == 1) bar_sync<5, 480>();
    }
#pragma unroll 1
    for (int i = 0, o = 0; i < 10;) {
        const uint32_t now = now_ns() - t0;
        if (o < 6 && (int)now >= kb_ns(105) + o * kb_ns(10)) {
            if (elect_one()) tma2d(ST_WO + o * 10240, &tm->o, 160 * (cta & 3), (cta >> 2) * DH + 32 * o, bar_at(B_W + 1));
            o++;
        } else if ((int)now >= kb_ns(77) + i * CFG(GSTEP) && (i < 9 || o == 6)) {
            if (elect_one()) tma2d(ST_WG + (i & 1) * 20480 + (i >> 1) * 4096, i & 1 ? &tm->u : &tm->g, (12 * cta) & ~7, 128 * (i >> 1), bar_at(B_W + 2));
            i++;
        }
    }
#pragma unroll 1
    for (int k = 0; k < NB - 1; k++) {
        mbar_wait(bar_at(B_RK), k & 1);
        if (elect_one()) {
            const uint32_t dst = SB + slot_at(slots(k), 0) * PAIR;
            mbar_expect_tx(bar_at(B_FL), PAIR);
            tma_tile(dst, tmV, kv_group(k, 0), bar_at(B_FL), POL_FIRST);
            tma_tile(dst + TILE, tmV, kv_group(k, 1), bar_at(B_FL), POL_FIRST);
        }
        mbar_wait(bar_at(B_RV), k & 1);
        uint32_t due = now_ns() + (k == NB - 2 ? 0 : CFG(RLAG));
        if (elect_one()) mbar_expect_tx(bar_at(B_F3), 4 * PAIR);
#pragma unroll 1
        for (int t = 0; t < 8; t++) {
            wait_ns(due);
            due += k == NB - 2 ? CFG(RSTEP3) : CFG(RSTEP);
            if (elect_one())
                tma_tile(SB + slot_at(slots(k + 1), t >> 1) * PAIR + (t & 1) * TILE, tmK, kv_group(k + 1, t), bar_at(B_F3), POL_FIRST);
        }
        TRACE(121 + k);
    }
}

__device__ __forceinline__ void zero_role(const Params& p, int lane, unsigned ticket, uint32_t t0) {
    const int cta = blockIdx.x;
    const uint32_t epoch = __shfl_sync(0xffffffffu, ticket, 0) / NCTA + 1;
    if (lane == 0) { sts32(SM_EPOCH, epoch); mbar_arrive(bar_at(B_EP)); }
    mbar_wait(bar_at(B_EP), 0);
#pragma unroll 1
    for (int k = 0; k < NB + 2; k++) {
        lane = opaque(lane);
        const int cl = 2 * (cta & 15) + (lane & 1);
        const int col = 80 * (cta >> 4) + (cl & 2 ? 48 : 0) + (cl >> 2) + (cl & 1 ? 8 : 0);
        const char* own = p.scr + (cl >> 2) * 256 + (cl & 3) * 16;
        if (k < NB) {
            const int lg = lane >> 3, ty = (lane & 7) >> 1;
            const char* dst = own + acc_off((k - (lg >> 1)) & 3, lg != 0, cta >> 4) + ty * HALF;
            uint32_t v0 = 0, v1 = 0, v2 = 0;
            if (lane < 4) {
                const unsigned short* xp = p.x + k * DM + col;
                v0 = __ldg(xp) << 16; v1 = __ldg(xp + 16) << 16; v2 = cl & 2 ? 0 : __ldg(xp + 32) << 16;
            }
            wait_ns(t0 + batch_ns(k) + CFG(ZTILE) * CFG(TICK0));
            if (lg == 0 || (lg == 1 && (ty < 2 || k == NB - 1)) || (lg == 2 && k > 0 && ty > 1)) {
                st_pkt(dst, v0, v1, v2, 0);
                asm volatile("atom.relaxed.gpu.global.add.f32 %0, [%1+12], %2;" : "=r"(v0) : "l"(dst), "f"(lane < 4 ? 1.f : 0.f) : "memory");
            }
            if (__any_sync(0xffffffffu, v0 != 0)) __trap();
            const char* cnt = p.scr + SCR_COUNT;
            if (lane < 2) asm volatile("red.relaxed.gpu.global.add.u32 [%0], 1;" ::"l"(cnt + lane * HALF) : "memory");
            const uint32_t target = ((epoch - 1) * NB + k + 1) * NCTA;
            cnt += near_half();
            SPIN_DECL;
            uint32_t v;
            do {
                __nanosleep(100);
                asm volatile("ld.relaxed.gpu.global.u32 %0, [%1];" : "=r"(v) : "l"(cnt) : "memory");
                SPIN_CHECK(v);
            } while (__any_sync(0xffffffffu, (int)(v - target) < 0));
        }
        uint4 r;
        if (k == 1) mbar_wait(bar_at(B_RK), 0);
        if (k > 1) {
            mbar_wait(bar_at(B_FIN), k & 1);
            r = lds128(SM_FIN + (lane & 1) * 16);
        }
        __syncwarp();
        if (lane == 0) mbar_arrive(bar_at(B_Z));
        if (k > 1) {
            const int b = k - 2;
            const char* src = own + acc_off(b, 1, cta >> 4) + (2 + ((lane >> 1) & 1)) * HALF;
            unsigned short* o = p.out + b * DM + col + (lane >> 2) * 16;
            const bool on = !(lane & 2) && lane < (cl & 2 ? 8 : 12);
            wait_clk(clk32() + CFG(DLY_F));
            float cnt;
            SPIN_DECL;
            do {
                const uint4 v = ld_pkt(src);
                SPIN_CHECK(k);
                cnt = F(v.w) + shx(F(v.w), 2);
                const float y0 = F(v.x) + shx(F(v.x), 2), y1 = F(v.y) + shx(F(v.y), 2), y2 = F(v.z) + shx(F(v.z), 2);
                const uint32_t x01 = badd2(r.x, badd2(r.y, bmul2(pack2(y0, y1), r.w)));
                const uint32_t x2 = badd2(r.z, badd2(r.z >> 16, bmul2(pack2(y2, 0.f), r.w)));
                if (cnt == NCTA && on) *o = lane < 4 ? x01 : lane < 8 ? x01 >> 16 : x2;
            } while (__any_sync(0xffffffffu, cnt != NCTA));
            TRACES((2 * b + 1) * 6 + 4);
        }
    }
}

__host__ __device__ constexpr uint32_t desc_lo(uint32_t addr) { return ((addr & 0x3FFFFu) >> 4) | (1u << 16); }
constexpr uint32_t DESC_HI_TILE = (3072u >> 4) | (1u << 30);
constexpr uint32_t DESC_HI_VEC = 1u;
template <int TA, int AOFF, int BOFF>
__device__ __forceinline__ void wgmma_n8(float (&d)[4], uint32_t alo, uint32_t blo, int accumulate) {
    asm volatile("{\n.reg .pred p;\n.reg .b32 a, b;\n.reg .b64 da, db;\nsetp.ne.b32 p, %6, 0;\n"
                 "add.u32 a, %4, %8;\nadd.u32 b, %5, %9;\nmov.b64 da, {a, %10};\nmov.b64 db, {b, %11};\n"
                 "wgmma.mma_async.sync.aligned.m64n8k16.f32.bf16.bf16 {%0,%1,%2,%3}, da, db, p, 1, 1, %7, 0;\n}"
                 : "+f"(d[0]), "+f"(d[1]), "+f"(d[2]), "+f"(d[3])
                 : "r"(alo), "r"(blo), "r"(accumulate), "n"(TA), "n"(AOFF >> 4), "n"(BOFF >> 4), "n"(DESC_HI_TILE), "n"(DESC_HI_VEC));
}
template <int KS, int END>
__device__ __forceinline__ void qk_steps(float (&d)[4], uint32_t alo, uint32_t blo) {
    if constexpr (KS < END) {
        wgmma_n8<0, (KS >> 2) * 1024 + (KS & 3) * 32, KS * 32>(d, alo, blo, KS > 0);
        qk_steps<KS + 1, END>(d, alo, blo);
    }
}
__device__ __forceinline__ void pv_steps(float (&e)[3][4], uint32_t alo, uint32_t blo, int acc) {
    wgmma_n8<1, 0, 0>(e[0], alo, blo, acc); wgmma_n8<1, 1024, 0>(e[1], alo, blo, acc); wgmma_n8<1, 2048, 0>(e[2], alo, blo, acc);
    wgmma_n8<1, 6144, 32>(e[0], alo, blo, 1); wgmma_n8<1, 7168, 32>(e[1], alo, blo, 1); wgmma_n8<1, 8192, 32>(e[2], alo, blo, 1);
}
__device__ __forceinline__ void wg_fence() { asm volatile("wgmma.fence.sync.aligned;" ::: "memory"); }
__device__ __forceinline__ void wg_commit() { asm volatile("wgmma.commit_group.sync.aligned;" ::: "memory"); }
template <int N> __device__ __forceinline__ void wg_wait() { asm volatile("wgmma.wait_group.sync.aligned %0;" ::"n"(N) : "memory"); }
__device__ __forceinline__ void acc_ready(float (&d)[4]) { asm volatile("" : "+f"(d[0]), "+f"(d[1]), "+f"(d[2]), "+f"(d[3]) :: "memory"); }
__device__ __forceinline__ uint32_t score_pair(float (&d)[4], int lane) {
    acc_ready(d);
    const uint32_t r = pack2(d[0], d[2]);
    return shi(pack2(bf_lo(r) * SCALE, bf_hi(r) * SCALE), lane & 28);
}

__device__ __forceinline__ void attention_role(const Params& p, int w, int lane) {
    const int cta = blockIdx.x, t4 = lane & 3, g = lane >> 2;
    mbar_wait(bar_at(B_EP), 0);
    const uint32_t tag0 = lds32(SM_EPOCH) * NB;
    const char* const odst = p.scr + SCR_O + head_off(cta >> 2) + (2 * w + (g >> 2)) * 256 + (cta & 3) * 64 + (g & 3) * 16;
    const uint32_t pdst = SM_P + t4 * PSTR + (16 * w + g) * 2;
    auto softmax = [&](uint32_t sc, int ps) -> uint32_t {
        const float s0 = bf_lo(sc), s1 = bf_hi(sc);
        int key = __float_as_int(fmaxf(s0, s1));
        key ^= (key >> 31) & 0x7fffffff;
        key = __reduce_max_sync(0xffffffffu, key);
        sts32(SM_MAX + w * 4, key);
        bar_sync<4, 128>();
        const uint4 mx = lds128(SM_MAX);
        key = max(max((int)mx.x, (int)mx.y), max((int)mx.z, (int)mx.w));
        key ^= (key >> 31) & 0x7fffffff;
        const float mb = __int_as_float(key) * LOG2E;
        const uint32_t pp = pack2(fast_ex2(fmaf(s0, LOG2E, -mb)), fast_ex2(fmaf(s1, LOG2E, -mb)));
        sts16(pdst + ps * 4 * PSTR, pp); sts16(pdst + ps * 4 * PSTR + 16, pp >> 16);
        uint32_t fs;
        asm volatile("redux.sync.add.u32 %0, %1, 0xffffffff;" : "=r"(fs) : "r"(__float2uint_rn((bf_lo(pp) + bf_hi(pp)) * 8388608.f)));
        fence_async();
        bar_sync<4, 128>();
        sts32(SM_SUM + ps * 16 + w * 4, fs);
        return key;
    };
    auto aux_word = [&](uint32_t mx, const uint4& u, int k) {
        const float l = __uint2float_rn((u.x + u.y) + (u.z + u.w)) * (1.f / 8388608.f);
        return (g < 4 ? mx : (__float_as_uint(l) + 0x80u) & 0xffffff00u) | ((tag0 + k) & 0xffu);
    };
    auto send = [&](float (&e)[3][4], uint32_t aux, int ps) {
        acc_ready(e[0]); acc_ready(e[1]); acc_ready(e[2]);
        const uint32_t o0 = pack2(e[0][0], e[0][2]), o1 = pack2(e[1][0], e[1][2]), o2 = pack2(e[2][0], e[2][2]);
        st_pkt2_if(t4 == 0, odst + ps * 2048, o0, o1, o2, aux);
        mbar_arrive_if(lane == 0, bar_at(ps ? B_RV : B_PS));
    };
    mbar_wait(bar_at(B_QR), 0);
    TRACES(73);
#pragma unroll 1
    for (int it = 0; it <= NB; it++) {
        uint32_t m1 = 0;
        if (it < NB) {
            const uint32_t tab = slots(it);
            const uint32_t ka = SB + (2 * w + ((lane >> 3) & 1)) * 3072 + (lane & 7) * 128 + (((lane >> 4) ^ (lane & 7)) << 4);
            const uint32_t qa = SM_Q + it * 384 + (lane >> 3) * 16;
            uint32_t sc = 0;
#pragma unroll 1
            for (int u = 0; u < 4; u++) {
                const uint32_t base = ka + slot_at(tab, pass_nibble(it, u)) * PAIR;
                mbar_wait(bar_at(B_F1 + 2 * u + (w >> 1)), it & 1);
                float d0[4] = {}, d1[4] = {};
#pragma unroll
                for (int c = 0; c < 6; c++) {
                    uint32_t a0[4], a1[4], b[4];
                    ldsm4(b, qa + c * 64);
                    ldsm4(a0, (base ^ ((c & 1) * 64)) + (c >> 1) * 1024);
                    ldsm4(a1, (base ^ ((c & 1) * 64 + 32)) + (c >> 1) * 1024);
                    mma16816(d0, a0[0], a0[1], a0[2], a0[3], b[0], b[1]);
                    mma16816(d1, a1[0], a1[1], a1[2], a1[3], b[2], b[3]);
                }
                const uint32_t r = pack2(d0[0] + d1[0], d0[2] + d1[2]);
                mbar_arrive_if(lane == 0, bar_at(B_RR + 2 * u + (w >> 1)));
                if (t4 == u) sc = pack2(bf_lo(r) * SCALE, bf_hi(r) * SCALE);
            }
            m1 = softmax(sc, 0);
        }
        if (it > 0) {
            const int k = it - 1;
            const uint32_t tab = slots(k);
            const uint32_t v0 = slot_at(tab, k < NB - 1 ? 0 : 4);
            TRACES(48 + k * 6);
            if (k > 0) mbar_wait(bar_at(B_F3), it & 1);
            mbar_wait(bar_at(B_QR), it & 1);
            fence_async();
            TRACES(49 + k * 6);
            float d[4][4] = {};
#pragma unroll
            for (int u = 0; u < 4; u++) {
                const uint32_t alo = desc_lo(SB) + slot_at(tab, u) * (PAIR >> 4), blo = desc_lo(SM_Q + 4 * 384);
                wg_fence();
                qk_steps<0, 6>(d[u], alo, blo);
                wg_commit();
                wg_wait<1>();
                if (u > 0) mbar_arrive_if(lane == 0, bar_at(B_RK + u - 1));
                wg_fence();
                qk_steps<6, 12>(d[u], alo, blo);
                wg_commit();
                if (u < 3) wg_wait<1>();
            }
            uint32_t sc = score_pair(d[0], lane), s = score_pair(d[1], lane);
            if (t4 == 1) sc = s;
            s = score_pair(d[2], lane);
            if (t4 == 2) sc = s;
            wg_wait<0>();
            s = score_pair(d[3], lane);
            mbar_arrive_if(lane == 0, bar_at(B_RK + 3));
            if (t4 == 3) sc = s;
            TRACES(50 + k * 6);
            const uint32_t m2 = softmax(sc, 1);
            TRACES(51 + k * 6);
            float e[3][4] = {};
            uint4 u;
#pragma unroll
            for (int t = 0; t < 8; t++) {
                const int pr = ((t >> 1) + 1) & 3;
                if (t == 6 && k < NB - 1) mbar_wait(bar_at(B_FL), k & 1);
                if (t == 7) { bar_sync<4, 128>(); u = lds128(SM_SUM + 16); }
                wg_fence();
                pv_steps(e, desc_lo(SB + (t & 1) * TILE) + (pr ? slot_at(tab, 4 + pr) : v0) * (PAIR >> 4), desc_lo(SM_P + (4 + pr) * PSTR + (t & 1) * 64), t > 0);
                wg_commit();
                if (t < 7) wg_wait<1>();
                if (t == 0) st_pkt2_if(t4 == 0, odst + 2048, 0, 0, 0, tag0 + k + 128);
            }
            const uint32_t aux = opaque(aux_word(m2, u, k));
            wg_wait<0>();
            send(e, aux, 1);
            TRACES(52 + k * 6);
        }
        if (it < NB) {
            const uint32_t tab = slots(it);
            st_pkt2_if(t4 == 0, odst, 0, 0, 0, tag0 + it + 128);
            bar_sync<4, 128>();
            const uint32_t aux = opaque(aux_word(m1, lds128(SM_SUM), it));
            float e[3][4] = {};
#pragma unroll 1
            for (int u = 0; u < 4; u++) {
                const uint32_t alo = desc_lo(SB) + slot_at(tab, 4 + u) * (PAIR >> 4), blo = desc_lo(SM_P) + u * (PSTR >> 4);
                mbar_wait(bar_at(B_F1 + 8 + 2 * u), it & 1);
                wg_fence();
                pv_steps(e, alo, blo, u > 0);
                wg_commit();
                wg_wait<1>();
                if (u == 1) mbar_arrive_if(lane == 0, bar_at(B_RP));
                mbar_wait(bar_at(B_F1 + 9 + 2 * u), it & 1);
                wg_fence();
                pv_steps(e, alo + (TILE >> 4), blo + 4, 1);
                wg_commit();
                wg_wait<1>();
            }
            wg_wait<0>();
            send(e, aux, 0);
            TRACES(53 + it * 6);
        }
    }
}

__device__ __forceinline__ void ln_finish(float s, float q, float& mean_b, float& rden) {
    const float mean = s * (1.f / DM);
    const float var = fmaxf(fmaf(q, 1.f / DM, -mean * mean), 0.f);
    mean_b = bfr(mean);
    rden = fast_rcp(bfr(fast_sqrt(bfr(bfr(var) + 1e-5f))));
}
__device__ __forceinline__ uint32_t ln_apply(uint32_t w, float mean_b, float rden) {
    const uint32_t d = bsub2(w, __byte_perm(__float_as_uint(mean_b), 0, 0x3232));
    return pack2(bf_lo(d) * rden, bf_hi(d) * rden);
}
__device__ __forceinline__ void spread(uint32_t (&b)[10], uint32_t x01, uint32_t x2, uint32_t wa, uint32_t ra, bool e2) {
    sts16(wa, x01); sts16(wa + 8, x01 >> 16);
    sts16_if(!e2, wa + 16, x2);
    __syncwarp();
    const uint4 u = lds128(ra), v = lds128(ra + 16);
    const uint2 z = lds64(ra + 32);
    b[0] = u.x; b[1] = u.y; b[2] = u.z; b[3] = u.w; b[4] = v.x; b[5] = v.y; b[6] = v.z; b[7] = v.w; b[8] = z.x; b[9] = z.y;
}
__device__ __forceinline__ float fold(float a, float b, bool sel, int m) { return (sel ? b : a) + shx(sel ? a : b, m); }

__device__ __forceinline__ void chain_role(const Params& p, int w, int lane, uint32_t t0) {
    const int cta = blockIdx.x, h = cta >> 2, s = cta & 3;
    const int g = lane >> 2, t4 = lane & 3;
    const bool e1 = t4 & 1, e2 = t4 & 2;
    uint32_t wq[5][3][4], wo[3][5][4], wg[5][4], wh[5][2], wd[4][4];
    const int col0 = 80 * w + (e2 ? 48 : 0) + g + (e1 ? 8 : 0);
    const uint32_t xw = opaque(SM_X + w * 384 + 48 * (g >> 1) + (e2 ? 24 : 0) + (e1 ? 4 : 0) + 2 * (g & 1));
    const uint32_t xr = opaque(g == 1 ? SM_ONES : SM_X + w * 384 + (g == 3 ? 192 : 0) + 48 * t4);
    TRACES(75);
    sts32_if(lane < 12, SM_ONES + lane * 4, 0x3f803f80u);
    uint32_t zero = lane >> 5;
    const int mi = lane >> 3, mr = lane & 7;
    mbar_wait(bar_at(B_W), 0);
    TRACES(74);
    sts16(xw + 192, lds16(ST_X + 5120 + col0 * 2)); sts16(xw + 200, lds16(ST_X + 5120 + col0 * 2 + 32));
    sts16_if(!e2, xw + 208, lds16(ST_X + 5120 + col0 * 2 + 64));
#pragma unroll
    for (int i = 0; i < 5; i++)
#pragma unroll
        for (int mt = 0; mt < 3; mt++) ldsm4t(wq[i][mt], ST_WQ + (80 * w + 16 * i + mr + 8 * (mi >> 1)) * 96 + 32 * mt + 16 * (mi & 1), zero);
    const bool odd = cta & 1;
    const uint32_t lo = ST_WD + (mr + (odd ? 4 : 0)) * 1280 + 160 * w, hi = ST_WD + ((mr & 3) + (odd ? 0 : 8)) * 1280 + 160 * w;
    ldsm4t(wd[0], lo + 16 * mi, zero);
    ldsm4t(wd[1], lo + 64 + 16 * mi, zero);
    ldsm4t(wd[2], hi + 64 * (mi >> 1) + 32 * (mr >> 2) + 16 * (mi & 1), zero);
    ldsm4t(wd[3], (mi < 2 ? lo : hi) + 128 + 16 * (mi & 1), zero);
    fence_async();
    __syncwarp();
    mbar_arrive_if(lane == 0, bar_at(B_WC));
    mbar_wait(bar_at(B_EP), 0);
    const uint32_t near = __shfl_sync(0xffffffffu, near_half(), 0);
    uint32_t x01 = 0, x2 = 0, nx01 = 0, nx2 = 0;
#pragma unroll 1
    for (int n = -5; n < NROUND; n++) {
        const bool last = (ORD_LAST >> (n & 15)) & 1, head = !((ORD_NO_HEAD >> (n & 15)) & 1);
        const int k = (ORD_BATCH >> (2 * (n & 15))) & 3;
        if (n > -5 && n <= 0) bar_sync<7, 288>();
        else if (!last) bar_sync<2, 256>();
        TRACES(n <= 0 ? 83 + n : 95);
        const char* const slice = p.scr + acc_off(k, last, w);
        const char* const cell = opaque(slice + g * 256 + t4 * 16);
        if (n >= 0) {
          if (head) {
            if (!last || n == NROUND - 1) mbar_wait(bar_at(B_Z), (k + last) & 1);
            const char* src = p.scr + SCR_O + head_off(h) + head_near(h, near) + last * 2048 + (w & 6) * 256 + (lane & 15) * 16;
            const uint32_t tag = lds32(SM_EPOCH) * NB + k;
            mbar_wait(bar_at(last ? B_RV : B_PS), k & 1);
            if (!last && k < NB - 1) wait_ns(t0 + batch_ns(k + 1) + CFG(START));
            uint4 v, z;
            {
                SPIN_DECL;
                do {
                    v = ld_pkt(src); z = ld_pkt(src + 256);
                    SPIN_CHECK(n);
                } while (__any_sync(0xffffffffu, (((v.w ^ tag) | (z.w ^ tag)) & 0xffu) != 0));
            }
            TRACES(tr + 0);
            float a[3][4] = {};
            const uint32_t bb[3][2] = {{v.x, v.y}, {z.x, z.y}, {v.z, z.z}};
            float sa, sb, rl;
#pragma unroll
            for (int i = 0; i < 3; i++) {
                const uint32_t l0 = g < 4 ? bb[i][0] : 0, l1 = g < 4 ? bb[i][1] : 0, h0 = g < 4 ? 0 : bb[i][0], h1 = g < 4 ? 0 : bb[i][1];
#pragma unroll
                for (int mt = 0; mt < 5; mt++)
                    mma16816(a[mt % 3], wo[i][mt][0], wo[i][mt][1], wo[i][mt][2], wo[i][mt][3], mt < 3 ? l0 : h0, mt < 3 ? l1 : h1);
                if (i == 0) {
                    int key = v.w & 0xffffff00u;
                    key ^= (key >> 31) & 0x7fffffff;
                    key = __reduce_max_sync(0xffffffffu, key);
                    key ^= (key >> 31) & 0x7fffffff;
                    const float ws = fast_ex2((F(v.w & 0xffffff00u) - __int_as_float(key)) * LOG2E);
                    sa = shi(ws, e1 ? 8 : 0); sb = shi(ws, e1 ? 12 : 4);
                    rl = ws * F(z.w & 0xffffff00u);
                    rl += shx(rl, 4);
                }
                if (i == 1) rl += shx(rl, 8);
            }
            float y[3];
#pragma unroll
            for (int j = 2; j < 5; j++) {
                const int mt = j % 3;
                y[mt] = fold(fmaf(a[mt][0], sa, a[mt][1] * sb), fmaf(a[mt][2], sa, a[mt][3] * sb), e1, 1);
            }
            const uint32_t pa = SM_PO + w * 512 + lane * 16;
            if (w < 2) {
                const char* dst = opaque(cell + s * 16384);
                rl = fast_rcp(rl);
                bar_sync<1, 256>();
                const uint4 c1 = lds128(pa), c2 = lds128(pa + 1024), c3 = lds128(pa + 2048);
                red_cell2_if(true, dst, ((y[0] + F(c1.x)) + (F(c2.x) + F(c3.x))) * rl, ((y[1] + F(c1.y)) + (F(c2.y) + F(c3.y))) * rl,
                             ((y[2] + F(c1.z)) + (F(c2.z) + F(c3.z))) * rl);
            } else {
                stsf4(pa - 1024, y[0], y[1], y[2], 0.f);
                bar_sync<1, 256>();
            }
            TRACES(tr + 1);
            if ((ORD_NO_TAIL >> n) & 1) continue;
            wait_clk(clk32() + (w < 2 ? 0 : 60) + (n < QUIET ? CFG(DLY_AL) : CFG(DLY_A)));
            {
                SPIN_DECL;
                do {
                    v = ld_pkt(cell + near);
                    SPIN_CHECK(n);
                } while (__any_sync(0xffffffffu, v.w != FULL_A));
            }
            TRACES(tr + 2);
            x01 = pack2(F(v.x), F(v.y));
            x2 = pack2(F(v.z), 0.f);
          } else { x01 = nx01; x2 = nx2; }
        } else if (n == -1) {
            mbar_wait(bar_at(B_W + 1), 0);
            const uint32_t ln = opaque(lane);
            const int mi = ln >> 3, mr = ln & 7;
            uint32_t zero = ln >> 5;
            TRACES(76);
#pragma unroll
            for (int i = 0; i < 3; i++) {
                const int d = 16 * (w >> 1) + (mr >> 1) + 8 * (mr & 1) + (i < 2 ? 64 * (mi >> 1) + 4 * i : 128 + 4 * (mi >> 1));
#pragma unroll
                for (int mt = 0; mt < 5; mt++) ldsm4t(wo[i][mt], ST_WO + d * 320 + 160 * (w & 1) + 32 * mt + 16 * (mi & 1), zero);
            }
            fence_async();
            __syncwarp();
            mbar_arrive_if(lane == 0, bar_at(B_WC + 1));
            mbar_wait(bar_at(B_W + 2), 0);
            TRACES(77);
#pragma unroll
            for (int i = 0; i < 5; i++) {
                const uint32_t ga = ST_WG + (mi & 1) * 20480 + (80 * w + 16 * i + mr + 8 * (mi >> 1)) * 32;
                uint32_t r[4];
                ldsm4t(wg[i], ga + (odd ? 16 : 0), zero);
                ldsm4t(r, ga + (odd ? 0 : 16), zero);
#pragma unroll
                for (int kh = 0; kh < 2; kh++) {
                    const uint32_t moved = __shfl_xor_sync(0xffffffffu, odd ? r[2 * kh] : r[2 * kh + 1], 16);
                    wh[i][kh] = (g < 4) == odd ? moved : odd ? r[2 * kh + 1] : r[2 * kh];
                }
            }
            fence_async();
            __syncwarp();
            mbar_arrive_if(lane == 0, bar_at(B_WC + 2));
            TRACES(72);
            x01 = 0x3f803f80u; x2 = 0x3f80u;
        } else {
            const uint32_t xa = ST_X + (n + 5) * 1280, ln = opaque(lane);
            const int col0 = 80 * w + (ln & 2 ? 48 : 0) + (ln >> 2) + (ln & 1 ? 8 : 0);
            float sm = 0.f, sq = 0.f;
#pragma unroll
            for (int i = 0; i < 5; i++) {
                const uint2 c = lds64(xa + i * 256 + ln * 8);
                sm += (bf_lo(c.x) + bf_hi(c.x)) + (bf_lo(c.y) + bf_hi(c.y));
                sq = fmaf(bf_lo(c.x), bf_lo(c.x), fmaf(bf_hi(c.x), bf_hi(c.x), fmaf(bf_lo(c.y), bf_lo(c.y), fmaf(bf_hi(c.y), bf_hi(c.y), sq))));
            }
            x01 = lds16(xa + col0 * 2) | lds16(xa + col0 * 2 + 32) << 16;
            x2 = lds16(xa + col0 * 2 + 64);
#pragma unroll
            for (int o = 16; o; o >>= 1) { sm += shx(sm, o); sq += shx(sq, o); }
            float mean_b, rden;
            ln_finish(sm, sq, mean_b, rden);
            x01 = ln_apply(x01, mean_b, rden);
            x2 = ln_apply(x2, mean_b, rden);
        }
        if (n >= -1) {
            uint32_t b[10];
            spread(b, x01, x2, xw, xr, e2);
            float a[2][4] = {};
#pragma unroll
            for (int i = 0; i < 5; i++) {
                mma16816(a[0], wg[i][0], wg[i][1], wg[i][2], wg[i][3], b[2 * i], b[2 * i + 1]);
                mma16816(a[1], wh[i][0], b[2 * i], wh[i][1], b[2 * i + 1], b[2 * i], b[2 * i + 1]);
            }
            stsf(SM_PG + (w >> 2) * 512 + (g + 8 * t4) * 16 + (w & 3) * 4, e2 ? (e1 ? a[1][2] : a[1][0]) : (e1 ? a[0][2] : a[0][0]));
            const uint2 cs = lds64(SM_CSG + lane * 48);
            const char* dst = opaque(cell + 3 * HALF - near);
            bar_sync<2, 256>();
            const float S = sum8(lds128(SM_PG + lane * 16), lds128(SM_PG + 512 + lane * 16));
            const float sx = shi(S, 25), sq = shi(S, 24), Su = shi(S, lane + (lane < 16 ? 8 : 4));
            if (n < 0) {
                if (w == 0) stsf2(SM_CSG + lane * 48, S, Su);
            } else {
                float mean_b, rden;
                ln_fast(sx, sq, mean_b, rden);
                const float gv = bfr(fmaf(-mean_b, F(cs.x), S) * rden), uv = bfr(fmaf(-mean_b, F(cs.y), Su) * rden);
                const float sg = fast_rcp(1.f + fast_ex2(-LOG2E * gv));
                const uint32_t hb = pack2(bfr(gv * sg) * uv, 0.f);
                const uint32_t b0 = __byte_perm(shi(hb, 2 * t4), shi(hb, 2 * t4 + 1), 0x5410);
                const uint32_t b1 = __byte_perm(shi(hb, e1 ? 18 : 16), shi(hb, e1 ? 19 : 17), 0x5410);
                const bool up = g >= 4;
                const uint32_t l0 = up ? 0 : b0, h0 = up ? b0 : 0;
                const uint32_t l1 = up ? 0 : b1, h1 = up ? b1 : 0;
                float d[3][4] = {};
                mma1688(d[0], wd[0][0], wd[0][1], l0); mma1688(d[1], wd[0][2], wd[0][3], l0); mma1688(d[2], wd[1][0], wd[1][1], l0);
                mma1688(d[0], wd[1][2], wd[1][3], h0); mma1688(d[1], wd[3][0], wd[3][1], h0);
                mma1688(d[2], wd[2][2], wd[2][3], e2 ? 0 : l1);
                mma1688(d[0], wd[2][0], wd[2][1], e2 ? 0 : l1); mma1688(d[1], wd[2][0], wd[2][1], e2 ? l1 : 0);
                mma1688(d[0], wd[2][2], wd[2][3], e2 ? h1 : 0); mma1688(d[1], wd[3][2], wd[3][3], e2 ? 0 : h1);
                red_cell(dst, e1 ? d[0][2] : d[0][0], e1 ? d[1][2] : d[1][0], e1 ? d[2][2] : d[2][0]);
                const uint32_t tsend = clk32();
                TRACES(tr + 3);
                if (last && w != cta >> 4) continue;
                if (!last && w == 0) st_pkt82_if(lane < 24, p.scr + SCR_Q + head_off(h) + 4 * 768 + (24 * s + lane) * 8, 0, 0);
                const float sgr = shi(sg, 27);
                const uint32_t sg2 = pack2(sgr, sgr);
                const uint32_t n01 = opaque(pack2((bf_lo(x01) - mean_b) * rden, (bf_hi(x01) - mean_b) * rden));
                const uint32_t n2 = opaque(pack2((bf_lo(x2) - mean_b) * rden, 0.f));
                if (last) {
                    sts128_if(lane >> 1 == (cta & 15), SM_FIN + (lane & 1) * 16, x01, n01, __byte_perm(x2, n2, 0x5410), sg2);
                    mbar_arrive_if(lane >> 1 == (cta & 15), bar_at(B_FIN));
                    __syncwarp();
                    continue;
                }
                if (n > 0) {
                    const char* src = p.scr + acc_off(k - 1, 1, w) + near + g * 256 + t4 * 16;
                    SPIN_DECL;
                    while (true) {
                        const uint4 u = ld_pkt(src);
                        nx01 = pack2(F(u.x), F(u.y)); nx2 = pack2(F(u.z), 0.f);
                        if (__all_sync(0xffffffffu, u.w == FULL_A)) break;
                        SPIN_CHECK(n);
                    }
                }
                wait_clk(tsend + (n < QUIET ? CFG(DLY_BL) : CFG(DLY_B)));
                uint4 v, z;
                {
                    SPIN_DECL;
                    do {
                        v = ld_pkt(cell + 2 * HALF); z = ld_pkt(cell + 3 * HALF);
                        SPIN_CHECK(n);
                    } while (__any_sync(0xffffffffu, F(v.w) + F(z.w) != NCTA));
                }
                x01 = badd2(x01, badd2(n01, bmul2(pack2(F(v.x) + F(z.x), F(v.y) + F(z.y)), sg2)));
                x2 = badd2(x2, badd2(n2, bmul2(pack2(F(v.z) + F(z.z), 0.f), sg2)));
                TRACES(tr + 4);
            }
        }
        {
            uint32_t b[10];
            spread(b, x01, x2, xw, xr, e2);
            float a[3][4] = {};
            const float f0 = bf_lo(x01), f1 = bf_hi(x01), f2 = e2 ? 0.f : bf_lo(x2);
            float st;
#pragma unroll
            for (int i = 0; i < 5; i++) {
#pragma unroll
                for (int mt = 0; mt < 3; mt++) {
                    mma16816(a[mt], wq[i][mt][0], wq[i][mt][1], wq[i][mt][2], wq[i][mt][3], b[2 * i], b[2 * i + 1]);
                    if (i == 0 && mt == 0) st = fold(fmaf(f0, f0, fmaf(f1, f1, f2 * f2)), (f0 + f1) + f2, g & 1, 4);
                }
                if (i < 4) st += shx(st, i < 2 ? 1 << i : 2 << i);
            }
            const uint32_t pa = SM_PQ + (w >> 2) * 1024 + (g & 1) * 512 + ((e2 ? 16 : 0) + (e1 ? 4 : 0) + (g >> 1)) * 16 + (w & 3) * 4;
            stsf(pa + 128, e2 ? st : e1 ? a[1][2] : a[1][0]);
            stsf(pa, e2 ? (e1 ? a[2][2] : a[2][0]) : (e1 ? a[0][2] : a[0][0]));
            bar_arrive<3, 288>();
            if (n >= 0 && w == cta >> 4) {
                red_cell2_if(lane >> 1 == (cta & 15), cell + 128, f0, f1, f2);
                __syncwarp();
            }
        }
    }
}

template <int ID> __device__ __forceinline__ void role_exit() { asm volatile("exit; // %0" ::"n"(ID)); }
constexpr int NTHREADS = 512;
#define STR2(x) #x
#define STR(x) STR2(x)
__global__ void __launch_bounds__(NTHREADS, 1)
decode_kernel(const Params p, const __grid_constant__ Maps tm) {
    extern __shared__ __align__(1024) unsigned char smem[];
    if (threadIdx.x == 0) l2_prefetch(p.wq + (size_t)blockIdx.x * 12288, 12288);
    const uint32_t t0 = now_ns() - CFG(LEAD);
    const int lane = threadIdx.x & 31;
    const int warp = __shfl_sync(0xffffffffu, threadIdx.x >> 5, 0);
    if (warp < 8) {
        asm volatile("setmaxnreg.inc.sync.aligned.u32 " STR(CFG_REG_CHAIN) ";");
        bar_arrive<5, 480 + 0>();
        const uint32_t vote = probe_near(p, warp, lane);
        bar_sync<2, 256 + 32>();
        sts32(SM_NEAR + warp * 4, vote);
        mbar_arrive_if(lane == 0, bar_at(B_EP));
        chain_role(p, warp, __shfl_sync(0xffffffffu, lane, lane), t0);
        role_exit<3>();
    } else if (warp < 12) {
        asm volatile("setmaxnreg.dec.sync.aligned.u32 " STR(CFG_REG_ATT) ";");
        if (elect_one()) {
#pragma unroll 1
            for (int i = warp - 8; i < NBAR; i += 4)
                if (i < B_W || i >= B_WC) mbar_init(bar_at(i), i == B_FIN ? 2 : i == B_EP ? 9 : i == B_QR ? 32 : i == B_PS || i == B_RP ? 4 : i >= B_F3 ? 1 : i >= B_WC ? 8 : i < B_RR || i > B_RV ? 1 : i < B_RK ? 2 : 4);
            asm volatile("fence.mbarrier_init.release.cluster;" ::: "memory");
            fence_async();
        }
        bar_sync<5, 480>();
        attention_role(p, warp - 8, lane);
        role_exit<2>();
    } else {
        asm volatile("setmaxnreg.dec.sync.aligned.u32 " STR(CFG_REG_HELP) ";");
        if (warp == 12) {
            load_role(p, &tm.k, lane, t0);
            role_exit<0>();
        } else {
            if (warp == 14) {
                if (smem_u32(smem) != SB) __trap();
                if (elect_one()) {
                    asm volatile("prefetch.tensormap [%0];" ::"l"(&tm.q) : "memory");
                    mbar_init(bar_at(B_W), 1); mbar_init(bar_at(B_W + 1), 1); mbar_init(bar_at(B_W + 2), 1);
                    asm volatile("fence.mbarrier_init.release.cluster;" ::: "memory");
                    fence_async();
                    mbar_expect_tx(bar_at(B_W), 61440 + 15360 + 6400); mbar_expect_tx(bar_at(B_W + 1), 61440); mbar_expect_tx(bar_at(B_W + 2), 40960);
                    bulk_load(ST_X, p.x, 5120, bar_at(B_W));
                    bulk_load(ST_X + 5120, p.wr, 1280, bar_at(B_W));
                }
                reload_role(p, &tm, t0);
            } else {
                unsigned ticket = 0;
                if (warp == 15 && lane == 0) asm volatile("atom.relaxed.gpu.global.add.u32 %0, [%1], 1;" : "=r"(ticket) : "l"(&g_epoch) : "memory");
                if (warp == 13 && elect_one()) {
                    asm volatile("prefetch.tensormap [%0];" ::"l"(&tm.g) : "memory");
                    asm volatile("prefetch.tensormap [%0];" ::"l"(&tm.u) : "memory");
                    asm volatile("prefetch.tensormap [%0];" ::"l"(&tm.o) : "memory");
                    asm volatile("prefetch.tensormap [%0];" ::"l"(&tm.k) : "memory");
                    asm volatile("prefetch.tensormap [%0];" ::"l"(&tm.v) : "memory");
                }
                bar_sync<5, 480>();
                if (warp == 13) { bar_arrive<6, 64>(); q_role(p, lane); }
                else { bar_arrive<2, 256 + 32>(); zero_role(p, lane, ticket, t0); }
            }
            role_exit<1>();
        }
    }
}

typedef CUresult (*EncodeFn)(CUtensorMap*, CUtensorMapDataType, cuuint32_t, void*, const cuuint64_t*, const cuuint64_t*,
                             const cuuint32_t*, const cuuint32_t*, CUtensorMapInterleave, CUtensorMapSwizzle,
                             CUtensorMapL2promotion, CUtensorMapFloatOOBfill);

bool make_map(EncodeFn fn, CUtensorMap* m, const void* ptr, uint64_t cols, uint64_t rows, uint32_t bc, uint32_t br) {
    cuuint64_t dims[2] = {cols, rows};
    cuuint64_t strides[1] = {cols * 2};
    cuuint32_t box[2] = {bc, br};
    cuuint32_t es[2] = {1, 1};
    return fn(m, CU_TENSOR_MAP_DATA_TYPE_BFLOAT16, 2, const_cast<void*>(ptr), dims, strides, box, es, CU_TENSOR_MAP_INTERLEAVE_NONE,
              CU_TENSOR_MAP_SWIZZLE_NONE, CU_TENSOR_MAP_L2_PROMOTION_L2_128B, CU_TENSOR_MAP_FLOAT_OOB_FILL_NONE) == CUDA_SUCCESS;
}

bool make_kv_map(EncodeFn fn, CUtensorMap* m, const void* ptr) {
    cuuint64_t dims[4] = {64, 8, 3, (cuuint64_t)NB * NHEAD * SK / 8};
    cuuint64_t strides[3] = {DH * 2, 128, 8 * DH * 2};
    cuuint32_t box[4] = {64, 8, 3, 4};
    cuuint32_t es[4] = {1, 1, 1, 1};
    return fn(m, CU_TENSOR_MAP_DATA_TYPE_BFLOAT16, 4, const_cast<void*>(ptr), dims, strides, box, es, CU_TENSOR_MAP_INTERLEAVE_NONE,
              CU_TENSOR_MAP_SWIZZLE_128B, CU_TENSOR_MAP_L2_PROMOTION_L2_128B, CU_TENSOR_MAP_FLOAT_OOB_FILL_NONE) == CUDA_SUCCESS;
}

}

extern "C" void kernel_launch(void* const* d_in, const int* in_sizes, int n_in, void* d_out, int out_size) {
    (void)in_sizes; (void)n_in; (void)out_size;
    static EncodeFn fn = nullptr;
    static const char* scr = nullptr;
    if (!fn) {
        void* f = nullptr;
        cudaDriverEntryPointQueryResult qr;
        if (cudaGetDriverEntryPoint("cuTensorMapEncodeTiled", &f, cudaEnableDefault, &qr) != cudaSuccess || !f) return;
        void* sp = nullptr;
        if (cudaGetSymbolAddress(&sp, g_scratch) != cudaSuccess) return;
        scr = (const char*)(((uintptr_t)sp + (2 << 20) - 1) & ~(uintptr_t)((2 << 20) - 1));
        fn = (EncodeFn)f;
        cudaFuncSetAttribute(decode_kernel, cudaFuncAttributeMaxDynamicSharedMemorySize, SMEM_BYTES);
    }
    Maps tm;
    if (!make_kv_map(fn, &tm.k, d_in[1]) || !make_kv_map(fn, &tm.v, d_in[2])) return;
    if (!make_map(fn, &tm.q, d_in[3], NHEAD * DH, DM, 48, 128) || !make_map(fn, &tm.o, d_in[4], DM, NHEAD * DH, 160, 32)) return;
    if (!make_map(fn, &tm.g, d_in[7], FF, DM, 16, 128) || !make_map(fn, &tm.u, d_in[8], FF, DM, 16, 128)) return;
    Params p;
    p.x = (const unsigned short*)d_in[0];
    p.wq = (const char*)d_in[3];
    p.wo = (const char*)d_in[4];
    p.wr = (const unsigned short*)d_in[6];
    p.wg = (const char*)d_in[7];
    p.wu = (const char*)d_in[8];
    p.wd = (const char*)d_in[9];
    p.out = (unsigned short*)d_out;
    p.scr = scr;
    decode_kernel<<<NCTA, NTHREADS, SMEM_BYTES>>>(p, tm);
}
```

```cpp
#include <cuda_runtime.h>
#include <cuda_bf16.h>
#include <cuda.h>
#include <stdint.h>

namespace {

constexpr int NB = 4, DM = 640, NHEAD = 32, DH = 192, SK = 4096, WIN = 1024, FF = 1536;
constexpr int NCTA = 128;
constexpr int TILE = 12288, PAIR = 2 * TILE;

#define CFG_LIST(X) \
    X(TICK0, 476)        \
    X(TICK, 492)        \
    X(LEAD, 350)        \
    X(STAG, 500)        \
    X(WLAG, 200)        \
    X(GSTEP, 750)        \
    X(WIN, 5)        \
    X(PMAX, 3)        \
    X(PGRACE, 50)        \
    X(LMAX0, 150)        \
    X(LMAX, 200) \
    X(GAIN, 5)        \
    X(VSTEP, 250)        \
    X(RLAG, 0)        \
    X(RSTEP, 640) \
    X(RSTEP3, 450) \
    X(ZTILE, 11)        \
    X(START, 1)        \
    X(DLY_A, 450)        \
    X(DLY_AL, 100) \
    X(DLY_B, 600) \
    X(DLY_BL, 950) \
    X(DLY_F, 250) \
    X(FLIP, 0) \

#define X(n, v) constexpr int CFG_##n = v;
CFG_LIST(X)
#undef X
#define CFG(n) CFG_##n
constexpr int QUIET = 8;
#define CFG_REG_CHAIN 216
#define CFG_REG_ATT 48
#define CFG_REG_HELP 32
constexpr int KB_KV0 = 165;
__device__ __forceinline__ int kb_ns(int kb) { return kb * CFG(TICK0) / 12; }
__device__ __forceinline__ int tick_ns(int j) { return j <= 16 ? CFG(TICK0) : CFG(TICK); }
__device__ __forceinline__ int batch_ns(int k) { return kb_ns(KB_KV0) + (k ? 16 * (CFG(TICK0) + (k - 1) * CFG(TICK)) : 0); }

__device__ __forceinline__ uint32_t slots(int k) { return k & 2 ? (k & 1 ? 0x21304768u : 0x76835214u) : (k & 1 ? 0x21480765u : 0x76543210u); }
__device__ __forceinline__ int pass_nibble(int k, int u) { return k > 0 ? 4 + (u & 1) : u; }
__device__ __forceinline__ uint32_t slot_at(uint32_t tab, int u) { return (tab >> (4 * u)) & 15; }

constexpr int NROUND = 11;
constexpr uint32_t ORD_BATCH = 0x3b9910, ORD_LAST = 0x6da, ORD_NO_HEAD = 0x248, ORD_NO_TAIL = 0x092;

constexpr uint32_t SB = 1024;
constexpr uint32_t SM_BAR = SB + 9 * PAIR;
constexpr int B_F1 = 0;
constexpr int B_RR = 24;
constexpr int B_RK = 32;
constexpr int B_RV = 36;
constexpr int B_Z = 37;
constexpr int B_EP = 38;
constexpr int B_W = 39;
constexpr int B_WC = 42;
constexpr int B_FIN = 45;
constexpr int B_F3 = 46;
constexpr int B_PS = 48;
constexpr int B_RP = 49;
constexpr int B_FL = 50;
constexpr int B_QR = 51;
constexpr int NBAR = 52;
__host__ __device__ constexpr uint32_t bar_at(int i) { return SM_BAR + 8 * i; }
constexpr uint32_t SM_EPOCH = SM_BAR + 416;
constexpr uint32_t SM_MAX = SM_EPOCH + 16;
constexpr uint32_t SM_SUM = SM_MAX + 16;
constexpr uint32_t SM_NEAR = SM_SUM + 32;
constexpr uint32_t SM_FIN = SM_NEAR + 32;
constexpr uint32_t SM_Q = SM_FIN + 32;
constexpr uint32_t PSTR = 144;
constexpr uint32_t SM_P = SM_Q + 5 * 384;
constexpr uint32_t SM_X = SM_P + 8 * PSTR;
constexpr uint32_t SM_CSG = SM_X + 40;
constexpr uint32_t SM_ONES = SM_X + 8 * 384;
constexpr uint32_t SM_PG = SM_ONES + 48;
constexpr uint32_t SM_PO = SM_PG + 1024;
constexpr uint32_t SM_PQ = SM_PO;
constexpr int SMEM_BYTES = SM_PO + 3072 - SB;
static_assert(SMEM_BYTES <= 232448 && SM_Q % 16 == 0 && SM_P % 16 == 0 && SM_X % 16 == 0 && SM_PO % 16 == 0, "smem");
constexpr uint32_t ST_WQ = SB, ST_WD = SB + 3 * PAIR, ST_WO = SB + 4 * PAIR, ST_WG = SB + 7 * PAIR, ST_X = ST_WG + 40960;

__device__ unsigned g_epoch;
__device__ unsigned char g_scratch[4 << 20];
constexpr uint32_t HALF = 4096, SCR_O = 1 << 16, SCR_Q = 1 << 17, SCR_COUNT = 3 << 16;
__device__ __forceinline__ uint32_t acc_off(int k, int layer, int w) {
    return (k & 1) << 6 | layer << 7 | (w & 1) << 11 | (w >> 1) << 14 | (k + layer == NB) << 18;
}
__device__ __forceinline__ uint32_t head_off(int h) { return (h & 3) << 14 | (h & 4) << 16 | (h & 8) << 17 | (h & 16) << 9; }
__device__ __forceinline__ uint32_t head_near(int h, uint32_t near) { return near ^ HALF ^ (h & 16) << 8; }
constexpr uint32_t FULL_A = 0x42040000u;

struct Params {
    const char* wq;
    const unsigned short* x;
    const char* wo;
    const unsigned short* wr;
    const char* wg;
    const char* wu;
    const char* wd;
    unsigned short* out;
    const char* scr;
};

__device__ __forceinline__ uint32_t smem_u32(const void* p) { return (uint32_t)__cvta_generic_to_shared(p); }
__device__ __forceinline__ void mbar_init(uint32_t a, uint32_t c) { asm volatile("mbarrier.init.shared::cta.b64 [%0], %1;" ::"r"(a), "r"(c) : "memory"); }
__device__ __forceinline__ void mbar_expect_tx(uint32_t a, uint32_t b) {
    asm volatile("mbarrier.arrive.expect_tx.shared::cta.b64 _, [%0], %1;" ::"r"(a), "r"(b) : "memory");
}
__device__ __forceinline__ void mbar_arrive(uint32_t a) { asm volatile("mbarrier.arrive.shared::cta.b64 _, [%0];" ::"r"(a) : "memory"); }
constexpr uint32_t SPIN_LIMIT = 1u << 22;
#define SPIN_DECL uint32_t spins = 0
#define SPIN_CHECK(info) { if (++spins > SPIN_LIMIT) __trap(); }
__device__ __forceinline__ void mbar_wait(uint32_t a, uint32_t parity) {
    uint32_t ok;
    SPIN_DECL;
    while (true) {
        asm volatile("{\n.reg .pred p;\nmbarrier.try_wait.parity.shared::cta.b64 p, [%1], %2;\nselp.u32 %0, 1, 0, p;\n}"
                     : "=r"(ok) : "r"(a), "r"(parity) : "memory");
        if (ok) break;
        SPIN_CHECK((a - SM_BAR) / 8 * 10 + parity);
    }
}
__device__ __forceinline__ bool mbar_test2(uint32_t a, uint32_t pa, uint32_t b, uint32_t pb) {
    uint32_t ok;
    asm volatile("{\n.reg .pred p, q;\nmbarrier.test_wait.parity.shared::cta.b64 p, [%1], %2;\n"
                 "mbarrier.test_wait.parity.shared::cta.b64 q, [%3], %4;\nand.pred p, p, q;\nvote.sync.all.pred p, p, 0xffffffff;\nselp.u32 %0, 1, 0, p;\n}"
                 : "=r"(ok) : "r"(a), "r"(pa), "r"(b), "r"(pb) : "memory");
    return ok;
}
__device__ __forceinline__ uint32_t now_ns() { uint32_t t; asm volatile("mov.u32 %0, %%globaltimer_lo;" : "=r"(t) :: "memory"); return t; }
__device__ __forceinline__ uint32_t clk32() { uint32_t c; asm volatile("mov.u32 %0, %%clock;" : "=r"(c) :: "memory"); return c; }
__device__ __forceinline__ void wait_ns(uint32_t t) { while ((int)(now_ns() - t) < 0) {} }
__device__ __forceinline__ void wait_clk(uint32_t t) { while ((int)(clk32() - t) < 0) {} }
__device__ __forceinline__ bool elect_one() {
    uint32_t e;
    asm volatile("{\n.reg .pred p;\nelect.sync _|p, 0xffffffff;\nselp.u32 %0, 1, 0, p;\n}" : "=r"(e));
    return e;
}
constexpr uint64_t POL_FIRST = 0x12F0000000000000ull, POL_NORMAL = 0x1000000000000000ull;
__device__ __forceinline__ void tma_tile(uint32_t dst, const CUtensorMap* tm, int group, uint32_t bar, uint64_t pol) {
    asm volatile("cp.async.bulk.tensor.4d.shared::cluster.global.mbarrier::complete_tx::bytes.L2::cache_hint"
                 " [%0], [%1, {%3, %3, %3, %4}], [%2], %5;"
                 ::"r"(dst), "l"(tm), "r"(bar), "r"(0), "r"(group), "l"(pol) : "memory");
}
__device__ __forceinline__ void tma2d(uint32_t dst, const CUtensorMap* tm, int x, int y, uint32_t bar) {
    asm volatile("cp.async.bulk.tensor.2d.shared::cluster.global.mbarrier::complete_tx::bytes [%0], [%1, {%3, %4}], [%2];"
                 ::"r"(dst), "l"(tm), "r"(bar), "r"(x), "r"(y) : "memory");
}
__device__ __forceinline__ void bulk_load(uint32_t dst, const void* src, uint32_t bytes, uint32_t bar) {
    asm volatile("cp.async.bulk.shared::cluster.global.mbarrier::complete_tx::bytes [%0], [%1], %2, [%3];"
                 ::"r"(dst), "l"(src), "r"(bytes), "r"(bar) : "memory");
}
__device__ __forceinline__ void l2_prefetch(const void* p, uint32_t bytes) {
    asm volatile("cp.async.bulk.prefetch.L2.global [%0], %1;" ::"l"(p), "r"(bytes) : "memory");
}
__device__ __forceinline__ void mma16816(float (&c)[4], uint32_t a0, uint32_t a1, uint32_t a2, uint32_t a3, uint32_t b0, uint32_t b1) {
    asm volatile("mma.sync.aligned.m16n8k16.row.col.f32.bf16.bf16.f32 {%0,%1,%2,%3}, {%4,%5,%6,%7}, {%8,%9}, {%0,%1,%2,%3};"
                 : "+f"(c[0]), "+f"(c[1]), "+f"(c[2]), "+f"(c[3]) : "r"(a0), "r"(a1), "r"(a2), "r"(a3), "r"(b0), "r"(b1));
}
__device__ __forceinline__ void mma1688(float (&c)[4], uint32_t a0, uint32_t a1, uint32_t b0) {
    asm volatile("mma.sync.aligned.m16n8k8.row.col.f32.bf16.bf16.f32 {%0,%1,%2,%3}, {%4,%5}, {%6}, {%0,%1,%2,%3};"
                 : "+f"(c[0]), "+f"(c[1]), "+f"(c[2]), "+f"(c[3]) : "r"(a0), "r"(a1), "r"(b0));
}
__device__ __forceinline__ void ldsm4(uint32_t (&r)[4], uint32_t a) {
    asm volatile("ldmatrix.sync.aligned.m8n8.x4.shared.b16 {%0,%1,%2,%3}, [%4];"
                 : "=r"(r[0]), "=r"(r[1]), "=r"(r[2]), "=r"(r[3]) : "r"(a) : "memory");
}
__device__ __forceinline__ void ldsm4t(uint32_t (&r)[4], uint32_t a, uint32_t& zero) {
    asm volatile("ldmatrix.sync.aligned.m8n8.x4.trans.shared.b16 {%0,%1,%2,%3}, [%4];"
                 : "=r"(r[0]), "=r"(r[1]), "=r"(r[2]), "=r"(r[3]) : "r"(a + zero) : "memory");
    zero &= r[3];
}
__device__ __forceinline__ uint4 ld_pkt(const void* p) {
    uint4 v;
    asm volatile("{\n.reg .b128 t;\nld.relaxed.gpu.global.b128 t, [%4];\nmov.b128 {%0,%1,%2,%3}, t;\n}"
                 : "=r"(v.x), "=r"(v.y), "=r"(v.z), "=r"(v.w) : "l"(p) : "memory");
    return v;
}
__device__ __forceinline__ void st_pkt(const void* p, uint32_t a, uint32_t b, uint32_t c, uint32_t d) {
    asm volatile("{\n.reg .b128 t;\nmov.b128 t, {%1,%2,%3,%4};\nst.relaxed.gpu.global.b128 [%0], t;\n}"
                 ::"l"(p), "r"(a), "r"(b), "r"(c), "r"(d) : "memory");
}
__device__ __forceinline__ uint2 ld_pkt8(const void* p) {
    uint2 v;
    asm volatile("{\n.reg .b64 t;\nld.relaxed.gpu.global.b64 t, [%2];\nmov.b64 {%0,%1}, t;\n}" : "=r"(v.x), "=r"(v.y) : "l"(p) : "memory");
    return v;
}
__device__ __forceinline__ void red_cell(const char* p, float a, float b, float c) {
    asm volatile("red.relaxed.gpu.global.add.v4.f32 [%0], {%1,%2,%3,%4};" ::"l"(p), "f"(a), "f"(b), "f"(c), "f"(1.0f) : "memory");
}
#define PRED(n) "{\n.reg .pred p;\nsetp.ne.u32 p, %" #n ", 0;\n"
__device__ __forceinline__ void red_cell2_if(bool on, const char* p, float a, float b, float c) {
    asm volatile(PRED(5) "@p red.relaxed.gpu.global.add.v4.f32 [%0], {%1,%2,%3,%4};\n@p red.relaxed.gpu.global.add.v4.f32 [%0+4096], {%1,%2,%3,%4};\n}"
                 ::"l"(p), "f"(a), "f"(b), "f"(c), "f"(1.0f), "r"((uint32_t)on) : "memory");
}
__device__ __forceinline__ void st_pkt8_if(bool on, const void* p, uint32_t a, uint32_t b) {
    asm volatile(PRED(3) ".reg .b64 t;\nmov.b64 t, {%1,%2};\n@p st.relaxed.gpu.global.b64 [%0], t;\n}" ::"l"(p), "r"(a), "r"(b), "r"((uint32_t)on) : "memory");
}
__device__ __forceinline__ void st_pkt82_if(bool on, const void* p, uint32_t a, uint32_t b) {
    asm volatile(PRED(3) ".reg .b64 t;\nmov.b64 t, {%1,%2};\n@p st.relaxed.gpu.global.b64 [%0], t;\n@p st.relaxed.gpu.global.b64 [%0+4096], t;\n}"
                 ::"l"(p), "r"(a), "r"(b), "r"((uint32_t)on) : "memory");
}
__device__ __forceinline__ void st_pkt2_if(bool on, const void* p, uint32_t a, uint32_t b, uint32_t c, uint32_t d) {
    asm volatile(PRED(5) ".reg .b128 t;\nmov.b128 t, {%1,%2,%3,%4};\n@p st.relaxed.gpu.global.b128 [%0], t;\n@p st.relaxed.gpu.global.b128 [%0+4096], t;\n}"
                 ::"l"(p), "r"(a), "r"(b), "r"(c), "r"(d), "r"((uint32_t)on) : "memory");
}
__device__ __forceinline__ void mbar_arrive_if(bool on, uint32_t a) {
    asm volatile(PRED(1) "@p mbarrier.arrive.shared::cta.b64 _, [%0];\n}" ::"r"(a), "r"((uint32_t)on) : "memory");
}
__device__ __forceinline__ void sts16_if(bool on, uint32_t a, uint32_t v) {
    asm volatile(PRED(2) "@p st.shared.u16 [%0], %1;\n}" ::"r"(a), "h"((unsigned short)v), "r"((uint32_t)on) : "memory");
}
__device__ __forceinline__ void sts32_if(bool on, uint32_t a, uint32_t v) {
    asm volatile(PRED(2) "@p st.shared.u32 [%0], %1;\n}" ::"r"(a), "r"(v), "r"((uint32_t)on) : "memory");
}
__device__ __forceinline__ void sts128_if(bool on, uint32_t a, uint32_t x, uint32_t y, uint32_t z, uint32_t w) {
    asm volatile(PRED(5) "@p st.shared.v4.u32 [%0], {%1,%2,%3,%4};\n}" ::"r"(a), "r"(x), "r"(y), "r"(z), "r"(w), "r"((uint32_t)on) : "memory");
}
__device__ __forceinline__ float fast_rcp(float x) { float r; asm("rcp.approx.ftz.f32 %0, %1;" : "=f"(r) : "f"(x)); return r; }
__device__ __forceinline__ float fast_sqrt(float x) { float r; asm("sqrt.approx.ftz.f32 %0, %1;" : "=f"(r) : "f"(x)); return r; }
__device__ __forceinline__ float fast_ex2(float x) { float r; asm("ex2.approx.ftz.f32 %0, %1;" : "=f"(r) : "f"(x)); return r; }
__device__ __forceinline__ uint32_t pack2(float lo, float hi) {
    uint32_t r;
    asm("cvt.rn.bf16x2.f32 %0, %1, %2;" : "=r"(r) : "f"(hi), "f"(lo));
    return r;
}
__device__ __forceinline__ float bfr(float x) { return __uint_as_float(pack2(0.f, x)); }
__device__ __forceinline__ uint32_t badd2(uint32_t a, uint32_t b) { uint32_t r; asm("add.rn.bf16x2 %0, %1, %2;" : "=r"(r) : "r"(a), "r"(b)); return r; }
__device__ __forceinline__ uint32_t bsub2(uint32_t a, uint32_t b) { uint32_t r; asm("sub.rn.bf16x2 %0, %1, %2;" : "=r"(r) : "r"(a), "r"(b)); return r; }
__device__ __forceinline__ uint32_t bmul2(uint32_t a, uint32_t b) { uint32_t r; asm("mul.rn.bf16x2 %0, %1, %2;" : "=r"(r) : "r"(a), "r"(b)); return r; }
__device__ __forceinline__ float bf_lo(uint32_t w) { return __uint_as_float(w << 16); }
__device__ __forceinline__ float bf_hi(uint32_t w) { return __uint_as_float(w & 0xffff0000u); }
__device__ __forceinline__ float F(uint32_t t) { return __uint_as_float(t); }
__device__ __forceinline__ uint32_t lds16(uint32_t a) { unsigned short h; asm volatile("ld.shared.u16 %0, [%1];" : "=h"(h) : "r"(a) : "memory"); return h; }
__device__ __forceinline__ uint32_t lds32(uint32_t a) { uint32_t v; asm volatile("ld.shared.u32 %0, [%1];" : "=r"(v) : "r"(a) : "memory"); return v; }
__device__ __forceinline__ uint2 lds64(uint32_t a) {
    uint2 v; asm volatile("ld.shared.v2.u32 {%0,%1}, [%2];" : "=r"(v.x), "=r"(v.y) : "r"(a) : "memory"); return v;
}
__device__ __forceinline__ uint4 lds128(uint32_t a) {
    uint4 v; asm volatile("ld.shared.v4.u32 {%0,%1,%2,%3}, [%4];" : "=r"(v.x), "=r"(v.y), "=r"(v.z), "=r"(v.w) : "r"(a) : "memory"); return v;
}
__device__ __forceinline__ float sum8(const uint4& u, const uint4& v) {
    return ((F(u.x) + F(u.y)) + (F(u.z) + F(u.w))) + ((F(v.x) + F(v.y)) + (F(v.z) + F(v.w)));
}
__device__ __forceinline__ void sts16(uint32_t a, uint32_t v) { asm volatile("st.shared.u16 [%0], %1;" ::"r"(a), "h"((unsigned short)v) : "memory"); }
__device__ __forceinline__ void sts32(uint32_t a, uint32_t v) { asm volatile("st.shared.u32 [%0], %1;" ::"r"(a), "r"(v) : "memory"); }
__device__ __forceinline__ void stsf(uint32_t a, float v) { asm volatile("st.shared.f32 [%0], %1;" ::"r"(a), "f"(v) : "memory"); }
__device__ __forceinline__ void stsf2(uint32_t a, float x, float y) { asm volatile("st.shared.v2.f32 [%0], {%1,%2};" ::"r"(a), "f"(x), "f"(y) : "memory"); }
__device__ __forceinline__ void stsf4(uint32_t a, float x, float y, float z, float w) {
    asm volatile("st.shared.v4.f32 [%0], {%1,%2,%3,%4};" ::"r"(a), "f"(x), "f"(y), "f"(z), "f"(w) : "memory");
}
template <int ID, int N> __device__ __forceinline__ void bar_sync() { asm volatile("bar.sync %0, %1;" ::"n"(ID), "n"(N) : "memory"); }
template <int ID, int N> __device__ __forceinline__ void bar_arrive() { asm volatile("bar.arrive %0, %1;" ::"n"(ID), "n"(N) : "memory"); }
__device__ __forceinline__ void fence_async() { asm volatile("fence.proxy.async.shared::cta;" ::: "memory"); }
__device__ __forceinline__ float shx(float v, int m) { return __shfl_xor_sync(0xffffffffu, v, m); }
__device__ __forceinline__ float shi(float v, int l) { return __shfl_sync(0xffffffffu, v, l); }
__device__ __forceinline__ uint32_t shi(uint32_t v, int l) { return __shfl_sync(0xffffffffu, v, l); }
__device__ __forceinline__ uint32_t opaque(uint32_t x) { asm volatile("mov.u32 %0, %0;" : "+r"(x)); return x; }
__device__ __forceinline__ const char* opaque(const char* x) { asm volatile("mov.u64 %0, %0;" : "+l"(x)); return x; }
constexpr float LOG2E = 1.4426950408889634f, SCALE = 0.07216878364870322f;

#define TRACE(idx) do {} while (0)
#define TRACES(slot) do {} while (0)

__device__ __forceinline__ uint32_t probe_near(const Params& p, int w, int lane) {
    const int cta = blockIdx.x;
    const char* pr = p.scr + SCR_O + head_off(cta >> 2) + 2048 + w * 256 + (cta & 3) * 64;
    st_pkt2_if(lane < 4, pr + lane * 16, 0, 0, 0, 0);
    uint32_t best0 = ~0u, best1 = ~0u;
#pragma unroll 1
    for (int i = w & 1; i < 6 + (w & 1); i++) {
        uint32_t c = clk32(), v = 0;
        if (lane == 0) asm volatile("atom.relaxed.gpu.global.add.u32 %0, [%1], 1;" : "=r"(v) : "l"(pr + (i & 1) * HALF) : "memory");
        c += __shfl_sync(0xffffffffu, v, 0) >> 16;
        c = clk32() - c;
        if (i & 1) best1 = min(best1, c); else best0 = min(best0, c);
    }
    return min(best0, 0xffffu) | min(best1, 0xffffu) << 16;
}
__device__ __forceinline__ uint32_t near_half() {
    const uint4 a = lds128(SM_NEAR), b = lds128(SM_NEAR + 16);
    const uint32_t m = __vminu2(__vminu2(__vminu2(a.x, a.y), __vminu2(a.z, a.w)), __vminu2(__vminu2(b.x, b.y), __vminu2(b.z, b.w)));
    return head_near(blockIdx.x >> 2, ((m & 0xffffu) > m >> 16) != (CFG(FLIP) != 0) ? HALF : 0);
}

__device__ __forceinline__ int kv_group(int k, int t) {
    const int cta = blockIdx.x;
    return ((k * NHEAD + (cta >> 2)) * SK + (SK - WIN) + (cta & 3) * 256 + t * 32) / 8;
}
__device__ __forceinline__ uint32_t phase_ns() { return (((blockIdx.x >> 2) * 13) & 31) * CFG(STAG) / 32; }

__device__ __forceinline__ void ln_fast(float s, float q, float& mean, float& rstd) {
    mean = s * (1.f / DM);
    asm("rsqrt.approx.ftz.f32 %0, %1;" : "=f"(rstd) : "f"(fmaxf(fmaf(-mean, mean, fmaf(q, 1.f / DM, 1e-5f)), 1e-5f)));
}
__device__ __forceinline__ void q_role(const Params& p, int lane) {
    const int cta = blockIdx.x;
    mbar_wait(bar_at(B_EP), 0);
    const uint32_t epoch = lds32(SM_EPOCH), near = head_near(cta >> 2, near_half());
    auto sums = [&](float& S0, float& S1) {
        bar_sync<3, 288>();
        const uint32_t ra = SM_PQ + lane * 16;
        S0 = sum8(lds128(ra), lds128(ra + 1024)); S1 = sum8(lds128(ra + 512), lds128(ra + 1536));
    };
    float cs0, cs1;
    {
        uint32_t q0 = 0, q1 = 0, q2 = 0, q3 = 0;
#pragma unroll 1
        for (int r = 0; r < NB; r++) {
            sums(cs0, cs1);
            bar_arrive<7, 288>();
            q0 = q1; q1 = q2; q2 = q3; q3 = pack2(cs0, cs1);
        }
        const uint32_t t0 = shi(q3, 3 * lane - 72), t1 = shi(q3, 3 * lane - 71), t2 = shi(q3, 3 * lane - 70), tag = epoch << 8 | 0x40;
        const char* box = p.scr + SCR_O + head_off(cta >> 2) + 2048 + (lane >> 2) * 256 + (lane & 3) * 16;
        st_pkt2_if(true, box + (cta & 3) * 64, lane < 24 ? q0 : t0, lane < 24 ? q1 : t1, lane < 24 ? q2 : t2, tag);
        const uint32_t qd = SM_Q + (lane < 24 ? lane * 4 : 3 * 384 + (lane - 24) * 12), step = lane < 24 ? 384 : 4;
#pragma unroll 1
        for (int j = 0; j < 4; j++) {
            uint4 v;
            SPIN_DECL;
            do {
                __nanosleep(200);
                v = ld_pkt(box + near + j * 64);
                SPIN_CHECK(j);
            } while (__any_sync(0xffffffffu, v.w != tag));
            sts32(qd + j * 96, v.x); sts32(qd + j * 96 + step, v.y); sts32(qd + j * 96 + 2 * step, v.z);
        }
        mbar_arrive(bar_at(B_QR));
    }
    sums(cs0, cs1);
    bar_arrive<7, 288>();
    const char* const src = p.scr + SCR_Q + head_off(cta >> 2) + lane * 8 + near;
    const char* const dst = src + (cta & 3) * 192;
    const uint32_t qd = SM_Q + NB * 384 + lane * 4;
#pragma unroll 1
    for (int k = 0; k < NB; k++) {
        float S0, S1, mean, rstd;
        sums(S0, S1);
        ln_fast(shi(S1, 24), shi(S0, 24), mean, rstd);
        const uint32_t qq = pack2(fmaf(-mean, cs0, S0) * rstd, fmaf(-mean, cs1, S1) * rstd), tag = epoch * NB + k;
        st_pkt8_if(lane < 24, dst + ((int)HALF - 2 * (int)near), qq, tag);
        st_pkt8_if(lane < 24, dst, qq, tag);
        TRACES(k * 12 + 5);
        uint2 a, b, c;
        SPIN_DECL;
        do {
            a = ld_pkt8(src); b = ld_pkt8(src + 256); c = ld_pkt8(src + 512);
            SPIN_CHECK(k);
            sts32(qd, a.x); sts32(qd + 128, b.x); sts32(qd + 256, c.x);
        } while (__any_sync(0xffffffffu, a.y != tag || b.y != tag || c.y != tag));
        mbar_arrive(bar_at(B_QR));
    }
}

struct Maps { CUtensorMap k, v, q, o, g, u; };
__device__ __forceinline__ void load_role(const Params& p, const CUtensorMap* tmKV, int lane, uint32_t t0) {
    const int cta = blockIdx.x;
    t0 += phase_ns();
#pragma unroll 1
    for (int i = 1; i < 5; i++) {
        wait_ns(t0 + i * CFG(TICK0));
        if (elect_one()) l2_prefetch(p.wq + (size_t)(128 * i + cta) * 12288, 12288);
    }
    uint32_t plan[2];
#pragma unroll
    for (int i = 0; i < 2; i++) {
        const int j = lane + 32 * i, k = j >> 4, t = j & 15, u = t >> 1, jw = j - CFG(WIN);
        const int sb = k == 0 ? B_WC + (t >= 8) + (t >= 14) : t >= 12 ? B_RK + u - 5 : t >= 4 ? B_RR + t - 4 : t >= 2 ? B_RP : k > 1 ? B_RK + 3 : B_RR + t;
        const uint32_t sw = sb * 8 | (j < 18 ? 0 : (t >= 12 || u == 1 ? k - 1 : k) & 1) << 9;
        plan[i] = sw | (jw < 0 ? sw : (B_F1 + (jw & 15)) * 8 | ((jw >> 4) & 1) << 9) << 10 |
                  (slot_at(slots(k), t < 8 ? pass_nibble(k, u) : u) * 2 + (t & 1)) << 20 | (t < 10 && j >= 8 && j < 56) << 25;
    }
    bar_sync<6, 64>();
    wait_ns(t0 + kb_ns(60));
    if (elect_one()) bulk_load(ST_WD, p.wd + cta * 15360, 15360, bar_at(B_W));
#pragma unroll 1
    for (int i = 0; i < 5; i++) {
        wait_ns(t0 + kb_ns(75) + i * kb_ns(6));
        if (elect_one()) { l2_prefetch(p.wg + (128 * i + cta) * 3072, 3072); l2_prefetch(p.wu + (128 * i + cta) * 3072, 3072); }
    }
#pragma unroll 1
    for (int i = 0; i < 6; i++) {
        wait_ns(t0 + kb_ns(105) + min(i, 4) * kb_ns(10));
        if (elect_one()) l2_prefetch(p.wo + (size_t)((cta >> 2) * DH + 32 * i + 8 * (cta & 3)) * 1280, 10240);
    }
    t0 += batch_ns(0);
    int jp = 0, shift = 0;
    uint32_t earliest = t0;
    auto requested = [&](uint32_t now) {
        shift = max(max(shift - CFG(GAIN), 0), (int)(now - t0) - (jp < 12 ? CFG(LMAX0) : CFG(LMAX)));
        TRACE(128 + jp);
        t0 += tick_ns(++jp);
    };
    const int grp0 = kv_group(0, 0);
    auto group = [&](int j) { return grp0 + (j >> 4) * (NHEAD * SK / 8) + (j & 7) * 4; };
#pragma unroll 1
    for (int j = 0; j < 16 * NB; j++) {
        const uint32_t pl = __shfl_sync(0xffffffffu, j & 32 ? plan[1] : plan[0], j);
        const int jmax = min(j + CFG(PMAX), 16 * NB);
        uint32_t now;
        SPIN_DECL;
        while (true) {
            const bool ok = mbar_test2(SM_BAR + (pl & 511), (pl >> 9) & 1, SM_BAR + ((pl >> 10) & 511), (pl >> 19) & 1);
            now = now_ns();
            const int late = now - t0 - shift;
            if (ok && (jp > j ? (int)(now - earliest) : late) >= 0) break;
            if (late >= (jp > j ? 0 : CFG(PGRACE)) && jp < jmax) {
                if (elect_one())
                    asm volatile("cp.async.bulk.prefetch.tensor.4d.L2.global [%0, {%1, %1, %1, %2}];" ::"l"(tmKV + ((jp >> 3) & 1)), "r"(0), "r"(group(jp)) : "memory");
                requested(now);
            }
            SPIN_CHECK(j);
        }
        if (elect_one()) {
            mbar_expect_tx(bar_at(B_F1 + (j & 15)), TILE);
            tma_tile(SB + ((pl >> 20) & 31) * TILE, tmKV + ((j >> 3) & 1), group(j), bar_at(B_F1 + (j & 15)), pl >> 25 ? POL_NORMAL : POL_FIRST);
        }
        TRACE(256 + j);
        earliest = now + CFG(VSTEP);
        if (jp == j) requested(now);
    }
}

__device__ __forceinline__ void reload_role(const Params& p, const Maps* tm, uint32_t t0) {
    const CUtensorMap* const tmK = &tm->k;
    const CUtensorMap* const tmV = &tm->v;
    const int cta = blockIdx.x;
    t0 += CFG(TICK0) + CFG(WLAG) + phase_ns();
#pragma unroll 1
    for (int i = 0; i < 5; i++) {
        wait_ns(t0 + i * CFG(TICK0));
        if (elect_one()) tma2d(ST_WQ + i * 12288, &tm->q, 48 * cta, 128 * i, bar_at(B_W));
        if (i == 1) bar_sync<5, 480>();
    }
#pragma unroll 1
    for (int i = 0, o = 0; i < 10;) {
        const uint32_t now = now_ns() - t0;
        if (o < 6 && (int)now >= kb_ns(105) + o * kb_ns(10)) {
            if (elect_one()) tma2d(ST_WO + o * 10240, &tm->o, 160 * (cta & 3), (cta >> 2) * DH + 32 * o, bar_at(B_W + 1));
            o++;
        } else if ((int)now >= kb_ns(77) + i * CFG(GSTEP) && (i < 9 || o == 6)) {
            if (elect_one()) tma2d(ST_WG + (i & 1) * 20480 + (i >> 1) * 4096, i & 1 ? &tm->u : &tm->g, (12 * cta) & ~7, 128 * (i >> 1), bar_at(B_W + 2));
            i++;
        }
    }
#pragma unroll 1
    for (int k = 0; k < NB - 1; k++) {
        mbar_wait(bar_at(B_RK), k & 1);
        if (elect_one()) {
            const uint32_t dst = SB + slot_at(slots(k), 0) * PAIR;
            mbar_expect_tx(bar_at(B_FL), PAIR);
            tma_tile(dst, tmV, kv_group(k, 0), bar_at(B_FL), POL_FIRST);
            tma_tile(dst + TILE, tmV, kv_group(k, 1), bar_at(B_FL), POL_FIRST);
        }
        mbar_wait(bar_at(B_RV), k & 1);
        uint32_t due = now_ns() + (k == NB - 2 ? 0 : CFG(RLAG));
        if (elect_one()) mbar_expect_tx(bar_at(B_F3), 4 * PAIR);
#pragma unroll 1
        for (int t = 0; t < 8; t++) {
            wait_ns(due);
            due += k == NB - 2 ? CFG(RSTEP3) : CFG(RSTEP);
            if (elect_one())
                tma_tile(SB + slot_at(slots(k + 1), t >> 1) * PAIR + (t & 1) * TILE, tmK, kv_group(k + 1, t), bar_at(B_F3), POL_FIRST);
        }
        TRACE(121 + k);
    }
}

__device__ __forceinline__ void zero_role(const Params& p, int lane, unsigned ticket, uint32_t t0) {
    const int cta = blockIdx.x;
    const uint32_t epoch = __shfl_sync(0xffffffffu, ticket, 0) / NCTA + 1;
    if (lane == 0) { sts32(SM_EPOCH, epoch); mbar_arrive(bar_at(B_EP)); }
    mbar_wait(bar_at(B_EP), 0);
#pragma unroll 1
    for (int k = 0; k < NB + 2; k++) {
        lane = opaque(lane);
        const int cl = 2 * (cta & 15) + (lane & 1);
        const int col = 80 * (cta >> 4) + (cl & 2 ? 48 : 0) + (cl >> 2) + (cl & 1 ? 8 : 0);
        const char* own = p.scr + (cl >> 2) * 256 + (cl & 3) * 16;
        uint32_t v0 = 0, v1 = 0, v2 = 0;
        if (lane < 4 && k < NB) {
            const unsigned short* xp = p.x + k * DM + col;
            v0 = __ldg(xp) << 16; v1 = __ldg(xp + 16) << 16; v2 = cl & 2 ? 0 : __ldg(xp + 32) << 16;
        }
        uint4 r;
        if (k == 1) mbar_wait(bar_at(B_RK), 0);
        if (k > 1) {
            mbar_wait(bar_at(B_FIN), k & 1);
            r = lds128(SM_FIN + (lane & 1) * 16);
        }
        if (k < NB) {
            const int lg = lane >> 3, ty = (lane & 7) >> 1;
            const char* dst = own + acc_off((k - (lg >> 1)) & 3, lg != 0, cta >> 4) + ty * HALF;
            wait_ns(t0 + batch_ns(k) + CFG(ZTILE) * CFG(TICK0));
            if (lg == 0 || (lg == 1 && (ty < 2 || k == NB - 1)) || (lg == 2 && k > 0 && ty > 1)) {
                st_pkt(dst, v0, v1, v2, 0);
                asm volatile("atom.relaxed.gpu.global.add.f32 %0, [%1+12], %2;" : "=r"(v0) : "l"(dst), "f"(lane < 4 ? 1.f : 0.f) : "memory");
            }
            if (__any_sync(0xffffffffu, v0 != 0)) __trap();
            const char* cnt = p.scr + SCR_COUNT;
            if (lane < 2) asm volatile("red.relaxed.gpu.global.add.u32 [%0], 1;" ::"l"(cnt + lane * HALF) : "memory");
            const uint32_t target = ((epoch - 1) * NB + k + 1) * NCTA;
            cnt += near_half();
            SPIN_DECL;
            uint32_t v;
            do {
                __nanosleep(100);
                asm volatile("ld.relaxed.gpu.global.u32 %0, [%1];" : "=r"(v) : "l"(cnt) : "memory");
                SPIN_CHECK(v);
            } while (__any_sync(0xffffffffu, (int)(v - target) < 0));
        }
        __syncwarp();
        if (lane == 0) mbar_arrive(bar_at(B_Z));
        if (k > 1) {
            const int b = k - 2;
            const char* src = own + acc_off(b, 1, cta >> 4) + (2 + ((lane >> 1) & 1)) * HALF;
            unsigned short* o = p.out + b * DM + col + (lane >> 2) * 16;
            const bool on = !(lane & 2) && lane < (cl & 2 ? 8 : 12);
            wait_clk(clk32() + CFG(DLY_F));
            float cnt;
            SPIN_DECL;
            do {
                const uint4 v = ld_pkt(src);
                SPIN_CHECK(k);
                cnt = F(v.w) + shx(F(v.w), 2);
                const float y0 = F(v.x) + shx(F(v.x), 2), y1 = F(v.y) + shx(F(v.y), 2), y2 = F(v.z) + shx(F(v.z), 2);
                const uint32_t x01 = badd2(r.x, badd2(r.y, bmul2(pack2(y0, y1), r.w)));
                const uint32_t x2 = badd2(r.z, badd2(r.z >> 16, bmul2(pack2(y2, 0.f), r.w)));
                if (cnt == NCTA && on) *o = lane < 4 ? x01 : lane < 8 ? x01 >> 16 : x2;
            } while (__any_sync(0xffffffffu, cnt != NCTA));
            TRACES((2 * b + 1) * 6 + 4);
        }
    }
}

__host__ __device__ constexpr uint32_t desc_lo(uint32_t addr) { return ((addr & 0x3FFFFu) >> 4) | (1u << 16); }
constexpr uint32_t DESC_HI_TILE = (3072u >> 4) | (1u << 30);
constexpr uint32_t DESC_HI_VEC = 1u;
template <int TA, int AOFF, int BOFF>
__device__ __forceinline__ void wgmma_n8(float (&d)[4], uint32_t alo, uint32_t blo, int accumulate) {
    asm volatile("{\n.reg .pred p;\n.reg .b32 a, b;\n.reg .b64 da, db;\nsetp.ne.b32 p, %6, 0;\n"
                 "add.u32 a, %4, %8;\nadd.u32 b, %5, %9;\nmov.b64 da, {a, %10};\nmov.b64 db, {b, %11};\n"
                 "wgmma.mma_async.sync.aligned.m64n8k16.f32.bf16.bf16 {%0,%1,%2,%3}, da, db, p, 1, 1, %7, 0;\n}"
                 : "+f"(d[0]), "+f"(d[1]), "+f"(d[2]), "+f"(d[3])
                 : "r"(alo), "r"(blo), "r"(accumulate), "n"(TA), "n"(AOFF >> 4), "n"(BOFF >> 4), "n"(DESC_HI_TILE), "n"(DESC_HI_VEC));
}
template <int KS, int END>
__device__ __forceinline__ void qk_steps(float (&d)[4], uint32_t alo, uint32_t blo) {
    if constexpr (KS < END) {
        wgmma_n8<0, (KS >> 2) * 1024 + (KS & 3) * 32, KS * 32>(d, alo, blo, KS > 0);
        qk_steps<KS + 1, END>(d, alo, blo);
    }
}
__device__ __forceinline__ void pv_steps(float (&e)[3][4], uint32_t alo, uint32_t blo, int acc) {
    wgmma_n8<1, 0, 0>(e[0], alo, blo, acc); wgmma_n8<1, 1024, 0>(e[1], alo, blo, acc); wgmma_n8<1, 2048, 0>(e[2], alo, blo, acc);
    wgmma_n8<1, 6144, 32>(e[0], alo, blo, 1); wgmma_n8<1, 7168, 32>(e[1], alo, blo, 1); wgmma_n8<1, 8192, 32>(e[2], alo, blo, 1);
}
__device__ __forceinline__ void wg_fence() { asm volatile("wgmma.fence.sync.aligned;" ::: "memory"); }
__device__ __forceinline__ void wg_commit() { asm volatile("wgmma.commit_group.sync.aligned;" ::: "memory"); }
template <int N> __device__ __forceinline__ void wg_wait() { asm volatile("wgmma.wait_group.sync.aligned %0;" ::"n"(N) : "memory"); }
__device__ __forceinline__ void acc_ready(float (&d)[4]) { asm volatile("" : "+f"(d[0]), "+f"(d[1]), "+f"(d[2]), "+f"(d[3]) :: "memory"); }
__device__ __forceinline__ uint32_t score_pair(float (&d)[4], int lane) {
    acc_ready(d);
    const uint32_t r = pack2(d[0], d[2]);
    return shi(pack2(bf_lo(r) * SCALE, bf_hi(r) * SCALE), lane & 28);
}

__device__ __forceinline__ void attention_role(const Params& p, int w, int lane) {
    const int cta = blockIdx.x, t4 = lane & 3, g = lane >> 2;
    mbar_wait(bar_at(B_EP), 0);
    const uint32_t tag0 = lds32(SM_EPOCH) * NB;
    const char* const odst = p.scr + SCR_O + head_off(cta >> 2) + (2 * w + (g >> 2)) * 256 + (cta & 3) * 64 + (g & 3) * 16;
    const uint32_t pdst = SM_P + t4 * PSTR + (16 * w + g) * 2;
    auto softmax = [&](uint32_t sc, int ps) -> uint32_t {
        const float s0 = bf_lo(sc), s1 = bf_hi(sc);
        int key = __float_as_int(fmaxf(s0, s1));
        key ^= (key >> 31) & 0x7fffffff;
        key = __reduce_max_sync(0xffffffffu, key);
        sts32(SM_MAX + w * 4, key);
        bar_sync<4, 128>();
        const uint4 mx = lds128(SM_MAX);
        key = max(max((int)mx.x, (int)mx.y), max((int)mx.z, (int)mx.w));
        key ^= (key >> 31) & 0x7fffffff;
        const float mb = __int_as_float(key) * LOG2E;
        const uint32_t pp = pack2(fast_ex2(fmaf(s0, LOG2E, -mb)), fast_ex2(fmaf(s1, LOG2E, -mb)));
        sts16(pdst + ps * 4 * PSTR, pp); sts16(pdst + ps * 4 * PSTR + 16, pp >> 16);
        uint32_t fs;
        asm volatile("redux.sync.add.u32 %0, %1, 0xffffffff;" : "=r"(fs) : "r"(__float2uint_rn((bf_lo(pp) + bf_hi(pp)) * 8388608.f)));
        fence_async();
        bar_sync<4, 128>();
        sts32(SM_SUM + ps * 16 + w * 4, fs);
        return key;
    };
    auto aux_word = [&](uint32_t mx, const uint4& u, int k) {
        const float l = __uint2float_rn((u.x + u.y) + (u.z + u.w)) * (1.f / 8388608.f);
        return (g < 4 ? mx : (__float_as_uint(l) + 0x80u) & 0xffffff00u) | ((tag0 + k) & 0x7fu) | 0x80u;
    };
    auto send = [&](float (&e)[3][4], uint32_t aux, int ps) {
        acc_ready(e[0]); acc_ready(e[1]); acc_ready(e[2]);
        const uint32_t o0 = pack2(e[0][0], e[0][2]), o1 = pack2(e[1][0], e[1][2]), o2 = pack2(e[2][0], e[2][2]);
        st_pkt2_if(t4 == 0, odst + ps * 2048, o0, o1, o2, aux);
        mbar_arrive_if(lane == 0, bar_at(ps ? B_RV : B_PS));
    };
    mbar_wait(bar_at(B_QR), 0);
    TRACES(73);
#pragma unroll 1
    for (int it = 0; it <= NB; it++) {
        uint32_t m1 = 0;
        if (it < NB) {
            const uint32_t tab = slots(it);
            const uint32_t ka = SB + (2 * w + ((lane >> 3) & 1)) * 3072 + (lane & 7) * 128 + (((lane >> 4) ^ (lane & 7)) << 4);
            const uint32_t qa = SM_Q + it * 384 + (lane >> 3) * 16;
            uint32_t sc = 0;
#pragma unroll 1
            for (int u = 0; u < 4; u++) {
                const uint32_t base = ka + slot_at(tab, pass_nibble(it, u)) * PAIR;
                mbar_wait(bar_at(B_F1 + 2 * u + (w >> 1)), it & 1);
                float d0[4] = {}, d1[4] = {};
#pragma unroll
                for (int c = 0; c < 6; c++) {
                    uint32_t a0[4], a1[4], b[4];
                    ldsm4(b, qa + c * 64);
                    ldsm4(a0, (base ^ ((c & 1) * 64)) + (c >> 1) * 1024);
                    ldsm4(a1, (base ^ ((c & 1) * 64 + 32)) + (c >> 1) * 1024);
                    mma16816(d0, a0[0], a0[1], a0[2], a0[3], b[0], b[1]);
                    mma16816(d1, a1[0], a1[1], a1[2], a1[3], b[2], b[3]);
                }
                const uint32_t r = pack2(d0[0] + d1[0], d0[2] + d1[2]);
                mbar_arrive_if(lane == 0, bar_at(B_RR + 2 * u + (w >> 1)));
                if (t4 == u) sc = pack2(bf_lo(r) * SCALE, bf_hi(r) * SCALE);
            }
            m1 = softmax(sc, 0);
        }
        if (it > 0) {
            const int k = it - 1;
            const uint32_t tab = slots(k);
            const uint32_t v0 = slot_at(tab, k < NB - 1 ? 0 : 4);
            TRACES(48 + k * 6);
            if (k > 0) mbar_wait(bar_at(B_F3), it & 1);
            mbar_wait(bar_at(B_QR), it & 1);
            fence_async();
            TRACES(49 + k * 6);
            float d[4][4] = {};
#pragma unroll
            for (int u = 0; u < 4; u++) {
                const uint32_t alo = desc_lo(SB) + slot_at(tab, u) * (PAIR >> 4), blo = desc_lo(SM_Q + 4 * 384);
                wg_fence();
                qk_steps<0, 6>(d[u], alo, blo);
                wg_commit();
                wg_wait<1>();
                if (u > 0) mbar_arrive_if(lane == 0, bar_at(B_RK + u - 1));
                wg_fence();
                qk_steps<6, 12>(d[u], alo, blo);
                wg_commit();
                if (u < 3) wg_wait<1>();
            }
            uint32_t sc = score_pair(d[0], lane), s = score_pair(d[1], lane);
            if (t4 == 1) sc = s;
            s = score_pair(d[2], lane);
            if (t4 == 2) sc = s;
            wg_wait<0>();
            s = score_pair(d[3], lane);
            mbar_arrive_if(lane == 0, bar_at(B_RK + 3));
            if (t4 == 3) sc = s;
            TRACES(50 + k * 6);
            const uint32_t m2 = softmax(sc, 1);
            TRACES(51 + k * 6);
            float e[3][4] = {};
            uint4 u;
#pragma unroll
            for (int t = 0; t < 8; t++) {
                const int pr = ((t >> 1) + 1) & 3;
                if (t == 6 && k < NB - 1) mbar_wait(bar_at(B_FL), k & 1);
                if (t == 7) { bar_sync<4, 128>(); u = lds128(SM_SUM + 16); }
                wg_fence();
                pv_steps(e, desc_lo(SB + (t & 1) * TILE) + (pr ? slot_at(tab, 4 + pr) : v0) * (PAIR >> 4), desc_lo(SM_P + (4 + pr) * PSTR + (t & 1) * 64), t > 0);
                wg_commit();
                if (t < 7) wg_wait<1>();
                if (t == 0) st_pkt2_if(t4 == 0, odst + 2048, 0, 0, 0, 0);
            }
            const uint32_t aux = opaque(aux_word(m2, u, k));
            wg_wait<0>();
            send(e, aux, 1);
            TRACES(52 + k * 6);
        }
        if (it < NB) {
            const uint32_t tab = slots(it);
            st_pkt2_if(t4 == 0, odst, 0, 0, 0, 0);
            bar_sync<4, 128>();
            const uint32_t aux = opaque(aux_word(m1, lds128(SM_SUM), it));
            float e[3][4] = {};
#pragma unroll 1
            for (int u = 0; u < 4; u++) {
                const uint32_t alo = desc_lo(SB) + slot_at(tab, 4 + u) * (PAIR >> 4), blo = desc_lo(SM_P) + u * (PSTR >> 4);
                mbar_wait(bar_at(B_F1 + 8 + 2 * u), it & 1);
                wg_fence();
                pv_steps(e, alo, blo, u > 0);
                wg_commit();
                wg_wait<1>();
                if (u == 1) mbar_arrive_if(lane == 0, bar_at(B_RP));
                mbar_wait(bar_at(B_F1 + 9 + 2 * u), it & 1);
                wg_fence();
                pv_steps(e, alo + (TILE >> 4), blo + 4, 1);
                wg_commit();
                wg_wait<1>();
            }
            wg_wait<0>();
            send(e, aux, 0);
            TRACES(53 + it * 6);
        }
    }
}

__device__ __forceinline__ void ln_finish(float s, float q, float& mean_b, float& rden) {
    const float mean = s * (1.f / DM);
    const float var = fmaxf(fmaf(q, 1.f / DM, -mean * mean), 0.f);
    mean_b = bfr(mean);
    rden = fast_rcp(bfr(fast_sqrt(bfr(bfr(var) + 1e-5f))));
}
__device__ __forceinline__ uint32_t ln_apply(uint32_t w, float mean_b, float rden) {
    const uint32_t d = bsub2(w, __byte_perm(__float_as_uint(mean_b), 0, 0x3232));
    return pack2(bf_lo(d) * rden, bf_hi(d) * rden);
}
__device__ __forceinline__ void spread(uint32_t (&b)[10], uint32_t x01, uint32_t x2, uint32_t wa, uint32_t ra, bool e2) {
    sts16(wa, x01); sts16(wa + 8, x01 >> 16);
    sts16_if(!e2, wa + 16, x2);
    __syncwarp();
    const uint4 u = lds128(ra), v = lds128(ra + 16);
    const uint2 z = lds64(ra + 32);
    b[0] = u.x; b[1] = u.y; b[2] = u.z; b[3] = u.w; b[4] = v.x; b[5] = v.y; b[6] = v.z; b[7] = v.w; b[8] = z.x; b[9] = z.y;
}
__device__ __forceinline__ float fold(float a, float b, bool sel, int m) { return (sel ? b : a) + shx(sel ? a : b, m); }

__device__ __forceinline__ void chain_role(const Params& p, int w, int lane, uint32_t t0) {
    const int cta = blockIdx.x, h = cta >> 2, s = cta & 3;
    const int g = lane >> 2, t4 = lane & 3;
    const bool e1 = t4 & 1, e2 = t4 & 2;
    uint32_t wq[5][3][4], wo[3][5][4], wg[5][4], wh[5][2], wd[4][4];
    const int col0 = 80 * w + (e2 ? 48 : 0) + g + (e1 ? 8 : 0);
    const uint32_t xw = opaque(SM_X + w * 384 + 48 * (g >> 1) + (e2 ? 24 : 0) + (e1 ? 4 : 0) + 2 * (g & 1));
    const uint32_t xr = opaque(g == 1 ? SM_ONES : SM_X + w * 384 + (g == 3 ? 192 : 0) + 48 * t4);
    TRACES(75);
    sts32_if(lane < 12, SM_ONES + lane * 4, 0x3f803f80u);
    uint32_t zero = lane >> 5;
    const int mi = lane >> 3, mr = lane & 7;
    mbar_wait(bar_at(B_W), 0);
    TRACES(74);
    sts16(xw + 192, lds16(ST_X + 5120 + col0 * 2)); sts16(xw + 200, lds16(ST_X + 5120 + col0 * 2 + 32));
    sts16_if(!e2, xw + 208, lds16(ST_X + 5120 + col0 * 2 + 64));
#pragma unroll
    for (int i = 0; i < 5; i++)
#pragma unroll
        for (int mt = 0; mt < 3; mt++) ldsm4t(wq[i][mt], ST_WQ + (80 * w + 16 * i + mr + 8 * (mi >> 1)) * 96 + 32 * mt + 16 * (mi & 1), zero);
    const bool odd = cta & 1;
    const uint32_t lo = ST_WD + (mr + (odd ? 4 : 0)) * 1280 + 160 * w, hi = ST_WD + ((mr & 3) + (odd ? 0 : 8)) * 1280 + 160 * w;
    ldsm4t(wd[0], lo + 16 * mi, zero);
    ldsm4t(wd[1], lo + 64 + 16 * mi, zero);
    ldsm4t(wd[2], hi + 64 * (mi >> 1) + 32 * (mr >> 2) + 16 * (mi & 1), zero);
    ldsm4t(wd[3], (mi < 2 ? lo : hi) + 128 + 16 * (mi & 1), zero);
    fence_async();
    __syncwarp();
    mbar_arrive_if(lane == 0, bar_at(B_WC));
    mbar_wait(bar_at(B_EP), 0);
    const uint32_t near = __shfl_sync(0xffffffffu, near_half(), 0);
    uint32_t x01 = 0, x2 = 0, nx01 = 0, nx2 = 0;
#pragma unroll 1
    for (int n = -5; n < NROUND; n++) {
        const bool last = (ORD_LAST >> (n & 15)) & 1, head = !((ORD_NO_HEAD >> (n & 15)) & 1);
        const int k = (ORD_BATCH >> (2 * (n & 15))) & 3;
        if (n > -5 && n <= 0) bar_sync<7, 288>();
        else if (!last) bar_sync<2, 256>();
        TRACES(n <= 0 ? 83 + n : 95);
        const char* const slice = p.scr + acc_off(k, last, w);
        const char* const cell = opaque(slice + g * 256 + t4 * 16);
        if (n >= 0) {
          if (head) {
            if (!last || n == NROUND - 1) mbar_wait(bar_at(B_Z), (k + last) & 1);
            const char* src = p.scr + SCR_O + head_off(h) + head_near(h, near) + last * 2048 + (w & 6) * 256 + (lane & 15) * 16;
            const uint32_t tag = (lds32(SM_EPOCH) * NB + k) | 0x80u;
            mbar_wait(bar_at(last ? B_RV : B_PS), k & 1);
            if (!last && k < NB - 1) wait_ns(t0 + batch_ns(k + 1) + CFG(START));
            uint4 v, z;
            {
                SPIN_DECL;
                do {
                    v = ld_pkt(src); z = ld_pkt(src + 256);
                    SPIN_CHECK(n);
                } while (__any_sync(0xffffffffu, (((v.w ^ tag) | (z.w ^ tag)) & 0xffu) != 0));
            }
            TRACES(tr + 0);
            float a[3][4] = {};
            const uint32_t bb[3][2] = {{v.x, v.y}, {z.x, z.y}, {v.z, z.z}};
            float sa, sb, rl;
#pragma unroll
            for (int i = 0; i < 3; i++) {
                const uint32_t l0 = g < 4 ? bb[i][0] : 0, l1 = g < 4 ? bb[i][1] : 0, h0 = g < 4 ? 0 : bb[i][0], h1 = g < 4 ? 0 : bb[i][1];
#pragma unroll
                for (int mt = 0; mt < 5; mt++)
                    mma16816(a[mt % 3], wo[i][mt][0], wo[i][mt][1], wo[i][mt][2], wo[i][mt][3], mt < 3 ? l0 : h0, mt < 3 ? l1 : h1);
                if (i == 0) {
                    int key = v.w & 0xffffff00u;
                    key ^= (key >> 31) & 0x7fffffff;
                    key = __reduce_max_sync(0xffffffffu, key);
                    key ^= (key >> 31) & 0x7fffffff;
                    const float ws = fast_ex2((F(v.w & 0xffffff00u) - __int_as_float(key)) * LOG2E);
                    sa = shi(ws, e1 ? 8 : 0); sb = shi(ws, e1 ? 12 : 4);
                    rl = ws * F(z.w & 0xffffff00u);
                    rl += shx(rl, 4);
                }
                if (i == 1) rl += shx(rl, 8);
            }
            float y[3];
#pragma unroll
            for (int j = 2; j < 5; j++) {
                const int mt = j % 3;
                y[mt] = fold(fmaf(a[mt][0], sa, a[mt][1] * sb), fmaf(a[mt][2], sa, a[mt][3] * sb), e1, 1);
            }
            const uint32_t pa = SM_PO + w * 512 + lane * 16;
            if (w < 2) {
                const char* dst = opaque(cell + s * 16384);
                rl = fast_rcp(rl);
                bar_sync<1, 256>();
                const uint4 c1 = lds128(pa), c2 = lds128(pa + 1024), c3 = lds128(pa + 2048);
                red_cell2_if(true, dst, ((y[0] + F(c1.x)) + (F(c2.x) + F(c3.x))) * rl, ((y[1] + F(c1.y)) + (F(c2.y) + F(c3.y))) * rl,
                             ((y[2] + F(c1.z)) + (F(c2.z) + F(c3.z))) * rl);
            } else {
                stsf4(pa - 1024, y[0], y[1], y[2], 0.f);
                bar_sync<1, 256>();
            }
            TRACES(tr + 1);
            if ((ORD_NO_TAIL >> n) & 1) continue;
            const uint32_t tsend = clk32();
            if (n == 0) {
                st_pkt2_if(lane < 4, p.scr + SCR_O + head_off(h) + 2048 + w * 256 + s * 64 + lane * 16, 0, 0, 0, 0);
                __syncwarp();
            } else if (!last) {
                const char* nsrc = p.scr + acc_off(k - 1, 1, w) + near + g * 256 + t4 * 16;
                SPIN_DECL;
                do {
                    v = ld_pkt(nsrc);
                    SPIN_CHECK(n);
                    nx01 = pack2(F(v.x), F(v.y)); nx2 = pack2(F(v.z), 0.f);
                } while (__any_sync(0xffffffffu, v.w != FULL_A));
            }
            wait_clk(tsend + (w < 2 ? 0 : 60) + (n < QUIET ? CFG(DLY_AL) : CFG(DLY_A)));
            {
                SPIN_DECL;
                do {
                    v = ld_pkt(cell + near);
                    SPIN_CHECK(n);
                } while (__any_sync(0xffffffffu, v.w != FULL_A));
            }
            TRACES(tr + 2);
            x01 = pack2(F(v.x), F(v.y));
            x2 = pack2(F(v.z), 0.f);
          } else { x01 = nx01; x2 = nx2; }
        } else if (n == -1) {
            mbar_wait(bar_at(B_W + 1), 0);
            const uint32_t ln = opaque(lane);
            const int mi = ln >> 3, mr = ln & 7;
            uint32_t zero = ln >> 5;
            TRACES(76);
#pragma unroll
            for (int i = 0; i < 3; i++) {
                const int d = 16 * (w >> 1) + (mr >> 1) + 8 * (mr & 1) + (i < 2 ? 64 * (mi >> 1) + 4 * i : 128 + 4 * (mi >> 1));
#pragma unroll
                for (int mt = 0; mt < 5; mt++) ldsm4t(wo[i][mt], ST_WO + d * 320 + 160 * (w & 1) + 32 * mt + 16 * (mi & 1), zero);
            }
            fence_async();
            __syncwarp();
            mbar_arrive_if(lane == 0, bar_at(B_WC + 1));
            mbar_wait(bar_at(B_W + 2), 0);
            TRACES(77);
#pragma unroll
            for (int i = 0; i < 5; i++) {
                const uint32_t ga = ST_WG + (mi & 1) * 20480 + (80 * w + 16 * i + mr + 8 * (mi >> 1)) * 32;
                uint32_t r[4];
                ldsm4t(wg[i], ga + (odd ? 16 : 0), zero);
                ldsm4t(r, ga + (odd ? 0 : 16), zero);
#pragma unroll
                for (int kh = 0; kh < 2; kh++) {
                    const uint32_t moved = __shfl_xor_sync(0xffffffffu, odd ? r[2 * kh] : r[2 * kh + 1], 16);
                    wh[i][kh] = (g < 4) == odd ? moved : odd ? r[2 * kh + 1] : r[2 * kh];
                }
            }
            fence_async();
            __syncwarp();
            mbar_arrive_if(lane == 0, bar_at(B_WC + 2));
            TRACES(72);
            x01 = 0x3f803f80u; x2 = 0x3f80u;
        } else {
            const uint32_t xa = ST_X + (n + 5) * 1280, ln = opaque(lane);
            const int col0 = 80 * w + (ln & 2 ? 48 : 0) + (ln >> 2) + (ln & 1 ? 8 : 0);
            float sm = 0.f, sq = 0.f;
#pragma unroll
            for (int i = 0; i < 5; i++) {
                const uint2 c = lds64(xa + i * 256 + ln * 8);
                sm += (bf_lo(c.x) + bf_hi(c.x)) + (bf_lo(c.y) + bf_hi(c.y));
                sq = fmaf(bf_lo(c.x), bf_lo(c.x), fmaf(bf_hi(c.x), bf_hi(c.x), fmaf(bf_lo(c.y), bf_lo(c.y), fmaf(bf_hi(c.y), bf_hi(c.y), sq))));
            }
            x01 = lds16(xa + col0 * 2) | lds16(xa + col0 * 2 + 32) << 16;
            x2 = lds16(xa + col0 * 2 + 64);
#pragma unroll
            for (int o = 16; o; o >>= 1) { sm += shx(sm, o); sq += shx(sq, o); }
            float mean_b, rden;
            ln_finish(sm, sq, mean_b, rden);
            x01 = ln_apply(x01, mean_b, rden);
            x2 = ln_apply(x2, mean_b, rden);
        }
        if (n >= -1) {
            uint32_t b[10];
            spread(b, x01, x2, xw, xr, e2);
            float a[2][4] = {};
#pragma unroll
            for (int i = 0; i < 5; i++) {
                mma16816(a[0], wg[i][0], wg[i][1], wg[i][2], wg[i][3], b[2 * i], b[2 * i + 1]);
                mma16816(a[1], wh[i][0], b[2 * i], wh[i][1], b[2 * i + 1], b[2 * i], b[2 * i + 1]);
            }
            stsf(SM_PG + (w >> 2) * 512 + (g + 8 * t4) * 16 + (w & 3) * 4, e2 ? (e1 ? a[1][2] : a[1][0]) : (e1 ? a[0][2] : a[0][0]));
            const uint2 cs = lds64(SM_CSG + lane * 48);
            const char* dst = opaque(cell + 3 * HALF - near);
            bar_sync<2, 256>();
            const float S = sum8(lds128(SM_PG + lane * 16), lds128(SM_PG + 512 + lane * 16));
            const float sx = shi(S, 25), sq = shi(S, 24), Su = shi(S, lane + (lane < 16 ? 8 : 4));
            if (n < 0) {
                if (w == 0) stsf2(SM_CSG + lane * 48, S, Su);
            } else {
                float mean_b, rden;
                ln_fast(sx, sq, mean_b, rden);
                const float gv = bfr(fmaf(-mean_b, F(cs.x), S) * rden), uv = bfr(fmaf(-mean_b, F(cs.y), Su) * rden);
                const float sg = fast_rcp(1.f + fast_ex2(-LOG2E * gv));
                const uint32_t hb = pack2(bfr(gv * sg) * uv, 0.f);
                const uint32_t b0 = __byte_perm(shi(hb, 2 * t4), shi(hb, 2 * t4 + 1), 0x5410);
                const uint32_t b1 = __byte_perm(shi(hb, e1 ? 18 : 16), shi(hb, e1 ? 19 : 17), 0x5410);
                const bool up = g >= 4;
                const uint32_t l0 = up ? 0 : b0, h0 = up ? b0 : 0;
                const uint32_t l1 = up ? 0 : b1, h1 = up ? b1 : 0;
                float d[3][4] = {};
                mma1688(d[0], wd[0][0], wd[0][1], l0); mma1688(d[1], wd[0][2], wd[0][3], l0); mma1688(d[2], wd[1][0], wd[1][1], l0);
                mma1688(d[0], wd[1][2], wd[1][3], h0); mma1688(d[1], wd[3][0], wd[3][1], h0);
                mma1688(d[2], wd[2][2], wd[2][3], e2 ? 0 : l1);
                mma1688(d[0], wd[2][0], wd[2][1], e2 ? 0 : l1); mma1688(d[1], wd[2][0], wd[2][1], e2 ? l1 : 0);
                mma1688(d[0], wd[2][2], wd[2][3], e2 ? h1 : 0); mma1688(d[1], wd[3][2], wd[3][3], e2 ? 0 : h1);
                red_cell(dst, e1 ? d[0][2] : d[0][0], e1 ? d[1][2] : d[1][0], e1 ? d[2][2] : d[2][0]);
                const uint32_t tsend = clk32();
                TRACES(tr + 3);
                if (last && w != cta >> 4) continue;
                if (!last && w == 0) st_pkt82_if(lane < 24, p.scr + SCR_Q + head_off(h) + (24 * s + lane) * 8, 0, 0);
                const float sgr = shi(sg, 27);
                const uint32_t sg2 = pack2(sgr, sgr);
                const uint32_t n01 = opaque(pack2((bf_lo(x01) - mean_b) * rden, (bf_hi(x01) - mean_b) * rden));
                const uint32_t n2 = opaque(pack2((bf_lo(x2) - mean_b) * rden, 0.f));
                if (last) {
                    sts128_if(lane >> 1 == (cta & 15), SM_FIN + (lane & 1) * 16, x01, n01, __byte_perm(x2, n2, 0x5410), sg2);
                    mbar_arrive_if(lane >> 1 == (cta & 15), bar_at(B_FIN));
                    __syncwarp();
                    continue;
                }
                wait_clk(tsend + (n < QUIET ? CFG(DLY_BL) : CFG(DLY_B)));
                uint4 v, z;
                {
                    SPIN_DECL;
                    do {
                        v = ld_pkt(cell + 2 * HALF); z = ld_pkt(cell + 3 * HALF);
                        SPIN_CHECK(n);
                    } while (__any_sync(0xffffffffu, F(v.w) + F(z.w) != NCTA));
                }
                x01 = badd2(x01, badd2(n01, bmul2(pack2(F(v.x) + F(z.x), F(v.y) + F(z.y)), sg2)));
                x2 = badd2(x2, badd2(n2, bmul2(pack2(F(v.z) + F(z.z), 0.f), sg2)));
                TRACES(tr + 4);
            }
        }
        {
            uint32_t b[10];
            spread(b, x01, x2, xw, xr, e2);
            float a[3][4] = {};
            const float f0 = bf_lo(x01), f1 = bf_hi(x01), f2 = e2 ? 0.f : bf_lo(x2);
            float st;
#pragma unroll
            for (int i = 0; i < 5; i++) {
#pragma unroll
                for (int mt = 0; mt < 3; mt++) {
                    mma16816(a[mt], wq[i][mt][0], wq[i][mt][1], wq[i][mt][2], wq[i][mt][3], b[2 * i], b[2 * i + 1]);
                    if (i == 0 && mt == 0) st = fold(fmaf(f0, f0, fmaf(f1, f1, f2 * f2)), (f0 + f1) + f2, g & 1, 4);
                }
                if (i < 4) st += shx(st, i < 2 ? 1 << i : 2 << i);
            }
            const uint32_t pa = SM_PQ + (w >> 2) * 1024 + (g & 1) * 512 + ((e2 ? 16 : 0) + (e1 ? 4 : 0) + (g >> 1)) * 16 + (w & 3) * 4;
            stsf(pa + 128, e2 ? st : e1 ? a[1][2] : a[1][0]);
            stsf(pa, e2 ? (e1 ? a[2][2] : a[2][0]) : (e1 ? a[0][2] : a[0][0]));
            bar_arrive<3, 288>();
            if (n >= 0 && w == cta >> 4) {
                red_cell2_if(lane >> 1 == (cta & 15), cell + (acc_off(k, 1, 0) - acc_off(k, 0, 0)), f0, f1, f2);
                __syncwarp();
            }
        }
    }
}

template <int ID> __device__ __forceinline__ void role_exit() { asm volatile("exit; // %0" ::"n"(ID)); }
constexpr int NTHREADS = 512;
#define STR2(x) #x
#define STR(x) STR2(x)
__global__ void __launch_bounds__(NTHREADS, 1)
decode_kernel(const Params p, const __grid_constant__ Maps tm) {
    extern __shared__ __align__(1024) unsigned char smem[];
    if (threadIdx.x == 0) l2_prefetch(p.wq + (size_t)blockIdx.x * 12288, 12288);
    const uint32_t t0 = now_ns() - CFG(LEAD);
    const int lane = threadIdx.x & 31;
    const int warp = __reduce_max_sync(0xffffffffu, threadIdx.x >> 5);
    if (warp < 8) {
        asm volatile("setmaxnreg.inc.sync.aligned.u32 " STR(CFG_REG_CHAIN) ";");
        bar_arrive<5, 480 + 0>();
        const uint32_t vote = probe_near(p, warp, lane);
        bar_sync<2, 256 + 32>();
        sts32(SM_NEAR + warp * 4, vote);
        mbar_arrive_if(lane == 0, bar_at(B_EP));
        chain_role(p, warp, __shfl_sync(0xffffffffu, lane, lane), t0);
        role_exit<3>();
    } else if (warp < 12) {
        asm volatile("setmaxnreg.dec.sync.aligned.u32 " STR(CFG_REG_ATT) ";");
        if (elect_one()) {
#pragma unroll 1
            for (int i = warp - 8; i < NBAR; i += 4)
                if (i < B_W || i >= B_WC) mbar_init(bar_at(i), i == B_FIN ? 2 : i == B_EP ? 9 : i == B_QR ? 32 : i == B_PS || i == B_RP ? 4 : i >= B_F3 ? 1 : i >= B_WC ? 8 : i < B_RR || i > B_RV ? 1 : i < B_RK ? 2 : 4);
            asm volatile("fence.mbarrier_init.release.cluster;" ::: "memory");
            fence_async();
        }
        bar_sync<5, 480>();
        attention_role(p, warp - 8, lane);
        role_exit<2>();
    } else {
        asm volatile("setmaxnreg.dec.sync.aligned.u32 " STR(CFG_REG_HELP) ";");
        if (warp == 12) {
            load_role(p, &tm.k, lane, t0);
            role_exit<0>();
        } else {
            if (warp == 14) {
                if (smem_u32(smem) != SB) __trap();
                if (elect_one()) {
                    asm volatile("prefetch.tensormap [%0];" ::"l"(&tm.q) : "memory");
                    mbar_init(bar_at(B_W), 1); mbar_init(bar_at(B_W + 1), 1); mbar_init(bar_at(B_W + 2), 1);
                    asm volatile("fence.mbarrier_init.release.cluster;" ::: "memory");
                    fence_async();
                    mbar_expect_tx(bar_at(B_W), 61440 + 15360 + 6400); mbar_expect_tx(bar_at(B_W + 1), 61440); mbar_expect_tx(bar_at(B_W + 2), 40960);
                    bulk_load(ST_X, p.x, 5120, bar_at(B_W));
                    bulk_load(ST_X + 5120, p.wr, 1280, bar_at(B_W));
                }
                reload_role(p, &tm, t0);
            } else {
                unsigned ticket = 0;
                if (warp == 15 && lane == 0) asm volatile("atom.relaxed.gpu.global.add.u32 %0, [%1], 1;" : "=r"(ticket) : "l"(&g_epoch) : "memory");
                if (warp == 13 && elect_one()) {
                    asm volatile("prefetch.tensormap [%0];" ::"l"(&tm.g) : "memory");
                    asm volatile("prefetch.tensormap [%0];" ::"l"(&tm.u) : "memory");
                    asm volatile("prefetch.tensormap [%0];" ::"l"(&tm.o) : "memory");
                    asm volatile("prefetch.tensormap [%0];" ::"l"(&tm.k) : "memory");
                    asm volatile("prefetch.tensormap [%0];" ::"l"(&tm.v) : "memory");
                }
                bar_sync<5, 480>();
                if (warp == 13) { bar_arrive<6, 64>(); q_role(p, lane); }
                else { bar_arrive<2, 256 + 32>(); zero_role(p, lane, ticket, t0); }
            }
            role_exit<1>();
        }
    }
}

typedef CUresult (*EncodeFn)(CUtensorMap*, CUtensorMapDataType, cuuint32_t, void*, const cuuint64_t*, const cuuint64_t*,
                             const cuuint32_t*, const cuuint32_t*, CUtensorMapInterleave, CUtensorMapSwizzle,
                             CUtensorMapL2promotion, CUtensorMapFloatOOBfill);

bool make_map(EncodeFn fn, CUtensorMap* m, const void* ptr, uint64_t cols, uint64_t rows, uint32_t bc, uint32_t br) {
    cuuint64_t dims[2] = {cols, rows};
    cuuint64_t strides[1] = {cols * 2};
    cuuint32_t box[2] = {bc, br};
    cuuint32_t es[2] = {1, 1};
    return fn(m, CU_TENSOR_MAP_DATA_TYPE_BFLOAT16, 2, const_cast<void*>(ptr), dims, strides, box, es, CU_TENSOR_MAP_INTERLEAVE_NONE,
              CU_TENSOR_MAP_SWIZZLE_NONE, CU_TENSOR_MAP_L2_PROMOTION_L2_128B, CU_TENSOR_MAP_FLOAT_OOB_FILL_NONE) == CUDA_SUCCESS;
}

bool make_kv_map(EncodeFn fn, CUtensorMap* m, const void* ptr) {
    cuuint64_t dims[4] = {64, 8, 3, (cuuint64_t)NB * NHEAD * SK / 8};
    cuuint64_t strides[3] = {DH * 2, 128, 8 * DH * 2};
    cuuint32_t box[4] = {64, 8, 3, 4};
    cuuint32_t es[4] = {1, 1, 1, 1};
    return fn(m, CU_TENSOR_MAP_DATA_TYPE_BFLOAT16, 4, const_cast<void*>(ptr), dims, strides, box, es, CU_TENSOR_MAP_INTERLEAVE_NONE,
              CU_TENSOR_MAP_SWIZZLE_128B, CU_TENSOR_MAP_L2_PROMOTION_L2_128B, CU_TENSOR_MAP_FLOAT_OOB_FILL_NONE) == CUDA_SUCCESS;
}

}

extern "C" void kernel_launch(void* const* d_in, const int* in_sizes, int n_in, void* d_out, int out_size) {
    (void)in_sizes; (void)n_in; (void)out_size;
    static EncodeFn fn = nullptr;
    static const char* scr = nullptr;
    if (!fn) {
        void* f = nullptr;
        cudaDriverEntryPointQueryResult qr;
        if (cudaGetDriverEntryPoint("cuTensorMapEncodeTiled", &f, cudaEnableDefault, &qr) != cudaSuccess || !f) return;
        void* sp = nullptr;
        if (cudaGetSymbolAddress(&sp, g_scratch) != cudaSuccess) return;
        scr = (const char*)(((uintptr_t)sp + (2 << 20) - 1) & ~(uintptr_t)((2 << 20) - 1));
        fn = (EncodeFn)f;
        cudaFuncSetAttribute(decode_kernel, cudaFuncAttributeMaxDynamicSharedMemorySize, SMEM_BYTES);
    }
    Maps tm;
    if (!make_kv_map(fn, &tm.k, d_in[1]) || !make_kv_map(fn, &tm.v, d_in[2])) return;
    if (!make_map(fn, &tm.q, d_in[3], NHEAD * DH, DM, 48, 128) || !make_map(fn, &tm.o, d_in[4], DM, NHEAD * DH, 160, 32)) return;
    if (!make_map(fn, &tm.g, d_in[7], FF, DM, 16, 128) || !make_map(fn, &tm.u, d_in[8], FF, DM, 16, 128)) return;
    Params p;
    p.x = (const unsigned short*)d_in[0];
    p.wq = (const char*)d_in[3];
    p.wo = (const char*)d_in[4];
    p.wr = (const unsigned short*)d_in[6];
    p.wg = (const char*)d_in[7];
    p.wu = (const char*)d_in[8];
    p.wd = (const char*)d_in[9];
    p.out = (unsigned short*)d_out;
    p.scr = scr;
    decode_kernel<<<NCTA, NTHREADS, SMEM_BYTES>>>(p, tm);
}
```

```cpp
#include <cuda_runtime.h>
#include <cuda_bf16.h>
#include <cuda.h>
#include <stdint.h>

namespace {

constexpr int NB = 4, DM = 640, NHEAD = 32, DH = 192, SK = 4096, WIN = 1024, FF = 1536;
constexpr int NCTA = 128;
constexpr int TILE = 12288, PAIR = 2 * TILE;

#define CFG_LIST(X) \
    X(TICK0, 476)        \
    X(TICK, 492)        \
    X(LEAD, 350)        \
    X(STAG, 500)        \
    X(WLAG, 200)        \
    X(GSTEP, 750)        \
    X(WIN, 5)        \
    X(PMAX, 3)        \
    X(PGRACE, 50)        \
    X(LMAX0, 150)        \
    X(LMAX, 200) \
    X(GAIN, 5)        \
    X(VSTEP, 250)        \
    X(RLAG, 0)        \
    X(RSTEP, 640) \
    X(RSTEP3, 450) \
    X(ZTILE, 11)        \
    X(START, 1)        \
    X(DLY_A, 410)        \
    X(DLY_AL, 100) \
    X(DLY_B, 570) \
    X(DLY_BL, 950) \
    X(DLY_F, 290) \
    X(FLIP, 0) \

#define X(n, v) constexpr int CFG_##n = v;
CFG_LIST(X)
#undef X
#define CFG(n) CFG_##n
constexpr int QUIET = 8;
#define CFG_REG_CHAIN 216
#define CFG_REG_ATT 48
#define CFG_REG_HELP 32
constexpr int KB_KV0 = 165;
__device__ __forceinline__ int kb_ns(int kb) { return kb * CFG(TICK0) / 12; }
__device__ __forceinline__ int tick_ns(int j) { return j <= 16 ? CFG(TICK0) : CFG(TICK); }
__device__ __forceinline__ int batch_ns(int k) { return kb_ns(KB_KV0) + (k ? 16 * (CFG(TICK0) + (k - 1) * CFG(TICK)) : 0); }

__device__ __forceinline__ uint32_t slots(int k) { return k & 2 ? (k & 1 ? 0x21304768u : 0x76835214u) : (k & 1 ? 0x21480765u : 0x76543210u); }
__device__ __forceinline__ int pass_nibble(int k, int u) { return k > 0 ? 4 + (u & 1) : u; }
__device__ __forceinline__ uint32_t slot_at(uint32_t tab, int u) { return (tab >> (4 * u)) & 15; }

constexpr int NROUND = 11;
constexpr uint32_t ORD_BATCH = 0x3b9910, ORD_LAST = 0x6da, ORD_NO_HEAD = 0x248, ORD_NO_TAIL = 0x092;

constexpr uint32_t SB = 1024;
constexpr uint32_t SM_BAR = SB + 9 * PAIR;
constexpr int B_F1 = 0;
constexpr int B_RR = 24;
constexpr int B_RK = 32;
constexpr int B_RV = 36;
constexpr int B_Z = 37;
constexpr int B_EP = 38;
constexpr int B_W = 39;
constexpr int B_WC = 42;
constexpr int B_FIN = 45;
constexpr int B_F3 = 46;
constexpr int B_PS = 48;
constexpr int B_RP = 49;
constexpr int B_FL = 50;
constexpr int B_QR = 51;
constexpr int NBAR = 52;
__host__ __device__ constexpr uint32_t bar_at(int i) { return SM_BAR + 8 * i; }
constexpr uint32_t SM_EPOCH = SM_BAR + 416;
constexpr uint32_t SM_MAX = SM_EPOCH + 16;
constexpr uint32_t SM_SUM = SM_MAX + 16;
constexpr uint32_t SM_NEAR = SM_SUM + 32;
constexpr uint32_t SM_FIN = SM_NEAR + 32;
constexpr uint32_t SM_Q = SM_FIN + 32;
constexpr uint32_t PSTR = 144;
constexpr uint32_t SM_P = SM_Q + 5 * 384;
constexpr uint32_t SM_X = SM_P + 8 * PSTR;
constexpr uint32_t SM_CSG = SM_X + 40;
constexpr uint32_t SM_ONES = SM_X + 8 * 384;
constexpr uint32_t SM_PG = SM_ONES + 48;
constexpr uint32_t SM_PO = SM_PG + 1024;
constexpr uint32_t SM_PQ = SM_PO;
constexpr int SMEM_BYTES = SM_PO + 3072 - SB;
static_assert(SMEM_BYTES <= 232448 && SM_Q % 16 == 0 && SM_P % 16 == 0 && SM_X % 16 == 0 && SM_PO % 16 == 0, "smem");
constexpr uint32_t ST_WQ = SB, ST_WD = SB + 3 * PAIR, ST_WO = SB + 4 * PAIR, ST_WG = SB + 7 * PAIR, ST_X = ST_WG + 40960;

__device__ unsigned g_epoch;
__device__ unsigned char g_scratch[4 << 20];
constexpr uint32_t HALF = 4096, SCR_O = 1 << 16, SCR_Q = 1 << 17, SCR_COUNT = 3 << 16;
__device__ __forceinline__ uint32_t acc_off(int k, int layer, int w) {
    return (k & 1) << 6 | layer << 7 | (w & 1) << 11 | (w >> 1) << 14 | (k + layer == NB) << 18;
}
__device__ __forceinline__ uint32_t head_off(int h) { return (h & 3) << 14 | (h & 4) << 16 | (h & 8) << 17 | (h & 16) << 9; }
__device__ __forceinline__ uint32_t head_near(int h, uint32_t near) { return near ^ HALF ^ (h & 16) << 8; }
constexpr uint32_t FULL_A = 0x42040000u;

struct Params {
    const char* wq;
    const unsigned short* x;
    const char* wo;
    const unsigned short* wr;
    const char* wg;
    const char* wu;
    const char* wd;
    unsigned short* out;
    const char* scr;
};

__device__ __forceinline__ uint32_t smem_u32(const void* p) { return (uint32_t)__cvta_generic_to_shared(p); }
__device__ __forceinline__ void mbar_init(uint32_t a, uint32_t c) { asm volatile("mbarrier.init.shared::cta.b64 [%0], %1;" ::"r"(a), "r"(c) : "memory"); }
__device__ __forceinline__ void mbar_expect_tx(uint32_t a, uint32_t b) {
    asm volatile("mbarrier.arrive.expect_tx.shared::cta.b64 _, [%0], %1;" ::"r"(a), "r"(b) : "memory");
}
__device__ __forceinline__ void mbar_arrive(uint32_t a) { asm volatile("mbarrier.arrive.shared::cta.b64 _, [%0];" ::"r"(a) : "memory"); }
constexpr uint32_t SPIN_LIMIT = 1u << 22;
#define SPIN_DECL uint32_t spins = 0
#define SPIN_CHECK(info) { if (++spins > SPIN_LIMIT) __trap(); }
__device__ __forceinline__ void mbar_wait(uint32_t a, uint32_t parity) {
    uint32_t ok;
    SPIN_DECL;
    while (true) {
        asm volatile("{\n.reg .pred p;\nmbarrier.try_wait.parity.shared::cta.b64 p, [%1], %2;\nselp.u32 %0, 1, 0, p;\n}"
                     : "=r"(ok) : "r"(a), "r"(parity) : "memory");
        if (ok) break;
        SPIN_CHECK((a - SM_BAR) / 8 * 10 + parity);
    }
}
__device__ __forceinline__ bool mbar_test2(uint32_t a, uint32_t pa, uint32_t b, uint32_t pb) {
    uint32_t ok;
    asm volatile("{\n.reg .pred p, q;\nmbarrier.test_wait.parity.shared::cta.b64 p, [%1], %2;\n"
                 "mbarrier.test_wait.parity.shared::cta.b64 q, [%3], %4;\nand.pred p, p, q;\nvote.sync.all.pred p, p, 0xffffffff;\nselp.u32 %0, 1, 0, p;\n}"
                 : "=r"(ok) : "r"(a), "r"(pa), "r"(b), "r"(pb) : "memory");
    return ok;
}
__device__ __forceinline__ uint32_t now_ns() { uint32_t t; asm volatile("mov.u32 %0, %%globaltimer_lo;" : "=r"(t) :: "memory"); return t; }
__device__ __forceinline__ uint32_t clk32() { uint32_t c; asm volatile("mov.u32 %0, %%clock;" : "=r"(c) :: "memory"); return c; }
__device__ __forceinline__ void wait_ns(uint32_t t) { while ((int)(now_ns() - t) < 0) {} }
__device__ __forceinline__ void wait_clk(uint32_t t) { while ((int)(clk32() - t) < 0) {} }
__device__ __forceinline__ bool elect_one() {
    uint32_t e;
    asm volatile("{\n.reg .pred p;\nelect.sync _|p, 0xffffffff;\nselp.u32 %0, 1, 0, p;\n}" : "=r"(e));
    return e;
}
constexpr uint64_t POL_FIRST = 0x12F0000000000000ull, POL_NORMAL = 0x1000000000000000ull;
__device__ __forceinline__ void tma_tile(uint32_t dst, const CUtensorMap* tm, int group, uint32_t bar, uint64_t pol) {
    asm volatile("cp.async.bulk.tensor.4d.shared::cluster.global.mbarrier::complete_tx::bytes.L2::cache_hint"
                 " [%0], [%1, {%3, %3, %3, %4}], [%2], %5;"
                 ::"r"(dst), "l"(tm), "r"(bar), "r"(0), "r"(group), "l"(pol) : "memory");
}
__device__ __forceinline__ void tma2d(uint32_t dst, const CUtensorMap* tm, int x, int y, uint32_t bar) {
    asm volatile("cp.async.bulk.tensor.2d.shared::cluster.global.mbarrier::complete_tx::bytes [%0], [%1, {%3, %4}], [%2];"
                 ::"r"(dst), "l"(tm), "r"(bar), "r"(x), "r"(y) : "memory");
}
__device__ __forceinline__ void bulk_load(uint32_t dst, const void* src, uint32_t bytes, uint32_t bar) {
    asm volatile("cp.async.bulk.shared::cluster.global.mbarrier::complete_tx::bytes [%0], [%1], %2, [%3];"
                 ::"r"(dst), "l"(src), "r"(bytes), "r"(bar) : "memory");
}
__device__ __forceinline__ void l2_prefetch(const void* p, uint32_t bytes) {
    asm volatile("cp.async.bulk.prefetch.L2.global [%0], %1;" ::"l"(p), "r"(bytes) : "memory");
}
__device__ __forceinline__ void mma16816(float (&c)[4], uint32_t a0, uint32_t a1, uint32_t a2, uint32_t a3, uint32_t b0, uint32_t b1) {
    asm volatile("mma.sync.aligned.m16n8k16.row.col.f32.bf16.bf16.f32 {%0,%1,%2,%3}, {%4,%5,%6,%7}, {%8,%9}, {%0,%1,%2,%3};"
                 : "+f"(c[0]), "+f"(c[1]), "+f"(c[2]), "+f"(c[3]) : "r"(a0), "r"(a1), "r"(a2), "r"(a3), "r"(b0), "r"(b1));
}
__device__ __forceinline__ void mma1688(float (&c)[4], uint32_t a0, uint32_t a1, uint32_t b0) {
    asm volatile("mma.sync.aligned.m16n8k8.row.col.f32.bf16.bf16.f32 {%0,%1,%2,%3}, {%4,%5}, {%6}, {%0,%1,%2,%3};"
                 : "+f"(c[0]), "+f"(c[1]), "+f"(c[2]), "+f"(c[3]) : "r"(a0), "r"(a1), "r"(b0));
}
__device__ __forceinline__ void ldsm4(uint32_t (&r)[4], uint32_t a) {
    asm volatile("ldmatrix.sync.aligned.m8n8.x4.shared.b16 {%0,%1,%2,%3}, [%4];"
                 : "=r"(r[0]), "=r"(r[1]), "=r"(r[2]), "=r"(r[3]) : "r"(a) : "memory");
}
__device__ __forceinline__ void ldsm4t(uint32_t (&r)[4], uint32_t a, uint32_t& zero) {
    asm volatile("ldmatrix.sync.aligned.m8n8.x4.trans.shared.b16 {%0,%1,%2,%3}, [%4];"
                 : "=r"(r[0]), "=r"(r[1]), "=r"(r[2]), "=r"(r[3]) : "r"(a + zero) : "memory");
    zero &= r[3];
}
__device__ __forceinline__ uint4 ld_pkt(const void* p) {
    uint4 v;
    asm volatile("{\n.reg .b128 t;\nld.relaxed.gpu.global.b128 t, [%4];\nmov.b128 {%0,%1,%2,%3}, t;\n}"
                 : "=r"(v.x), "=r"(v.y), "=r"(v.z), "=r"(v.w) : "l"(p) : "memory");
    return v;
}
__device__ __forceinline__ void st_pkt(const void* p, uint32_t a, uint32_t b, uint32_t c, uint32_t d) {
    asm volatile("{\n.reg .b128 t;\nmov.b128 t, {%1,%2,%3,%4};\nst.relaxed.gpu.global.b128 [%0], t;\n}"
                 ::"l"(p), "r"(a), "r"(b), "r"(c), "r"(d) : "memory");
}
__device__ __forceinline__ uint2 ld_pkt8(const void* p) {
    uint2 v;
    asm volatile("{\n.reg .b64 t;\nld.relaxed.gpu.global.b64 t, [%2];\nmov.b64 {%0,%1}, t;\n}" : "=r"(v.x), "=r"(v.y) : "l"(p) : "memory");
    return v;
}
__device__ __forceinline__ void red_cell(const char* p, float a, float b, float c) {
    asm volatile("red.relaxed.gpu.global.add.v4.f32 [%0], {%1,%2,%3,%4};" ::"l"(p), "f"(a), "f"(b), "f"(c), "f"(1.0f) : "memory");
}
#define PRED(n) "{\n.reg .pred p;\nsetp.ne.u32 p, %" #n ", 0;\n"
__device__ __forceinline__ void red_cell2_if(bool on, const char* p, float a, float b, float c) {
    asm volatile(PRED(5) "@p red.relaxed.gpu.global.add.v4.f32 [%0], {%1,%2,%3,%4};\n@p red.relaxed.gpu.global.add.v4.f32 [%0+4096], {%1,%2,%3,%4};\n}"
                 ::"l"(p), "f"(a), "f"(b), "f"(c), "f"(1.0f), "r"((uint32_t)on) : "memory");
}
__device__ __forceinline__ void st_pkt8_if(bool on, const void* p, uint32_t a, uint32_t b) {
    asm volatile(PRED(3) ".reg .b64 t;\nmov.b64 t, {%1,%2};\n@p st.relaxed.gpu.global.b64 [%0], t;\n}" ::"l"(p), "r"(a), "r"(b), "r"((uint32_t)on) : "memory");
}
__device__ __forceinline__ void st_pkt82_if(bool on, const void* p, uint32_t a, uint32_t b) {
    asm volatile(PRED(3) ".reg .b64 t;\nmov.b64 t, {%1,%2};\n@p st.relaxed.gpu.global.b64 [%0], t;\n@p st.relaxed.gpu.global.b64 [%0+4096], t;\n}"
                 ::"l"(p), "r"(a), "r"(b), "r"((uint32_t)on) : "memory");
}
__device__ __forceinline__ void st_pkt2_if(bool on, const void* p, uint32_t a, uint32_t b, uint32_t c, uint32_t d) {
    asm volatile(PRED(5) ".reg .b128 t;\nmov.b128 t, {%1,%2,%3,%4};\n@p st.relaxed.gpu.global.b128 [%0], t;\n@p st.relaxed.gpu.global.b128 [%0+4096], t;\n}"
                 ::"l"(p), "r"(a), "r"(b), "r"(c), "r"(d), "r"((uint32_t)on) : "memory");
}
__device__ __forceinline__ void mbar_arrive_if(bool on, uint32_t a) {
    asm volatile(PRED(1) "@p mbarrier.arrive.shared::cta.b64 _, [%0];\n}" ::"r"(a), "r"((uint32_t)on) : "memory");
}
__device__ __forceinline__ void sts16_if(bool on, uint32_t a, uint32_t v) {
    asm volatile(PRED(2) "@p st.shared.u16 [%0], %1;\n}" ::"r"(a), "h"((unsigned short)v), "r"((uint32_t)on) : "memory");
}
__device__ __forceinline__ void sts32_if(bool on, uint32_t a, uint32_t v) {
    asm volatile(PRED(2) "@p st.shared.u32 [%0], %1;\n}" ::"r"(a), "r"(v), "r"((uint32_t)on) : "memory");
}
__device__ __forceinline__ void sts128_if(bool on, uint32_t a, uint32_t x, uint32_t y, uint32_t z, uint32_t w) {
    asm volatile(PRED(5) "@p st.shared.v4.u32 [%0], {%1,%2,%3,%4};\n}" ::"r"(a), "r"(x), "r"(y), "r"(z), "r"(w), "r"((uint32_t)on) : "memory");
}
__device__ __forceinline__ float fast_rcp(float x) { float r; asm("rcp.approx.ftz.f32 %0, %1;" : "=f"(r) : "f"(x)); return r; }
__device__ __forceinline__ float fast_sqrt(float x) { float r; asm("sqrt.approx.ftz.f32 %0, %1;" : "=f"(r) : "f"(x)); return r; }
__device__ __forceinline__ float fast_ex2(float x) { float r; asm("ex2.approx.ftz.f32 %0, %1;" : "=f"(r) : "f"(x)); return r; }
__device__ __forceinline__ uint32_t pack2(float lo, float hi) {
    uint32_t r;
    asm("cvt.rn.bf16x2.f32 %0, %1, %2;" : "=r"(r) : "f"(hi), "f"(lo));
    return r;
}
__device__ __forceinline__ float bfr(float x) { return __uint_as_float(pack2(0.f, x)); }
__device__ __forceinline__ uint32_t badd2(uint32_t a, uint32_t b) { uint32_t r; asm("add.rn.bf16x2 %0, %1, %2;" : "=r"(r) : "r"(a), "r"(b)); return r; }
__device__ __forceinline__ uint32_t bsub2(uint32_t a, uint32_t b) { uint32_t r; asm("sub.rn.bf16x2 %0, %1, %2;" : "=r"(r) : "r"(a), "r"(b)); return r; }
__device__ __forceinline__ uint32_t bmul2(uint32_t a, uint32_t b) { uint32_t r; asm("mul.rn.bf16x2 %0, %1, %2;" : "=r"(r) : "r"(a), "r"(b)); return r; }
__device__ __forceinline__ float bf_lo(uint32_t w) { return __uint_as_float(w << 16); }
__device__ __forceinline__ float bf_hi(uint32_t w) { return __uint_as_float(w & 0xffff0000u); }
__device__ __forceinline__ float F(uint32_t t) { return __uint_as_float(t); }
__device__ __forceinline__ uint32_t lds16(uint32_t a) { unsigned short h; asm volatile("ld.shared.u16 %0, [%1];" : "=h"(h) : "r"(a) : "memory"); return h; }
__device__ __forceinline__ uint32_t lds32(uint32_t a) { uint32_t v; asm volatile("ld.shared.u32 %0, [%1];" : "=r"(v) : "r"(a) : "memory"); return v; }
__device__ __forceinline__ uint2 lds64(uint32_t a) {
    uint2 v; asm volatile("ld.shared.v2.u32 {%0,%1}, [%2];" : "=r"(v.x), "=r"(v.y) : "r"(a) : "memory"); return v;
}
__device__ __forceinline__ uint4 lds128(uint32_t a) {
    uint4 v; asm volatile("ld.shared.v4.u32 {%0,%1,%2,%3}, [%4];" : "=r"(v.x), "=r"(v.y), "=r"(v.z), "=r"(v.w) : "r"(a) : "memory"); return v;
}
__device__ __forceinline__ float sum8(const uint4& u, const uint4& v) {
    return ((F(u.x) + F(u.y)) + (F(u.z) + F(u.w))) + ((F(v.x) + F(v.y)) + (F(v.z) + F(v.w)));
}
__device__ __forceinline__ void sts16(uint32_t a, uint32_t v) { asm volatile("st.shared.u16 [%0], %1;" ::"r"(a), "h"((unsigned short)v) : "memory"); }
__device__ __forceinline__ void sts32(uint32_t a, uint32_t v) { asm volatile("st.shared.u32 [%0], %1;" ::"r"(a), "r"(v) : "memory"); }
__device__ __forceinline__ void stsf(uint32_t a, float v) { asm volatile("st.shared.f32 [%0], %1;" ::"r"(a), "f"(v) : "memory"); }
__device__ __forceinline__ void stsf2(uint32_t a, float x, float y) { asm volatile("st.shared.v2.f32 [%0], {%1,%2};" ::"r"(a), "f"(x), "f"(y) : "memory"); }
__device__ __forceinline__ void stsf4(uint32_t a, float x, float y, float z, float w) {
    asm volatile("st.shared.v4.f32 [%0], {%1,%2,%3,%4};" ::"r"(a), "f"(x), "f"(y), "f"(z), "f"(w) : "memory");
}
template <int ID, int N> __device__ __forceinline__ void bar_sync() { asm volatile("bar.sync %0, %1;" ::"n"(ID), "n"(N) : "memory"); }
template <int ID, int N> __device__ __forceinline__ void bar_arrive() { asm volatile("bar.arrive %0, %1;" ::"n"(ID), "n"(N) : "memory"); }
__device__ __forceinline__ void fence_async() { asm volatile("fence.proxy.async.shared::cta;" ::: "memory"); }
__device__ __forceinline__ float shx(float v, int m) { return __shfl_xor_sync(0xffffffffu, v, m); }
__device__ __forceinline__ float shi(float v, int l) { return __shfl_sync(0xffffffffu, v, l); }
__device__ __forceinline__ uint32_t shi(uint32_t v, int l) { return __shfl_sync(0xffffffffu, v, l); }
__device__ __forceinline__ uint32_t opaque(uint32_t x) { asm volatile("mov.u32 %0, %0;" : "+r"(x)); return x; }
__device__ __forceinline__ const char* opaque(const char* x) { asm volatile("mov.u64 %0, %0;" : "+l"(x)); return x; }
constexpr float LOG2E = 1.4426950408889634f, SCALE = 0.07216878364870322f;

#define TRACE(idx) do {} while (0)
#define TRACES(slot) do {} while (0)

__device__ __forceinline__ uint32_t probe_near(const Params& p, int w, int lane) {
    const int cta = blockIdx.x;
    const char* pr = p.scr + SCR_O + head_off(cta >> 2) + 2048 + w * 256 + (cta & 3) * 64;
    st_pkt2_if(lane < 4, pr + lane * 16, 0, 0, 0, 0);
    uint32_t best0 = ~0u, best1 = ~0u;
#pragma unroll 1
    for (int i = w & 1; i < 6 + (w & 1); i++) {
        uint32_t c = clk32(), v = 0;
        if (lane == 0) asm volatile("atom.relaxed.gpu.global.add.u32 %0, [%1], 1;" : "=r"(v) : "l"(pr + (i & 1) * HALF) : "memory");
        c += __shfl_sync(0xffffffffu, v, 0) >> 16;
        c = clk32() - c;
        if (i & 1) best1 = min(best1, c); else best0 = min(best0, c);
    }
    return min(best0, 0xffffu) | min(best1, 0xffffu) << 16;
}
__device__ __forceinline__ uint32_t near_half() {
    const uint4 a = lds128(SM_NEAR), b = lds128(SM_NEAR + 16);
    const uint32_t m = __vminu2(__vminu2(__vminu2(a.x, a.y), __vminu2(a.z, a.w)), __vminu2(__vminu2(b.x, b.y), __vminu2(b.z, b.w)));
    return head_near(blockIdx.x >> 2, ((m & 0xffffu) > m >> 16) != (CFG(FLIP) != 0) ? HALF : 0);
}

__device__ __forceinline__ int kv_group(int k, int t) {
    const int cta = blockIdx.x;
    return ((k * NHEAD + (cta >> 2)) * SK + (SK - WIN) + (cta & 3) * 256 + t * 32) / 8;
}
__device__ __forceinline__ uint32_t phase_ns() { return (((blockIdx.x >> 2) * 13) & 31) * CFG(STAG) / 32; }

__device__ __forceinline__ void ln_fast(float s, float q, float& mean, float& rstd) {
    mean = s * (1.f / DM);
    asm("rsqrt.approx.ftz.f32 %0, %1;" : "=f"(rstd) : "f"(fmaxf(fmaf(-mean, mean, fmaf(q, 1.f / DM, 1e-5f)), 1e-5f)));
}
__device__ __forceinline__ void q_role(const Params& p, int lane) {
    const int cta = blockIdx.x;
    mbar_wait(bar_at(B_EP), 0);
    const uint32_t epoch = lds32(SM_EPOCH), near = head_near(cta >> 2, near_half());
    auto sums = [&](float& S0, float& S1) {
        bar_sync<3, 288>();
        const uint32_t ra = SM_PQ + lane * 16;
        S0 = sum8(lds128(ra), lds128(ra + 1024)); S1 = sum8(lds128(ra + 512), lds128(ra + 1536));
    };
    float cs0, cs1;
    {
        uint32_t q0 = 0, q1 = 0, q2 = 0, q3 = 0;
#pragma unroll 1
        for (int r = 0; r < NB; r++) {
            sums(cs0, cs1);
            bar_arrive<7, 288>();
            q0 = q1; q1 = q2; q2 = q3; q3 = pack2(cs0, cs1);
        }
        const uint32_t t0 = shi(q3, 3 * lane - 72), t1 = shi(q3, 3 * lane - 71), t2 = shi(q3, 3 * lane - 70), tag = epoch << 8 | 0x40;
        const char* box = p.scr + SCR_O + head_off(cta >> 2) + 2048 + (lane >> 2) * 256 + (lane & 3) * 16;
        st_pkt2_if(true, box + (cta & 3) * 64, lane < 24 ? q0 : t0, lane < 24 ? q1 : t1, lane < 24 ? q2 : t2, tag);
        const uint32_t qd = SM_Q + (lane < 24 ? lane * 4 : 3 * 384 + (lane - 24) * 12), step = lane < 24 ? 384 : 4;
#pragma unroll 1
        for (int j = 0; j < 4; j++) {
            uint4 v;
            SPIN_DECL;
            do {
                __nanosleep(200);
                v = ld_pkt(box + near + j * 64);
                SPIN_CHECK(j);
            } while (__any_sync(0xffffffffu, v.w != tag));
            sts32(qd + j * 96, v.x); sts32(qd + j * 96 + step, v.y); sts32(qd + j * 96 + 2 * step, v.z);
        }
        mbar_arrive(bar_at(B_QR));
    }
    sums(cs0, cs1);
    bar_arrive<7, 288>();
    const char* const src = p.scr + SCR_Q + head_off(cta >> 2) + lane * 8 + near;
    const char* const dst = src + (cta & 3) * 192;
    const uint32_t qd = SM_Q + NB * 384 + lane * 4;
    st_pkt82_if(lane < 24, dst - near, 0, 0);
#pragma unroll 1
    for (int k = 0; k < NB; k++) {
        float S0, S1, mean, rstd;
        sums(S0, S1);
        ln_fast(shi(S1, 24), shi(S0, 24), mean, rstd);
        const uint32_t qq = pack2(fmaf(-mean, cs0, S0) * rstd, fmaf(-mean, cs1, S1) * rstd), tag = epoch * NB + k;
        st_pkt8_if(lane < 24, dst + ((int)HALF - 2 * (int)near), qq, tag);
        st_pkt8_if(lane < 24, dst, qq, tag);
        TRACES(k * 12 + 5);
        uint2 a, b, c;
        SPIN_DECL;
        do {
            a = ld_pkt8(src); b = ld_pkt8(src + 256); c = ld_pkt8(src + 512);
            SPIN_CHECK(k);
            sts32(qd, a.x); sts32(qd + 128, b.x); sts32(qd + 256, c.x);
        } while (__any_sync(0xffffffffu, a.y != tag || b.y != tag || c.y != tag));
        mbar_arrive(bar_at(B_QR));
    }
}

struct Maps { CUtensorMap k, v, q, o, g, u; };
__device__ __forceinline__ void load_role(const Params& p, const CUtensorMap* tmKV, int lane, uint32_t t0) {
    const int cta = blockIdx.x;
    t0 += phase_ns();
#pragma unroll 1
    for (int i = 1; i < 5; i++) {
        wait_ns(t0 + i * CFG(TICK0));
        if (elect_one()) l2_prefetch(p.wq + (size_t)(128 * i + cta) * 12288, 12288);
    }
    uint32_t plan[2];
#pragma unroll
    for (int i = 0; i < 2; i++) {
        const int j = lane + 32 * i, k = j >> 4, t = j & 15, u = t >> 1, jw = j - CFG(WIN);
        const int sb = k == 0 ? B_WC + (t >= 8) + (t >= 14) : t >= 12 ? B_RK + u - 5 : t >= 4 ? B_RR + t - 4 : t >= 2 ? B_RP : k > 1 ? B_RK + 3 : B_RR + t;
        const uint32_t sw = sb * 8 | (j < 18 ? 0 : (t >= 12 || u == 1 ? k - 1 : k) & 1) << 9;
        plan[i] = sw | (jw < 0 ? sw : (B_F1 + (jw & 15)) * 8 | ((jw >> 4) & 1) << 9) << 10 |
                  (slot_at(slots(k), t < 8 ? pass_nibble(k, u) : u) * 2 + (t & 1)) << 20 | (t < 10 && j >= 8 && j < 56) << 25;
    }
    bar_sync<6, 64>();
    wait_ns(t0 + kb_ns(60));
    if (elect_one()) bulk_load(ST_WD, p.wd + cta * 15360, 15360, bar_at(B_W));
#pragma unroll 1
    for (int i = 0; i < 5; i++) {
        wait_ns(t0 + kb_ns(75) + i * kb_ns(6));
        if (elect_one()) { l2_prefetch(p.wg + (128 * i + cta) * 3072, 3072); l2_prefetch(p.wu + (128 * i + cta) * 3072, 3072); }
    }
#pragma unroll 1
    for (int i = 0; i < 6; i++) {
        wait_ns(t0 + kb_ns(105) + min(i, 4) * kb_ns(10));
        if (elect_one()) l2_prefetch(p.wo + (size_t)((cta >> 2) * DH + 32 * i + 8 * (cta & 3)) * 1280, 10240);
    }
    t0 += batch_ns(0);
    int jp = 0, shift = 0;
    uint32_t earliest = t0;
    auto requested = [&](uint32_t now) {
        shift = max(max(shift - CFG(GAIN), 0), (int)(now - t0) - (jp < 12 ? CFG(LMAX0) : CFG(LMAX)));
        TRACE(128 + jp);
        t0 += tick_ns(++jp);
    };
    const int grp0 = kv_group(0, 0);
    auto group = [&](int j) { return grp0 + (j >> 4) * (NHEAD * SK / 8) + (j & 7) * 4; };
#pragma unroll 1
    for (int j = 0; j < 16 * NB; j++) {
        const uint32_t pl = __shfl_sync(0xffffffffu, j & 32 ? plan[1] : plan[0], j);
        const int jmax = min(j + CFG(PMAX), 16 * NB);
        uint32_t now;
        SPIN_DECL;
        while (true) {
            const bool ok = mbar_test2(SM_BAR + (pl & 511), (pl >> 9) & 1, SM_BAR + ((pl >> 10) & 511), (pl >> 19) & 1);
            now = now_ns();
            const int late = now - t0 - shift;
            if (ok && (jp > j ? (int)(now - earliest) : late) >= 0) break;
            if (late >= (jp > j ? 0 : CFG(PGRACE)) && jp < jmax) {
                if (elect_one())
                    asm volatile("cp.async.bulk.prefetch.tensor.4d.L2.global [%0, {%1, %1, %1, %2}];" ::"l"(tmKV + ((jp >> 3) & 1)), "r"(0), "r"(group(jp)) : "memory");
                requested(now);
            }
            SPIN_CHECK(j);
        }
        if (elect_one()) {
            mbar_expect_tx(bar_at(B_F1 + (j & 15)), TILE);
            tma_tile(SB + ((pl >> 20) & 31) * TILE, tmKV + ((j >> 3) & 1), group(j), bar_at(B_F1 + (j & 15)), pl >> 25 ? POL_NORMAL : POL_FIRST);
        }
        TRACE(256 + j);
        earliest = now + CFG(VSTEP);
        if (jp == j) requested(now);
    }
}

__device__ __forceinline__ void reload_role(const Params& p, const Maps* tm, uint32_t t0) {
    const CUtensorMap* const tmK = &tm->k;
    const CUtensorMap* const tmV = &tm->v;
    const int cta = blockIdx.x;
    t0 += CFG(TICK0) + CFG(WLAG) + phase_ns();
#pragma unroll 1
    for (int i = 0; i < 5; i++) {
        wait_ns(t0 + i * CFG(TICK0));
        if (elect_one()) tma2d(ST_WQ + i * 12288, &tm->q, 48 * cta, 128 * i, bar_at(B_W));
        if (i == 1) bar_sync<5, 480>();
    }
#pragma unroll 1
    for (int i = 0, o = 0; i < 10;) {
        const uint32_t now = now_ns() - t0;
        if (o < 6 && (int)now >= kb_ns(105) + o * kb_ns(10)) {
            if (elect_one()) tma2d(ST_WO + o * 10240, &tm->o, 160 * (cta & 3), (cta >> 2) * DH + 32 * o, bar_at(B_W + 1));
            o++;
        } else if ((int)now >= kb_ns(77) + i * CFG(GSTEP) && (i < 9 || o == 6)) {
            if (elect_one()) tma2d(ST_WG + (i & 1) * 20480 + (i >> 1) * 4096, i & 1 ? &tm->u : &tm->g, (12 * cta) & ~7, 128 * (i >> 1), bar_at(B_W + 2));
            i++;
        }
    }
#pragma unroll 1
    for (int k = 0; k < NB - 1; k++) {
        mbar_wait(bar_at(B_RK), k & 1);
        if (elect_one()) {
            const uint32_t dst = SB + slot_at(slots(k), 0) * PAIR;
            mbar_expect_tx(bar_at(B_FL), PAIR);
            tma_tile(dst, tmV, kv_group(k, 0), bar_at(B_FL), POL_FIRST);
            tma_tile(dst + TILE, tmV, kv_group(k, 1), bar_at(B_FL), POL_FIRST);
        }
        mbar_wait(bar_at(B_RV), k & 1);
        uint32_t due = now_ns() + (k == NB - 2 ? 0 : CFG(RLAG));
        if (elect_one()) mbar_expect_tx(bar_at(B_F3), 4 * PAIR);
#pragma unroll 1
        for (int t = 0; t < 8; t++) {
            wait_ns(due);
            due += k == NB - 2 ? CFG(RSTEP3) : CFG(RSTEP);
            if (elect_one())
                tma_tile(SB + slot_at(slots(k + 1), t >> 1) * PAIR + (t & 1) * TILE, tmK, kv_group(k + 1, t), bar_at(B_F3), POL_FIRST);
        }
        TRACE(121 + k);
    }
}

__device__ __forceinline__ void zero_role(const Params& p, int lane, unsigned ticket, uint32_t t0) {
    const int cta = blockIdx.x;
    const uint32_t epoch = __shfl_sync(0xffffffffu, ticket, 0) / NCTA + 1;
    if (lane == 0) { sts32(SM_EPOCH, epoch); mbar_arrive(bar_at(B_EP)); }
    mbar_wait(bar_at(B_EP), 0);
#pragma unroll 1
    for (int k = 0; k < NB + 2; k++) {
        lane = opaque(lane);
        const int cl = 2 * (cta & 15) + (lane & 1);
        const int col = 80 * (cta >> 4) + (cl & 2 ? 48 : 0) + (cl >> 2) + (cl & 1 ? 8 : 0);
        const char* own = p.scr + (cl >> 2) * 256 + (cl & 3) * 16;
        uint32_t v0 = 0, v1 = 0, v2 = 0;
        if (lane < 4 && k < NB) {
            const unsigned short* xp = p.x + k * DM + col;
            v0 = __ldg(xp) << 16; v1 = __ldg(xp + 16) << 16; v2 = cl & 2 ? 0 : __ldg(xp + 32) << 16;
        }
        uint4 r;
        if (k == 1) mbar_wait(bar_at(B_RK), 0);
        if (k > 1) {
            mbar_wait(bar_at(B_FIN), k & 1);
            r = lds128(SM_FIN + (lane & 1) * 16);
        }
        if (k < NB) {
            const int lg = lane >> 3, ty = (lane & 7) >> 1;
            const char* dst = own + acc_off((k - (lg >> 1)) & 3, lg != 0, cta >> 4) + ty * HALF;
            wait_ns(t0 + batch_ns(k) + CFG(ZTILE) * CFG(TICK0));
            if (lg == 0 || (lg == 1 && (ty < 2 || k == NB - 1)) || (lg == 2 && k > 0 && ty > 1)) {
                st_pkt(dst, v0, v1, v2, 0);
                asm volatile("atom.relaxed.gpu.global.add.f32 %0, [%1+12], %2;" : "=r"(v0) : "l"(dst), "f"(lane < 4 ? 1.f : 0.f) : "memory");
            }
            if (__any_sync(0xffffffffu, v0 != 0)) __trap();
            const char* cnt = p.scr + SCR_COUNT;
            if (lane < 2) asm volatile("red.relaxed.gpu.global.add.u32 [%0], 1;" ::"l"(cnt + lane * HALF) : "memory");
            const uint32_t target = ((epoch - 1) * NB + k + 1) * NCTA;
            cnt += near_half();
            SPIN_DECL;
            uint32_t v;
            do {
                __nanosleep(100);
                asm volatile("ld.relaxed.gpu.global.u32 %0, [%1];" : "=r"(v) : "l"(cnt) : "memory");
                SPIN_CHECK(v);
            } while (__any_sync(0xffffffffu, (int)(v - target) < 0));
        }
        __syncwarp();
        if (lane == 0) mbar_arrive(bar_at(B_Z));
        if (k > 1) {
            const int b = k - 2;
            const char* src = own + acc_off(b, 1, cta >> 4) + (2 + ((lane >> 1) & 1)) * HALF;
            unsigned short* o = p.out + b * DM + col + (lane >> 2) * 16;
            const bool on = !(lane & 2) && lane < (cl & 2 ? 8 : 12);
            wait_clk(clk32() + CFG(DLY_F));
            float cnt;
            SPIN_DECL;
            do {
                const uint4 v = ld_pkt(src);
                SPIN_CHECK(k);
                cnt = F(v.w) + shx(F(v.w), 2);
                const float y0 = F(v.x) + shx(F(v.x), 2), y1 = F(v.y) + shx(F(v.y), 2), y2 = F(v.z) + shx(F(v.z), 2);
                const uint32_t x01 = badd2(r.x, badd2(r.y, bmul2(pack2(y0, y1), r.w)));
                const uint32_t x2 = badd2(r.z, badd2(r.z >> 16, bmul2(pack2(y2, 0.f), r.w)));
                if (cnt == NCTA && on) *o = lane < 4 ? x01 : lane < 8 ? x01 >> 16 : x2;
            } while (__any_sync(0xffffffffu, cnt != NCTA));
            TRACES((2 * b + 1) * 6 + 4);
        }
    }
}

__host__ __device__ constexpr uint32_t desc_lo(uint32_t addr) { return ((addr & 0x3FFFFu) >> 4) | (1u << 16); }
constexpr uint32_t DESC_HI_TILE = (3072u >> 4) | (1u << 30);
constexpr uint32_t DESC_HI_VEC = 1u;
template <int TA, int AOFF, int BOFF>
__device__ __forceinline__ void wgmma_n8(float (&d)[4], uint32_t alo, uint32_t blo, int accumulate) {
    asm volatile("{\n.reg .pred p;\n.reg .b32 a, b;\n.reg .b64 da, db;\nsetp.ne.b32 p, %6, 0;\n"
                 "add.u32 a, %4, %8;\nadd.u32 b, %5, %9;\nmov.b64 da, {a, %10};\nmov.b64 db, {b, %11};\n"
                 "wgmma.mma_async.sync.aligned.m64n8k16.f32.bf16.bf16 {%0,%1,%2,%3}, da, db, p, 1, 1, %7, 0;\n}"
                 : "+f"(d[0]), "+f"(d[1]), "+f"(d[2]), "+f"(d[3])
                 : "r"(alo), "r"(blo), "r"(accumulate), "n"(TA), "n"(AOFF >> 4), "n"(BOFF >> 4), "n"(DESC_HI_TILE), "n"(DESC_HI_VEC));
}
template <int KS, int END>
__device__ __forceinline__ void qk_steps(float (&d)[4], uint32_t alo, uint32_t blo) {
    if constexpr (KS < END) {
        wgmma_n8<0, (KS >> 2) * 1024 + (KS & 3) * 32, KS * 32>(d, alo, blo, KS > 0);
        qk_steps<KS + 1, END>(d, alo, blo);
    }
}
__device__ __forceinline__ void pv_steps(float (&e)[3][4], uint32_t alo, uint32_t blo, int acc) {
    wgmma_n8<1, 0, 0>(e[0], alo, blo, acc); wgmma_n8<1, 1024, 0>(e[1], alo, blo, acc); wgmma_n8<1, 2048, 0>(e[2], alo, blo, acc);
    wgmma_n8<1, 6144, 32>(e[0], alo, blo, 1); wgmma_n8<1, 7168, 32>(e[1], alo, blo, 1); wgmma_n8<1, 8192, 32>(e[2], alo, blo, 1);
}
__device__ __forceinline__ void wg_fence() { asm volatile("wgmma.fence.sync.aligned;" ::: "memory"); }
__device__ __forceinline__ void wg_commit() { asm volatile("wgmma.commit_group.sync.aligned;" ::: "memory"); }
template <int N> __device__ __forceinline__ void wg_wait() { asm volatile("wgmma.wait_group.sync.aligned %0;" ::"n"(N) : "memory"); }
__device__ __forceinline__ void acc_ready(float (&d)[4]) { asm volatile("" : "+f"(d[0]), "+f"(d[1]), "+f"(d[2]), "+f"(d[3]) :: "memory"); }
__device__ __forceinline__ uint32_t score_pair(float (&d)[4]) {
    acc_ready(d);
    const uint32_t r = pack2(d[0], d[2]);
    return pack2(bf_lo(r) * SCALE, bf_hi(r) * SCALE);
}

__device__ __forceinline__ void attention_role(const Params& p, int w, int lane) {
    const int cta = blockIdx.x, t4 = lane & 3, g = lane >> 2;
    mbar_wait(bar_at(B_EP), 0);
    const uint32_t tag0 = lds32(SM_EPOCH) * NB;
    const char* const odst = p.scr + SCR_O + head_off(cta >> 2) + (2 * w + (g >> 2)) * 256 + (cta & 3) * 64 + (g & 3) * 16;
    const uint32_t pdst = SM_P + ((t4 + 3) & 3) * PSTR + (16 * w + g) * 2;
    auto softmax = [&](uint32_t& sc, int ps) -> uint32_t {
        const float s0 = bf_lo(sc), s1 = bf_hi(sc);
        int key = __float_as_int(fmaxf(s0, s1));
        key ^= (key >> 31) & 0x7fffffff;
        key = __reduce_max_sync(0xffffffffu, key);
        sts32(SM_MAX + w * 4, key);
        bar_sync<4, 128>();
        const uint4 mx = lds128(SM_MAX);
        key = max(max((int)mx.x, (int)mx.y), max((int)mx.z, (int)mx.w));
        key ^= (key >> 31) & 0x7fffffff;
        const float mb = __int_as_float(key) * LOG2E;
        const uint32_t pp = pack2(fast_ex2(fmaf(s0, LOG2E, -mb)), fast_ex2(fmaf(s1, LOG2E, -mb)));
        sts16(pdst + ps * 4 * PSTR, pp); sts16(pdst + ps * 4 * PSTR + 16, pp >> 16);
        fence_async();
        bar_sync<4, 128>();
        sc = pp;
        return key;
    };
    auto put_sum = [&](uint32_t pp, int ps) {
        uint32_t fs;
        asm volatile("redux.sync.add.u32 %0, %1, 0xffffffff;" : "=r"(fs) : "r"(__float2uint_rn((bf_lo(pp) + bf_hi(pp)) * 8388608.f)) : "memory");
        sts32(SM_SUM + ps * 16 + w * 4, fs);
    };
    auto aux_word = [&](uint32_t mx, const uint4& u, int k) {
        const float l = __uint2float_rn((u.x + u.y) + (u.z + u.w)) * (1.f / 8388608.f);
        return (g < 4 ? mx : (__float_as_uint(l) + 0x80u) & 0xffffff00u) | ((tag0 + k) & 0x7fu) | 0x80u;
    };
    auto send = [&](float (&e)[3][4], uint32_t aux, int ps) {
        acc_ready(e[0]); acc_ready(e[1]); acc_ready(e[2]);
        const uint32_t o0 = pack2(e[0][0], e[0][2]), o1 = pack2(e[1][0], e[1][2]), o2 = pack2(e[2][0], e[2][2]);
        st_pkt2_if(t4 == 0, odst + ps * 2048, o0, o1, o2, aux);
        mbar_arrive_if(lane == 0, bar_at(ps ? B_RV : B_PS));
    };
    mbar_wait(bar_at(B_QR), 0);
    TRACES(73);
#pragma unroll 1
    for (int it = 0; it <= NB; it++) {
        uint32_t m1 = 0;
        if (it < NB) {
            const uint32_t tab = slots(it);
            const uint32_t ka = SB + (2 * w + ((lane >> 3) & 1)) * 3072 + (lane & 7) * 128 + (((lane >> 4) ^ (lane & 7)) << 4);
            const uint32_t qa = SM_Q + it * 384 + (lane >> 3) * 16;
            uint32_t sc = 0;
#pragma unroll 1
            for (int u = 0; u < 4; u++) {
                const uint32_t base = ka + slot_at(tab, pass_nibble(it, u)) * PAIR;
                mbar_wait(bar_at(B_F1 + 2 * u + (w >> 1)), it & 1);
                float d0[4] = {}, d1[4] = {};
#pragma unroll
                for (int c = 0; c < 6; c++) {
                    uint32_t a0[4], a1[4], b[4];
                    ldsm4(b, qa + c * 64);
                    ldsm4(a0, (base ^ ((c & 1) * 64)) + (c >> 1) * 1024);
                    ldsm4(a1, (base ^ ((c & 1) * 64 + 32)) + (c >> 1) * 1024);
                    mma16816(d0, a0[0], a0[1], a0[2], a0[3], b[0], b[1]);
                    mma16816(d1, a1[0], a1[1], a1[2], a1[3], b[2], b[3]);
                }
                const uint32_t r = pack2(d0[0] + d1[0], d0[2] + d1[2]);
                mbar_arrive_if(lane == 0, bar_at(B_RR + 2 * u + (w >> 1)));
                if (t4 == ((u + 1) & 3)) sc = pack2(bf_lo(r) * SCALE, bf_hi(r) * SCALE);
            }
            m1 = softmax(sc, 0);
            put_sum(sc, 0);
        }
        if (it > 0) {
            const int k = it - 1;
            const uint32_t tab = slots(k);
            const uint32_t v0 = slot_at(tab, k < NB - 1 ? 0 : 4);
            TRACES(48 + k * 6);
            if (k > 0) mbar_wait(bar_at(B_F3), it & 1);
            mbar_wait(bar_at(B_QR), it & 1);
            fence_async();
            TRACES(49 + k * 6);
            float d[4][4] = {};
            const bool busy = k < NB - 1;
#pragma unroll
            for (int u = 0; u < 4; u++) {
                const uint32_t alo = desc_lo(SB) + slot_at(tab, u) * (PAIR >> 4), blo = desc_lo(SM_Q + 4 * 384);
                wg_fence();
                qk_steps<0, 6>(d[u], alo, blo);
                wg_commit();
                if (busy) {
                    wg_wait<1>();
                    if (u > 0) mbar_arrive_if(lane == 0, bar_at(B_RK + u - 1));
                }
                wg_fence();
                qk_steps<6, 12>(d[u], alo, blo);
                wg_commit();
                if (u < 3 && busy) wg_wait<1>();
            }
            wg_wait<2>();
            uint32_t sc = shi(score_pair(d[0]), lane & 28), s = shi(score_pair(d[1]), lane & 28);
            if (t4 == 2) sc = s;
            s = shi(score_pair(d[2]), lane & 28);
            if (t4 == 3) sc = s;
            wg_wait<0>();
            s = score_pair(d[3]);
            if (t4 == 0) sc = s;
            mbar_arrive_if(lane == 0, bar_at(B_RK + 3));
            TRACES(50 + k * 6);
            const uint32_t m2 = softmax(sc, 1);
            TRACES(51 + k * 6);
            float e[3][4] = {};
#pragma unroll
            for (int t = 0; t < 8; t++) {
                const int pr = ((t >> 1) + 1) & 3;
                if (t == 6 && k < NB - 1) mbar_wait(bar_at(B_FL), k & 1);
                wg_fence();
                pv_steps(e, desc_lo(SB + (t & 1) * TILE) + (pr ? slot_at(tab, 4 + pr) : v0) * (PAIR >> 4), desc_lo(SM_P + (4 + pr) * PSTR + (t & 1) * 64), t > 0);
                wg_commit();
                if (t < 7 && busy) wg_wait<1>();
                if (t == 1) put_sum(sc, 1);
            }
            bar_sync<4, 128>();
            const uint32_t aux = opaque(aux_word(m2, lds128(SM_SUM + 16), k));
            wg_wait<0>();
            send(e, aux, 1);
            TRACES(52 + k * 6);
        }
        if (it < NB) {
            const uint32_t tab = slots(it);
            if (it == 0) st_pkt2_if(t4 == 0, odst, 0, 0, 0, 0);
            bar_sync<4, 128>();
            const uint32_t aux = opaque(aux_word(m1, lds128(SM_SUM), it));
            float e[3][4] = {};
#pragma unroll 1
            for (int u = 0; u < 4; u++) {
                const uint32_t alo = desc_lo(SB) + slot_at(tab, 4 + u) * (PAIR >> 4), blo = desc_lo(SM_P) + u * (PSTR >> 4);
                mbar_wait(bar_at(B_F1 + 8 + 2 * u), it & 1);
                wg_fence();
                pv_steps(e, alo, blo, u > 0);
                wg_commit();
                wg_wait<1>();
                if (u == 1) mbar_arrive_if(lane == 0, bar_at(B_RP));
                mbar_wait(bar_at(B_F1 + 9 + 2 * u), it & 1);
                wg_fence();
                pv_steps(e, alo + (TILE >> 4), blo + 4, 1);
                wg_commit();
                wg_wait<1>();
            }
            wg_wait<0>();
            send(e, aux, 0);
            TRACES(53 + it * 6);
        }
    }
}

__device__ __forceinline__ void ln_finish(float s, float q, float& mean_b, float& rden) {
    const float mean = s * (1.f / DM);
    const float var = fmaxf(fmaf(q, 1.f / DM, -mean * mean), 0.f);
    mean_b = bfr(mean);
    rden = fast_rcp(bfr(fast_sqrt(bfr(bfr(var) + 1e-5f))));
}
__device__ __forceinline__ uint32_t ln_apply(uint32_t w, float mean_b, float rden) {
    const uint32_t d = bsub2(w, __byte_perm(__float_as_uint(mean_b), 0, 0x3232));
    return pack2(bf_lo(d) * rden, bf_hi(d) * rden);
}
__device__ __forceinline__ void put_x(uint32_t x01, uint32_t x2, uint32_t wa, bool e2) {
    sts16(wa, x01); sts16(wa + 8, x01 >> 16);
    sts16_if(!e2, wa + 16, x2);
}
__device__ __forceinline__ void get_x(uint32_t (&b)[10], uint32_t ra) {
    __syncwarp();
    const uint4 u = lds128(ra), v = lds128(ra + 16);
    const uint2 z = lds64(ra + 32);
    b[0] = u.x; b[1] = u.y; b[2] = u.z; b[3] = u.w; b[4] = v.x; b[5] = v.y; b[6] = v.z; b[7] = v.w; b[8] = z.x; b[9] = z.y;
}
__device__ __forceinline__ float fold(float a, float b, bool sel, int m) { return (sel ? b : a) + shx(sel ? a : b, m); }

__device__ __forceinline__ void chain_role(const Params& p, int w, int lane, uint32_t t0) {
    const int cta = blockIdx.x, h = cta >> 2, s = cta & 3;
    const int g = lane >> 2, t4 = lane & 3;
    const bool e1 = t4 & 1, e2 = t4 & 2;
    uint32_t wq[5][3][4], wo[3][5][4], wg[5][4], wh[5][2], wd[4][4];
    const int col0 = 80 * w + (e2 ? 48 : 0) + g + (e1 ? 8 : 0);
    const uint32_t xw = opaque(SM_X + w * 384 + 48 * (g >> 1) + (e2 ? 24 : 0) + (e1 ? 4 : 0) + 2 * (g & 1));
    const uint32_t xr = opaque(g == 1 ? SM_ONES : SM_X + w * 384 + (g == 3 ? 192 : 0) + 48 * t4);
    TRACES(75);
    sts32_if(lane < 12, SM_ONES + lane * 4, 0x3f803f80u);
    uint32_t zero = lane >> 5;
    const int mi = lane >> 3, mr = lane & 7;
    mbar_wait(bar_at(B_W), 0);
    TRACES(74);
    sts16(xw + 192, lds16(ST_X + 5120 + col0 * 2)); sts16(xw + 200, lds16(ST_X + 5120 + col0 * 2 + 32));
    sts16_if(!e2, xw + 208, lds16(ST_X + 5120 + col0 * 2 + 64));
#pragma unroll
    for (int i = 0; i < 5; i++)
#pragma unroll
        for (int mt = 0; mt < 3; mt++) ldsm4t(wq[i][mt], ST_WQ + (80 * w + 16 * i + mr + 8 * (mi >> 1)) * 96 + 32 * mt + 16 * (mi & 1), zero);
    const bool odd = cta & 1;
    const uint32_t lo = ST_WD + (mr + (odd ? 4 : 0)) * 1280 + 160 * w + 16 * (mi & 1);
    const uint32_t hi = ST_WD + ((mr & 3) + (odd ? 0 : 8)) * 1280 + 160 * w + 16 * (mi & 1);
    ldsm4t(wd[0], lo + 96 * (mi >> 1), zero);
    ldsm4t(wd[1], lo + 96 * (mi >> 1) + 32, zero);
    ldsm4t(wd[2], (mi < 2 ? lo : hi) + 64, zero);
    ldsm4t(wd[3], hi + 32 * (mi >> 1) + 96 * (mr >> 2), zero);
    fence_async();
    __syncwarp();
    mbar_arrive_if(lane == 0, bar_at(B_WC));
    mbar_wait(bar_at(B_EP), 0);
    const uint32_t near = __shfl_sync(0xffffffffu, near_half(), 0);
    uint32_t x01 = 0, x2 = 0, nx01 = 0, nx2 = 0;
#pragma unroll 1
    for (int n = -5; n < NROUND; n++) {
        const bool last = (ORD_LAST >> (n & 15)) & 1, head = !((ORD_NO_HEAD >> (n & 15)) & 1);
        const int k = (ORD_BATCH >> (2 * (n & 15))) & 3;
        if (n > -5 && n <= 0) bar_sync<7, 288>();
        else if (!last) bar_sync<2, 256>();
        TRACES(n <= 0 ? 83 + n : 95);
        const char* const slice = p.scr + acc_off(k, last, w);
        const char* const cell = opaque(slice + g * 256 + t4 * 16);
        if (n < -1) {
            const uint32_t xa = ST_X + (n + 5) * 1280, ln = opaque(lane);
            const int col0 = 80 * w + (ln & 2 ? 48 : 0) + (ln >> 2) + (ln & 1 ? 8 : 0);
            float sm = 0.f, sq = 0.f;
#pragma unroll
            for (int i = 0; i < 5; i++) {
                const uint2 c = lds64(xa + i * 256 + ln * 8);
                sm += (bf_lo(c.x) + bf_hi(c.x)) + (bf_lo(c.y) + bf_hi(c.y));
                sq = fmaf(bf_lo(c.x), bf_lo(c.x), fmaf(bf_hi(c.x), bf_hi(c.x), fmaf(bf_lo(c.y), bf_lo(c.y), fmaf(bf_hi(c.y), bf_hi(c.y), sq))));
            }
            x01 = lds16(xa + col0 * 2) | lds16(xa + col0 * 2 + 32) << 16;
            x2 = lds16(xa + col0 * 2 + 64);
#pragma unroll
            for (int o = 16; o; o >>= 1) { sm += shx(sm, o); sq += shx(sq, o); }
            float mean_b, rden;
            ln_finish(sm, sq, mean_b, rden);
            x01 = ln_apply(x01, mean_b, rden);
            x2 = ln_apply(x2, mean_b, rden);
            put_x(x01, x2, xw, e2);
        } else {
        if (n >= 0) {
          if (head) {
            if (!last || n == NROUND - 1) mbar_wait(bar_at(B_Z), (k + last) & 1);
            const char* src = p.scr + SCR_O + head_off(h) + head_near(h, near) + last * 2048 + (w & 6) * 256 + (lane & 15) * 16;
            const uint32_t tag = (lds32(SM_EPOCH) * NB + k) | 0x80u;
            mbar_wait(bar_at(last ? B_RV : B_PS), k & 1);
            if (!last && k < NB - 1) wait_ns(t0 + batch_ns(k + 1) + CFG(START));
            uint4 v, z;
            {
                SPIN_DECL;
                do {
                    v = ld_pkt(src); z = ld_pkt(src + 256);
                    SPIN_CHECK(n);
                } while (__any_sync(0xffffffffu, (((v.w ^ tag) | (z.w ^ tag)) & 0xffu) != 0));
            }
            TRACES(tr + 0);
            float a[3][4] = {};
            const uint32_t bb[3][2] = {{v.x, v.y}, {z.x, z.y}, {v.z, z.z}};
            float sa, sb, rl;
#pragma unroll
            for (int i = 0; i < 3; i++) {
                const uint32_t l0 = g < 4 ? bb[i][0] : 0, l1 = g < 4 ? bb[i][1] : 0, h0 = g < 4 ? 0 : bb[i][0], h1 = g < 4 ? 0 : bb[i][1];
#pragma unroll
                for (int mt = 0; mt < 5; mt++)
                    mma16816(a[mt % 3], wo[i][mt][0], wo[i][mt][1], wo[i][mt][2], wo[i][mt][3], mt < 3 ? l0 : h0, mt < 3 ? l1 : h1);
                if (i == 0) {
                    int key = v.w & 0xffffff00u;
                    key ^= (key >> 31) & 0x7fffffff;
                    key = __reduce_max_sync(0xffffffffu, key);
                    key ^= (key >> 31) & 0x7fffffff;
                    const float ws = fast_ex2((F(v.w & 0xffffff00u) - __int_as_float(key)) * LOG2E);
                    sa = shi(ws, e1 ? 8 : 0); sb = shi(ws, e1 ? 12 : 4);
                    rl = ws * F(z.w & 0xffffff00u);
                    rl += shx(rl, 4);
                }
                if (i == 1) rl += shx(rl, 8);
            }
            float y[3];
#pragma unroll
            for (int j = 2; j < 5; j++) {
                const int mt = j % 3;
                y[mt] = fold(fmaf(a[mt][0], sa, a[mt][1] * sb), fmaf(a[mt][2], sa, a[mt][3] * sb), e1, 1);
            }
            const uint32_t pa = SM_PO + w * 512 + lane * 16;
            if (w < 2) {
                const char* dst = opaque(cell + s * 16384);
                rl = fast_rcp(rl);
                bar_sync<1, 256>();
                const uint4 c1 = lds128(pa), c2 = lds128(pa + 1024), c3 = lds128(pa + 2048);
                red_cell2_if(true, dst, ((y[0] + F(c1.x)) + (F(c2.x) + F(c3.x))) * rl, ((y[1] + F(c1.y)) + (F(c2.y) + F(c3.y))) * rl,
                             ((y[2] + F(c1.z)) + (F(c2.z) + F(c3.z))) * rl);
            } else {
                stsf4(pa - 1024, y[0], y[1], y[2], 0.f);
                bar_sync<1, 256>();
            }
            TRACES(tr + 1);
            if ((ORD_NO_TAIL >> n) & 1) continue;
            const uint32_t tsend = clk32();
            if (n == 0) {
                st_pkt2_if(lane < 4, p.scr + SCR_O + head_off(h) + 2048 + w * 256 + s * 64 + lane * 16, 0, 0, 0, 0);
                __syncwarp();
            } else if (!last) {
                const char* nsrc = p.scr + acc_off(k - 1, 1, w) + near + g * 256 + t4 * 16;
                SPIN_DECL;
                do {
                    v = ld_pkt(nsrc);
                    SPIN_CHECK(n);
                    nx01 = pack2(F(v.x), F(v.y)); nx2 = pack2(F(v.z), 0.f);
                } while (__any_sync(0xffffffffu, v.w != FULL_A));
            }
            wait_clk(tsend + (w < 2 ? 0 : 60) + (n < QUIET ? CFG(DLY_AL) : CFG(DLY_A)));
            {
                SPIN_DECL;
                do {
                    v = ld_pkt(cell + near);
                    SPIN_CHECK(n);
                    x01 = pack2(F(v.x), F(v.y));
                    x2 = pack2(F(v.z), 0.f);
                    put_x(x01, x2, xw, e2);
                } while (__any_sync(0xffffffffu, v.w != FULL_A));
            }
            TRACES(tr + 2);
          } else { x01 = nx01; x2 = nx2; put_x(x01, x2, xw, e2); }
        } else {
            mbar_wait(bar_at(B_W + 1), 0);
            const uint32_t ln = opaque(lane);
            const int mi = ln >> 3, mr = ln & 7;
            uint32_t zero = ln >> 5;
            TRACES(76);
#pragma unroll
            for (int i = 0; i < 3; i++) {
                const int d = 16 * (w >> 1) + (mr >> 1) + 8 * (mr & 1) + (i < 2 ? 64 * (mi >> 1) + 4 * i : 128 + 4 * (mi >> 1));
#pragma unroll
                for (int mt = 0; mt < 5; mt++) ldsm4t(wo[i][mt], ST_WO + d * 320 + 160 * (w & 1) + 32 * mt + 16 * (mi & 1), zero);
            }
            fence_async();
            __syncwarp();
            mbar_arrive_if(lane == 0, bar_at(B_WC + 1));
            mbar_wait(bar_at(B_W + 2), 0);
            TRACES(77);
#pragma unroll
            for (int i = 0; i < 5; i++) {
                const uint32_t ga = ST_WG + (mi & 1) * 20480 + (80 * w + 16 * i + mr + 8 * (mi >> 1)) * 32;
                uint32_t r[4];
                ldsm4t(wg[i], ga + (odd ? 16 : 0), zero);
                ldsm4t(r, ga + (odd ? 0 : 16), zero);
#pragma unroll
                for (int kh = 0; kh < 2; kh++) {
                    const uint32_t moved = __shfl_xor_sync(0xffffffffu, odd ? r[2 * kh] : r[2 * kh + 1], 16);
                    wh[i][kh] = (g < 4) == odd ? moved : odd ? r[2 * kh + 1] : r[2 * kh];
                }
            }
            fence_async();
            __syncwarp();
            mbar_arrive_if(lane == 0, bar_at(B_WC + 2));
            TRACES(72);
            x01 = 0x3f803f80u; x2 = 0x3f80u;
            put_x(x01, x2, xw, e2);
        }
        {
            uint32_t b[10];
            get_x(b, xr);
            float a[2][4] = {};
#pragma unroll
            for (int i = 0; i < 5; i++) {
                mma16816(a[0], wg[i][0], wg[i][1], wg[i][2], wg[i][3], b[2 * i], b[2 * i + 1]);
                mma16816(a[1], wh[i][0], b[2 * i], wh[i][1], b[2 * i + 1], b[2 * i], b[2 * i + 1]);
            }
            stsf(SM_PG + (w >> 2) * 512 + (g + 8 * t4) * 16 + (w & 3) * 4, e2 ? (e1 ? a[1][2] : a[1][0]) : (e1 ? a[0][2] : a[0][0]));
            const uint2 cs = lds64(SM_CSG + lane * 48);
            const char* dst = opaque(cell + 3 * HALF - near);
            bar_sync<2, 256>();
            const float S = sum8(lds128(SM_PG + lane * 16), lds128(SM_PG + 512 + lane * 16));
            const float sx = shi(S, 25), sq = shi(S, 24), Su = shi(S, lane + (lane < 16 ? 8 : 4));
            if (n < 0) {
                if (w == 0) stsf2(SM_CSG + lane * 48, S, Su);
            } else {
                float mean_b, rden;
                ln_fast(sx, sq, mean_b, rden);
                const float gv = bfr(fmaf(-mean_b, F(cs.x), S) * rden), uv = bfr(fmaf(-mean_b, F(cs.y), Su) * rden);
                const float sg = fast_rcp(1.f + fast_ex2(-LOG2E * gv));
                const uint32_t hb = pack2(bfr(gv * sg) * uv, 0.f);
                const uint32_t b0 = __byte_perm(shi(hb, 2 * t4), shi(hb, 2 * t4 + 1), 0x5410);
                const uint32_t b1 = __byte_perm(shi(hb, e1 ? 18 : 16), shi(hb, e1 ? 19 : 17), 0x5410);
                const bool up = g >= 4;
                const uint32_t l0 = up ? 0 : b0, h0 = up ? b0 : 0;
                const uint32_t m1 = up == e2 ? b1 : 0;
                float d[3][4] = {};
                mma16816(d[0], wd[0][0], wd[0][1], wd[0][2], wd[0][3], l0, h0);
                mma16816(d[1], wd[1][0], wd[1][1], wd[1][2], wd[1][3], l0, h0);
                mma16816(d[2], wd[2][0], wd[2][1], wd[2][2], wd[2][3], l0, up ? 0 : m1);
                mma1688(d[0], wd[3][0], wd[3][1], m1);
                mma1688(d[1], wd[3][2], wd[3][3], m1);
                red_cell(dst, e1 ? d[0][2] : d[0][0], e1 ? d[1][2] : d[1][0], e1 ? d[2][2] : d[2][0]);
                const uint32_t tsend = clk32();
                TRACES(tr + 3);
                if (last && w != cta >> 4) continue;
                const float sgr = shi(sg, 27);
                const uint32_t sg2 = pack2(sgr, sgr);
                const uint32_t n01 = opaque(pack2((bf_lo(x01) - mean_b) * rden, (bf_hi(x01) - mean_b) * rden));
                const uint32_t n2 = opaque(pack2((bf_lo(x2) - mean_b) * rden, 0.f));
                if (last) {
                    sts128_if(lane >> 1 == (cta & 15), SM_FIN + (lane & 1) * 16, x01, n01, __byte_perm(x2, n2, 0x5410), sg2);
                    mbar_arrive_if(lane >> 1 == (cta & 15), bar_at(B_FIN));
                    __syncwarp();
                    continue;
                }
                wait_clk(tsend + (n < QUIET ? CFG(DLY_BL) : CFG(DLY_B)));
                const uint32_t r01 = x01, r2 = x2;
                float cnt;
                SPIN_DECL;
                do {
                    const uint4 v = ld_pkt(cell + 2 * HALF), z = ld_pkt(cell + 3 * HALF);
                    SPIN_CHECK(n);
                    cnt = F(v.w) + F(z.w);
                    x01 = badd2(r01, badd2(n01, bmul2(pack2(F(v.x) + F(z.x), F(v.y) + F(z.y)), sg2)));
                    x2 = badd2(r2, badd2(n2, bmul2(pack2(F(v.z) + F(z.z), 0.f), sg2)));
                    put_x(x01, x2, xw, e2);
                } while (__any_sync(0xffffffffu, cnt != NCTA));
                TRACES(tr + 4);
            }
        }
        }
        {
            uint32_t b[10];
            get_x(b, xr);
            float a[3][4] = {};
            const float f0 = bf_lo(x01), f1 = bf_hi(x01), f2 = e2 ? 0.f : bf_lo(x2);
            float st;
#pragma unroll
            for (int i = 0; i < 5; i++) {
#pragma unroll
                for (int mt = 0; mt < 3; mt++) {
                    mma16816(a[mt], wq[i][mt][0], wq[i][mt][1], wq[i][mt][2], wq[i][mt][3], b[2 * i], b[2 * i + 1]);
                    if (i == 0 && mt == 0) st = fold(fmaf(f0, f0, fmaf(f1, f1, f2 * f2)), (f0 + f1) + f2, g & 1, 4);
                }
                if (i < 4) st += shx(st, i < 2 ? 1 << i : 2 << i);
            }
            const uint32_t pa = SM_PQ + (w >> 2) * 1024 + (g & 1) * 512 + ((e2 ? 16 : 0) + (e1 ? 4 : 0) + (g >> 1)) * 16 + (w & 3) * 4;
            stsf(pa + 128, e2 ? st : e1 ? a[1][2] : a[1][0]);
            stsf(pa, e2 ? (e1 ? a[2][2] : a[2][0]) : (e1 ? a[0][2] : a[0][0]));
            bar_arrive<3, 288>();
            if (n >= 0 && w == cta >> 4) {
                red_cell2_if(lane >> 1 == (cta & 15), cell + (acc_off(k, 1, 0) - acc_off(k, 0, 0)), f0, f1, f2);
                __syncwarp();
            }
        }
    }
}

template <int ID> __device__ __forceinline__ void role_exit() { asm volatile("exit; // %0" ::"n"(ID)); }
constexpr int NTHREADS = 512;
#define STR2(x) #x
#define STR(x) STR2(x)
__global__ void __launch_bounds__(NTHREADS, 1)
decode_kernel(const Params p, const __grid_constant__ Maps tm) {
    extern __shared__ __align__(1024) unsigned char smem[];
    if (threadIdx.x == 0) l2_prefetch(p.wq + (size_t)blockIdx.x * 12288, 12288);
    const uint32_t t0 = now_ns() - CFG(LEAD);
    const int lane = threadIdx.x & 31;
    const int warp = __reduce_max_sync(0xffffffffu, threadIdx.x >> 5);
    if (warp < 8) {
        asm volatile("setmaxnreg.inc.sync.aligned.u32 " STR(CFG_REG_CHAIN) ";");
        bar_arrive<5, 480 + 0>();
        const uint32_t vote = probe_near(p, warp, lane);
        bar_sync<2, 256 + 32>();
        sts32(SM_NEAR + warp * 4, vote);
        mbar_arrive_if(lane == 0, bar_at(B_EP));
        chain_role(p, warp, __shfl_sync(0xffffffffu, lane, lane), t0);
        role_exit<3>();
    } else if (warp < 12) {
        asm volatile("setmaxnreg.dec.sync.aligned.u32 " STR(CFG_REG_ATT) ";");
        if (elect_one()) {
#pragma unroll 1
            for (int i = warp - 8; i < NBAR; i += 4)
                if (i < B_W || i >= B_WC) mbar_init(bar_at(i), i == B_FIN ? 2 : i == B_EP ? 9 : i == B_QR ? 32 : i == B_PS || i == B_RP ? 4 : i >= B_F3 ? 1 : i >= B_WC ? 8 : i < B_RR || i > B_RV ? 1 : i < B_RK ? 2 : 4);
            asm volatile("fence.mbarrier_init.release.cluster;" ::: "memory");
            fence_async();
        }
        bar_sync<5, 480>();
        attention_role(p, warp - 8, lane);
        role_exit<2>();
    } else {
        asm volatile("setmaxnreg.dec.sync.aligned.u32 " STR(CFG_REG_HELP) ";");
        if (warp == 12) {
            load_role(p, &tm.k, lane, t0);
            role_exit<0>();
        } else {
            if (warp == 14) {
                if (smem_u32(smem) != SB) __trap();
                if (elect_one()) {
                    asm volatile("prefetch.tensormap [%0];" ::"l"(&tm.q) : "memory");
                    mbar_init(bar_at(B_W), 1); mbar_init(bar_at(B_W + 1), 1); mbar_init(bar_at(B_W + 2), 1);
                    asm volatile("fence.mbarrier_init.release.cluster;" ::: "memory");
                    fence_async();
                    mbar_expect_tx(bar_at(B_W), 61440 + 15360 + 6400); mbar_expect_tx(bar_at(B_W + 1), 61440); mbar_expect_tx(bar_at(B_W + 2), 40960);
                    bulk_load(ST_X, p.x, 5120, bar_at(B_W));
                    bulk_load(ST_X + 5120, p.wr, 1280, bar_at(B_W));
                }
                reload_role(p, &tm, t0);
            } else {
                unsigned ticket = 0;
                if (warp == 15 && lane == 0) asm volatile("atom.relaxed.gpu.global.add.u32 %0, [%1], 1;" : "=r"(ticket) : "l"(&g_epoch) : "memory");
                if (warp == 13 && elect_one()) {
                    asm volatile("prefetch.tensormap [%0];" ::"l"(&tm.g) : "memory");
                    asm volatile("prefetch.tensormap [%0];" ::"l"(&tm.u) : "memory");
                    asm volatile("prefetch.tensormap [%0];" ::"l"(&tm.o) : "memory");
                    asm volatile("prefetch.tensormap [%0];" ::"l"(&tm.k) : "memory");
                    asm volatile("prefetch.tensormap [%0];" ::"l"(&tm.v) : "memory");
                }
                bar_sync<5, 480>();
                if (warp == 13) { bar_arrive<6, 64>(); q_role(p, lane); }
                else { bar_arrive<2, 256 + 32>(); zero_role(p, lane, ticket, t0); }
            }
            role_exit<1>();
        }
    }
}

typedef CUresult (*EncodeFn)(CUtensorMap*, CUtensorMapDataType, cuuint32_t, void*, const cuuint64_t*, const cuuint64_t*,
                             const cuuint32_t*, const cuuint32_t*, CUtensorMapInterleave, CUtensorMapSwizzle,
                             CUtensorMapL2promotion, CUtensorMapFloatOOBfill);

bool make_map(EncodeFn fn, CUtensorMap* m, const void* ptr, uint64_t cols, uint64_t rows, uint32_t bc, uint32_t br) {
    cuuint64_t dims[2] = {cols, rows};
    cuuint64_t strides[1] = {cols * 2};
    cuuint32_t box[2] = {bc, br};
    cuuint32_t es[2] = {1, 1};
    return fn(m, CU_TENSOR_MAP_DATA_TYPE_BFLOAT16, 2, const_cast<void*>(ptr), dims, strides, box, es, CU_TENSOR_MAP_INTERLEAVE_NONE,
              CU_TENSOR_MAP_SWIZZLE_NONE, CU_TENSOR_MAP_L2_PROMOTION_L2_128B, CU_TENSOR_MAP_FLOAT_OOB_FILL_NONE) == CUDA_SUCCESS;
}

bool make_kv_map(EncodeFn fn, CUtensorMap* m, const void* ptr) {
    cuuint64_t dims[4] = {64, 8, 3, (cuuint64_t)NB * NHEAD * SK / 8};
    cuuint64_t strides[3] = {DH * 2, 128, 8 * DH * 2};
    cuuint32_t box[4] = {64, 8, 3, 4};
    cuuint32_t es[4] = {1, 1, 1, 1};
    return fn(m, CU_TENSOR_MAP_DATA_TYPE_BFLOAT16, 4, const_cast<void*>(ptr), dims, strides, box, es, CU_TENSOR_MAP_INTERLEAVE_NONE,
              CU_TENSOR_MAP_SWIZZLE_128B, CU_TENSOR_MAP_L2_PROMOTION_L2_128B, CU_TENSOR_MAP_FLOAT_OOB_FILL_NONE) == CUDA_SUCCESS;
}

}

extern "C" void kernel_launch(void* const* d_in, const int* in_sizes, int n_in, void* d_out, int out_size) {
    (void)in_sizes; (void)n_in; (void)out_size;
    static EncodeFn fn = nullptr;
    static const char* scr = nullptr;
    if (!fn) {
        void* f = nullptr;
        cudaDriverEntryPointQueryResult qr;
        if (cudaGetDriverEntryPoint("cuTensorMapEncodeTiled", &f, cudaEnableDefault, &qr) != cudaSuccess || !f) return;
        void* sp = nullptr;
        if (cudaGetSymbolAddress(&sp, g_scratch) != cudaSuccess) return;
        scr = (const char*)(((uintptr_t)sp + (2 << 20) - 1) & ~(uintptr_t)((2 << 20) - 1));
        fn = (EncodeFn)f;
        cudaFuncSetAttribute(decode_kernel, cudaFuncAttributeMaxDynamicSharedMemorySize, SMEM_BYTES);
    }
    Maps tm;
    if (!make_kv_map(fn, &tm.k, d_in[1]) || !make_kv_map(fn, &tm.v, d_in[2])) return;
    if (!make_map(fn, &tm.q, d_in[3], NHEAD * DH, DM, 48, 128) || !make_map(fn, &tm.o, d_in[4], DM, NHEAD * DH, 160, 32)) return;
    if (!make_map(fn, &tm.g, d_in[7], FF, DM, 16, 128) || !make_map(fn, &tm.u, d_in[8], FF, DM, 16, 128)) return;
    Params p;
    p.x = (const unsigned short*)d_in[0];
    p.wq = (const char*)d_in[3];
    p.wo = (const char*)d_in[4];
    p.wr = (const unsigned short*)d_in[6];
    p.wg = (const char*)d_in[7];
    p.wu = (const char*)d_in[8];
    p.wd = (const char*)d_in[9];
    p.out = (unsigned short*)d_out;
    p.scr = scr;
    decode_kernel<<<NCTA, NTHREADS, SMEM_BYTES>>>(p, tm);
}
```

```cpp
#include <cuda_runtime.h>
#include <cuda_bf16.h>
#include <cuda.h>
#include <stdint.h>

namespace {

constexpr int NB = 4, DM = 640, NHEAD = 32, DH = 192, SK = 4096, WIN = 1024, FF = 1536;
constexpr int NCTA = 128;
constexpr int TILE = 12288, PAIR = 2 * TILE;

#define CFG_LIST(X) \
    X(TICK0, 476)        \
    X(TICK, 492)        \
    X(LEAD, 350)        \
    X(STAG, 500)        \
    X(WLAG, 200)        \
    X(GSTEP, 750)        \
    X(WIN, 5)        \
    X(PMAX, 2)        \
    X(PGRACE, 50)        \
    X(LMAX0, 150)        \
    X(LMAX, 200) \
    X(GAIN, 5)        \
    X(VSTEP, 250)        \
    X(RSTEP, 640)        \
    X(RSTEP3, 450) \
    X(ZTILE, 11)        \
    X(START, 1)        \
    X(DLY_A, 410)        \
    X(DLY_AL, 100) \
    X(DLY_B, 570) \
    X(DLY_BL, 950) \
    X(DLY_F, 290) \
    X(FLIP, 0) \

#define X(n, v) constexpr int CFG_##n = v;
CFG_LIST(X)
#undef X
#define CFG(n) CFG_##n
constexpr int QUIET = 8;
#define CFG_REG_CHAIN 216
#define CFG_REG_ATT 48
#define CFG_REG_HELP 32
constexpr int KB_KV0 = 165;
__device__ __forceinline__ int kb_ns(int kb) { return kb * CFG(TICK0) / 12; }
__device__ __forceinline__ int tick_ns(int j) { return j <= 16 ? CFG(TICK0) : CFG(TICK); }
__device__ __forceinline__ int batch_ns(int k) { return kb_ns(KB_KV0) + (k ? 16 * (CFG(TICK0) + (k - 1) * CFG(TICK)) : 0); }

__device__ __forceinline__ uint32_t slots(int k) { return k & 2 ? (k & 1 ? 0x21304768u : 0x76835214u) : (k & 1 ? 0x21480765u : 0x76543210u); }
__device__ __forceinline__ int pass_nibble(int k, int u) { return k > 0 ? 4 + (u & 1) : u; }
__device__ __forceinline__ uint32_t slot_at(uint32_t tab, int u) { return (tab >> (4 * u)) & 15; }

constexpr int NROUND = 11;
constexpr uint32_t ORD_BATCH = 0x3b9910, ORD_LAST = 0x6da, ORD_NO_HEAD = 0x248, ORD_NO_TAIL = 0x092;

constexpr uint32_t SB = 1024;
constexpr uint32_t SM_BAR = SB + 9 * PAIR;
constexpr int B_F1 = 0;
constexpr int B_RR = 24;
constexpr int B_RK = 32;
constexpr int B_RV = 36;
constexpr int B_Z = 37;
constexpr int B_EP = 38;
constexpr int B_W = 39;
constexpr int B_WC = 42;
constexpr int B_FIN = 45;
constexpr int B_F3 = 46;
constexpr int B_PS = 48;
constexpr int B_RP = 49;
constexpr int B_FL = 50;
constexpr int B_QR = 51;
constexpr int NBAR = 52;
__host__ __device__ constexpr uint32_t bar_at(int i) { return SM_BAR + 8 * i; }
constexpr uint32_t SM_EPOCH = SM_BAR + 416;
constexpr uint32_t SM_MAX = SM_EPOCH + 16;
constexpr uint32_t SM_SUM = SM_MAX + 16;
constexpr uint32_t SM_NEAR = SM_SUM + 32;
constexpr uint32_t SM_FIN = SM_NEAR + 32;
constexpr uint32_t SM_Q = SM_FIN + 32;
constexpr uint32_t PSTR = 144;
constexpr uint32_t SM_P = SM_Q + 5 * 384;
constexpr uint32_t SM_X = SM_P + 8 * PSTR;
constexpr uint32_t SM_CSG = SM_X + 40;
constexpr uint32_t SM_ONES = SM_X + 8 * 384;
constexpr uint32_t SM_PG = SM_ONES + 48;
constexpr uint32_t SM_PO = SM_PG + 1024;
constexpr uint32_t SM_PQ = SM_PO;
constexpr int SMEM_BYTES = SM_PO + 3072 - SB;
static_assert(SMEM_BYTES <= 232448 && SM_Q % 16 == 0 && SM_P % 16 == 0 && SM_X % 16 == 0 && SM_PO % 16 == 0, "smem");
constexpr uint32_t ST_WQ = SB, ST_WD = SB + 3 * PAIR, ST_WO = SB + 4 * PAIR, ST_WG = SB + 7 * PAIR, ST_X = ST_WG + 40960;

__device__ unsigned g_epoch;
__device__ unsigned char g_scratch[4 << 20];
constexpr uint32_t HALF = 4096, SCR_O = 1 << 16, SCR_Q = 1 << 17, SCR_COUNT = 3 << 16;
__device__ __forceinline__ uint32_t acc_off(int k, int layer, int w) {
    return (k & 1) << 6 | layer << 7 | (w & 1) << 11 | (w >> 1) << 14 | (k + layer == NB) << 18;
}
__device__ __forceinline__ uint32_t head_off(int h) { return (h & 3) << 14 | (h & 4) << 16 | (h & 8) << 17 | (h & 16) << 9; }
__device__ __forceinline__ uint32_t head_near(int h, uint32_t near) { return near ^ HALF ^ (h & 16) << 8; }
constexpr uint32_t FULL_A = 0x42040000u;

struct Params {
    const char* wq;
    const unsigned short* x;
    const char* wo;
    const unsigned short* wr;
    const char* wg;
    const char* wu;
    const char* wd;
    unsigned short* out;
    const char* scr;
};

__device__ __forceinline__ uint32_t smem_u32(const void* p) { return (uint32_t)__cvta_generic_to_shared(p); }
__device__ __forceinline__ void mbar_init(uint32_t a, uint32_t c) { asm volatile("mbarrier.init.shared::cta.b64 [%0], %1;" ::"r"(a), "r"(c) : "memory"); }
__device__ __forceinline__ void mbar_expect_tx(uint32_t a, uint32_t b) {
    asm volatile("mbarrier.arrive.expect_tx.shared::cta.b64 _, [%0], %1;" ::"r"(a), "r"(b) : "memory");
}
__device__ __forceinline__ void mbar_arrive(uint32_t a) { asm volatile("mbarrier.arrive.shared::cta.b64 _, [%0];" ::"r"(a) : "memory"); }
constexpr uint32_t SPIN_LIMIT = 1u << 22;
#define SPIN_DECL uint32_t spins = 0
#define SPIN_CHECK(info) { if (++spins > SPIN_LIMIT) __trap(); }
__device__ __forceinline__ void jitter() {}
__device__ __forceinline__ void mbar_wait(uint32_t a, uint32_t parity) {
    jitter();
    uint32_t ok;
    SPIN_DECL;
    while (true) {
        asm volatile("{\n.reg .pred p;\nmbarrier.try_wait.parity.shared::cta.b64 p, [%1], %2;\nselp.u32 %0, 1, 0, p;\n}"
                     : "=r"(ok) : "r"(a), "r"(parity) : "memory");
        if (ok) break;
        SPIN_CHECK((a - SM_BAR) / 8 * 10 + parity);
    }
    jitter();
}
__device__ __forceinline__ bool mbar_test2(uint32_t a, uint32_t pa, uint32_t b, uint32_t pb) {
    uint32_t ok;
    asm volatile("{\n.reg .pred p, q;\nmbarrier.test_wait.parity.shared::cta.b64 p, [%1], %2;\n"
                 "mbarrier.test_wait.parity.shared::cta.b64 q, [%3], %4;\nand.pred p, p, q;\nvote.sync.all.pred p, p, 0xffffffff;\nselp.u32 %0, 1, 0, p;\n}"
                 : "=r"(ok) : "r"(a), "r"(pa), "r"(b), "r"(pb) : "memory");
    return ok;
}
__device__ __forceinline__ uint32_t now_ns() { uint32_t t; asm volatile("mov.u32 %0, %%globaltimer_lo;" : "=r"(t) :: "memory"); return t; }
__device__ __forceinline__ uint32_t clk32() { uint32_t c; asm volatile("mov.u32 %0, %%clock;" : "=r"(c) :: "memory"); return c; }
__device__ __forceinline__ void wait_ns(uint32_t t) { jitter(); while ((int)(now_ns() - t) < 0) {} }
__device__ __forceinline__ void wait_clk(uint32_t t) { jitter(); while ((int)(clk32() - t) < 0) {} }
__device__ __forceinline__ bool elect_one() {
    uint32_t e;
    asm volatile("{\n.reg .pred p;\nelect.sync _|p, 0xffffffff;\nselp.u32 %0, 1, 0, p;\n}" : "=r"(e));
    return e;
}
constexpr uint64_t POL_FIRST = 0x12F0000000000000ull, POL_NORMAL = 0x1000000000000000ull;
__device__ __forceinline__ void tma_tile(uint32_t dst, const CUtensorMap* tm, int group, uint32_t bar, uint64_t pol) {
    asm volatile("cp.async.bulk.tensor.4d.shared::cluster.global.mbarrier::complete_tx::bytes.L2::cache_hint"
                 " [%0], [%1, {%3, %3, %3, %4}], [%2], %5;"
                 ::"r"(dst), "l"(tm), "r"(bar), "r"(0), "r"(group), "l"(pol) : "memory");
}
__device__ __forceinline__ void tma2d(uint32_t dst, const CUtensorMap* tm, int x, int y, uint32_t bar) {
    asm volatile("cp.async.bulk.tensor.2d.shared::cluster.global.mbarrier::complete_tx::bytes [%0], [%1, {%3, %4}], [%2];"
                 ::"r"(dst), "l"(tm), "r"(bar), "r"(x), "r"(y) : "memory");
}
__device__ __forceinline__ void bulk_load(uint32_t dst, const void* src, uint32_t bytes, uint32_t bar) {
    asm volatile("cp.async.bulk.shared::cluster.global.mbarrier::complete_tx::bytes [%0], [%1], %2, [%3];"
                 ::"r"(dst), "l"(src), "r"(bytes), "r"(bar) : "memory");
}
__device__ __forceinline__ void l2_prefetch(const void* p, uint32_t bytes) {
    asm volatile("cp.async.bulk.prefetch.L2.global [%0], %1;" ::"l"(p), "r"(bytes) : "memory");
}
__device__ __forceinline__ void mma16816(float (&c)[4], uint32_t a0, uint32_t a1, uint32_t a2, uint32_t a3, uint32_t b0, uint32_t b1) {
    asm volatile("mma.sync.aligned.m16n8k16.row.col.f32.bf16.bf16.f32 {%0,%1,%2,%3}, {%4,%5,%6,%7}, {%8,%9}, {%0,%1,%2,%3};"
                 : "+f"(c[0]), "+f"(c[1]), "+f"(c[2]), "+f"(c[3]) : "r"(a0), "r"(a1), "r"(a2), "r"(a3), "r"(b0), "r"(b1));
}
__device__ __forceinline__ void mma1688(float (&c)[4], uint32_t a0, uint32_t a1, uint32_t b0) {
    asm volatile("mma.sync.aligned.m16n8k8.row.col.f32.bf16.bf16.f32 {%0,%1,%2,%3}, {%4,%5}, {%6}, {%0,%1,%2,%3};"
                 : "+f"(c[0]), "+f"(c[1]), "+f"(c[2]), "+f"(c[3]) : "r"(a0), "r"(a1), "r"(b0));
}
__device__ __forceinline__ void ldsm4(uint32_t (&r)[4], uint32_t a) {
    asm volatile("ldmatrix.sync.aligned.m8n8.x4.shared.b16 {%0,%1,%2,%3}, [%4];"
                 : "=r"(r[0]), "=r"(r[1]), "=r"(r[2]), "=r"(r[3]) : "r"(a) : "memory");
}
__device__ __forceinline__ void ldsm4t(uint32_t (&r)[4], uint32_t a, uint32_t& zero) {
    asm volatile("ldmatrix.sync.aligned.m8n8.x4.trans.shared.b16 {%0,%1,%2,%3}, [%4];"
                 : "=r"(r[0]), "=r"(r[1]), "=r"(r[2]), "=r"(r[3]) : "r"(a + zero) : "memory");
    zero &= r[3];
}
__device__ __forceinline__ uint4 ld_pkt(const void* p) {
    uint4 v;
    asm volatile("{\n.reg .b128 t;\nld.relaxed.gpu.global.b128 t, [%4];\nmov.b128 {%0,%1,%2,%3}, t;\n}"
                 : "=r"(v.x), "=r"(v.y), "=r"(v.z), "=r"(v.w) : "l"(p) : "memory");
    return v;
}
__device__ __forceinline__ void st_pkt(const void* p, uint32_t a, uint32_t b, uint32_t c, uint32_t d) {
    asm volatile("{\n.reg .b128 t;\nmov.b128 t, {%1,%2,%3,%4};\nst.relaxed.gpu.global.b128 [%0], t;\n}"
                 ::"l"(p), "r"(a), "r"(b), "r"(c), "r"(d) : "memory");
}
__device__ __forceinline__ uint2 ld_pkt8(const void* p) {
    uint2 v;
    asm volatile("{\n.reg .b64 t;\nld.relaxed.gpu.global.b64 t, [%2];\nmov.b64 {%0,%1}, t;\n}" : "=r"(v.x), "=r"(v.y) : "l"(p) : "memory");
    return v;
}
__device__ __forceinline__ void red_cell(const char* p, float a, float b, float c) {
    jitter();
    asm volatile("red.relaxed.gpu.global.add.v4.f32 [%0], {%1,%2,%3,%4};" ::"l"(p), "f"(a), "f"(b), "f"(c), "f"(1.0f) : "memory");
}
#define PRED(n) "{\n.reg .pred p;\nsetp.ne.u32 p, %" #n ", 0;\n"
__device__ __forceinline__ void red_cell2_if(bool on, const char* p, float a, float b, float c) {
    jitter();
    asm volatile(PRED(5) "@p red.relaxed.gpu.global.add.v4.f32 [%0], {%1,%2,%3,%4};\n@p red.relaxed.gpu.global.add.v4.f32 [%0+4096], {%1,%2,%3,%4};\n}"
                 ::"l"(p), "f"(a), "f"(b), "f"(c), "f"(1.0f), "r"((uint32_t)on) : "memory");
}
__device__ __forceinline__ void st_pkt8_if(bool on, const void* p, uint32_t a, uint32_t b) {
    jitter();
    asm volatile(PRED(3) ".reg .b64 t;\nmov.b64 t, {%1,%2};\n@p st.relaxed.gpu.global.b64 [%0], t;\n}" ::"l"(p), "r"(a), "r"(b), "r"((uint32_t)on) : "memory");
}
__device__ __forceinline__ void st_pkt82_if(bool on, const void* p, uint32_t a, uint32_t b) {
    asm volatile(PRED(3) ".reg .b64 t;\nmov.b64 t, {%1,%2};\n@p st.relaxed.gpu.global.b64 [%0], t;\n@p st.relaxed.gpu.global.b64 [%0+4096], t;\n}"
                 ::"l"(p), "r"(a), "r"(b), "r"((uint32_t)on) : "memory");
}
__device__ __forceinline__ void st_pkt2_if(bool on, const void* p, uint32_t a, uint32_t b, uint32_t c, uint32_t d) {
    jitter();
    asm volatile(PRED(5) ".reg .b128 t;\nmov.b128 t, {%1,%2,%3,%4};\n@p st.relaxed.gpu.global.b128 [%0], t;\n@p st.relaxed.gpu.global.b128 [%0+4096], t;\n}"
                 ::"l"(p), "r"(a), "r"(b), "r"(c), "r"(d), "r"((uint32_t)on) : "memory");
}
__device__ __forceinline__ void mbar_arrive_if(bool on, uint32_t a) {
    jitter();
    asm volatile(PRED(1) "@p mbarrier.arrive.shared::cta.b64 _, [%0];\n}" ::"r"(a), "r"((uint32_t)on) : "memory");
}
__device__ __forceinline__ void sts16_if(bool on, uint32_t a, uint32_t v) {
    asm volatile(PRED(2) "@p st.shared.u16 [%0], %1;\n}" ::"r"(a), "h"((unsigned short)v), "r"((uint32_t)on) : "memory");
}
__device__ __forceinline__ void sts32_if(bool on, uint32_t a, uint32_t v) {
    asm volatile(PRED(2) "@p st.shared.u32 [%0], %1;\n}" ::"r"(a), "r"(v), "r"((uint32_t)on) : "memory");
}
__device__ __forceinline__ void sts128_if(bool on, uint32_t a, uint32_t x, uint32_t y, uint32_t z, uint32_t w) {
    jitter();
    asm volatile(PRED(5) "@p st.shared.v4.u32 [%0], {%1,%2,%3,%4};\n}" ::"r"(a), "r"(x), "r"(y), "r"(z), "r"(w), "r"((uint32_t)on) : "memory");
}
__device__ __forceinline__ float fast_rcp(float x) { float r; asm("rcp.approx.ftz.f32 %0, %1;" : "=f"(r) : "f"(x)); return r; }
__device__ __forceinline__ float fast_sqrt(float x) { float r; asm("sqrt.approx.ftz.f32 %0, %1;" : "=f"(r) : "f"(x)); return r; }
__device__ __forceinline__ float fast_ex2(float x) { float r; asm("ex2.approx.ftz.f32 %0, %1;" : "=f"(r) : "f"(x)); return r; }
__device__ __forceinline__ uint32_t pack2(float lo, float hi) {
    uint32_t r;
    asm("cvt.rn.bf16x2.f32 %0, %1, %2;" : "=r"(r) : "f"(hi), "f"(lo));
    return r;
}
__device__ __forceinline__ float bfr(float x) { return __uint_as_float(pack2(0.f, x)); }
__device__ __forceinline__ uint32_t badd2(uint32_t a, uint32_t b) { uint32_t r; asm("add.rn.bf16x2 %0, %1, %2;" : "=r"(r) : "r"(a), "r"(b)); return r; }
__device__ __forceinline__ uint32_t bsub2(uint32_t a, uint32_t b) { uint32_t r; asm("sub.rn.bf16x2 %0, %1, %2;" : "=r"(r) : "r"(a), "r"(b)); return r; }
__device__ __forceinline__ uint32_t bmul2(uint32_t a, uint32_t b) { uint32_t r; asm("mul.rn.bf16x2 %0, %1, %2;" : "=r"(r) : "r"(a), "r"(b)); return r; }
__device__ __forceinline__ float bf_lo(uint32_t w) { return __uint_as_float(w << 16); }
__device__ __forceinline__ float bf_hi(uint32_t w) { return __uint_as_float(w & 0xffff0000u); }
__device__ __forceinline__ float F(uint32_t t) { return __uint_as_float(t); }
__device__ __forceinline__ uint32_t lds16(uint32_t a) { unsigned short h; asm volatile("ld.shared.u16 %0, [%1];" : "=h"(h) : "r"(a) : "memory"); return h; }
__device__ __forceinline__ uint32_t lds32(uint32_t a) { uint32_t v; asm volatile("ld.shared.u32 %0, [%1];" : "=r"(v) : "r"(a) : "memory"); return v; }
__device__ __forceinline__ uint2 lds64(uint32_t a) {
    uint2 v; asm volatile("ld.shared.v2.u32 {%0,%1}, [%2];" : "=r"(v.x), "=r"(v.y) : "r"(a) : "memory"); return v;
}
__device__ __forceinline__ uint4 lds128(uint32_t a) {
    uint4 v; asm volatile("ld.shared.v4.u32 {%0,%1,%2,%3}, [%4];" : "=r"(v.x), "=r"(v.y), "=r"(v.z), "=r"(v.w) : "r"(a) : "memory"); return v;
}
__device__ __forceinline__ float sum8(const uint4& u, const uint4& v) {
    return ((F(u.x) + F(u.y)) + (F(u.z) + F(u.w))) + ((F(v.x) + F(v.y)) + (F(v.z) + F(v.w)));
}
__device__ __forceinline__ void sts16(uint32_t a, uint32_t v) { asm volatile("st.shared.u16 [%0], %1;" ::"r"(a), "h"((unsigned short)v) : "memory"); }
__device__ __forceinline__ void sts32(uint32_t a, uint32_t v) { asm volatile("st.shared.u32 [%0], %1;" ::"r"(a), "r"(v) : "memory"); }
__device__ __forceinline__ void stsf(uint32_t a, float v) { asm volatile("st.shared.f32 [%0], %1;" ::"r"(a), "f"(v) : "memory"); }
__device__ __forceinline__ void stsf2(uint32_t a, float x, float y) { asm volatile("st.shared.v2.f32 [%0], {%1,%2};" ::"r"(a), "f"(x), "f"(y) : "memory"); }
__device__ __forceinline__ void stsf4(uint32_t a, float x, float y, float z, float w) {
    asm volatile("st.shared.v4.f32 [%0], {%1,%2,%3,%4};" ::"r"(a), "f"(x), "f"(y), "f"(z), "f"(w) : "memory");
}
template <int ID, int N> __device__ __forceinline__ void bar_sync() { jitter(); asm volatile("bar.sync %0, %1;" ::"n"(ID), "n"(N) : "memory"); jitter(); }
template <int ID, int N> __device__ __forceinline__ void bar_arrive() { jitter(); asm volatile("bar.arrive %0, %1;" ::"n"(ID), "n"(N) : "memory"); jitter(); }
__device__ __forceinline__ void fence_async() { asm volatile("fence.proxy.async.shared::cta;" ::: "memory"); }
__device__ __forceinline__ float shx(float v, int m) { return __shfl_xor_sync(0xffffffffu, v, m); }
__device__ __forceinline__ float shi(float v, int l) { return __shfl_sync(0xffffffffu, v, l); }
__device__ __forceinline__ uint32_t shi(uint32_t v, int l) { return __shfl_sync(0xffffffffu, v, l); }
__device__ __forceinline__ uint32_t opaque(uint32_t x) { asm volatile("mov.u32 %0, %0;" : "+r"(x)); return x; }
__device__ __forceinline__ const char* opaque(const char* x) { asm volatile("mov.u64 %0, %0;" : "+l"(x)); return x; }
constexpr float LOG2E = 1.4426950408889634f, SCALE = 0.07216878364870322f;

#define TRACE(idx) do {} while (0)
#define TRACES(slot) do {} while (0)

__device__ __forceinline__ uint32_t probe_near(const Params& p, int w, int lane) {
    const int cta = blockIdx.x;
    const char* pr = p.scr + SCR_O + head_off(cta >> 2) + 2048 + w * 256 + (cta & 3) * 64;
    st_pkt2_if(lane < 4, pr + lane * 16, 0, 0, 0, 0);
    uint32_t best0 = ~0u, best1 = ~0u;
#pragma unroll 1
    for (int i = w & 1; i < 6 + (w & 1); i++) {
        uint32_t c = clk32(), v = 0;
        if (lane == 0) asm volatile("atom.relaxed.gpu.global.add.u32 %0, [%1], 1;" : "=r"(v) : "l"(pr + (i & 1) * HALF) : "memory");
        c += __shfl_sync(0xffffffffu, v, 0) >> 16;
        c = clk32() - c;
        if (i & 1) best1 = min(best1, c); else best0 = min(best0, c);
    }
    return min(best0, 0xffffu) | min(best1, 0xffffu) << 16;
}
__device__ __forceinline__ uint32_t near_half() {
    const uint4 a = lds128(SM_NEAR), b = lds128(SM_NEAR + 16);
    const uint32_t m = __vminu2(__vminu2(__vminu2(a.x, a.y), __vminu2(a.z, a.w)), __vminu2(__vminu2(b.x, b.y), __vminu2(b.z, b.w)));
    return head_near(blockIdx.x >> 2, ((m & 0xffffu) > m >> 16) != (CFG(FLIP) != 0) ? HALF : 0);
}

__device__ __forceinline__ int kv_group(int k, int t) {
    const int cta = blockIdx.x;
    return ((k * NHEAD + (cta >> 2)) * SK + (SK - WIN) + (cta & 3) * 256 + t * 32) / 8;
}
__device__ __forceinline__ uint32_t phase_ns() { return (((blockIdx.x >> 2) * 13) & 31) * CFG(STAG) / 32; }

__device__ __forceinline__ void ln_fast(float s, float q, float& mean, float& rstd) {
    mean = s * (1.f / DM);
    asm("rsqrt.approx.ftz.f32 %0, %1;" : "=f"(rstd) : "f"(fmaxf(fmaf(-mean, mean, fmaf(q, 1.f / DM, 1e-5f)), 1e-5f)));
}
__device__ __forceinline__ void q_role(const Params& p, int lane) {
    const int cta = blockIdx.x;
    mbar_wait(bar_at(B_EP), 0);
    const uint32_t epoch = lds32(SM_EPOCH), near = head_near(cta >> 2, near_half());
    auto sums = [&](float& S0, float& S1) {
        bar_sync<3, 288>();
        const uint32_t ra = SM_PQ + lane * 16;
        S0 = sum8(lds128(ra), lds128(ra + 1024)); S1 = sum8(lds128(ra + 512), lds128(ra + 1536));
    };
    float cs0, cs1;
    {
        uint32_t q0 = 0, q1 = 0, q2 = 0, q3 = 0;
#pragma unroll 1
        for (int r = 0; r < NB; r++) {
            sums(cs0, cs1);
            bar_arrive<7, 288>();
            q0 = q1; q1 = q2; q2 = q3; q3 = pack2(cs0, cs1);
        }
        const uint32_t t0 = shi(q3, 3 * lane - 72), t1 = shi(q3, 3 * lane - 71), t2 = shi(q3, 3 * lane - 70), tag = epoch << 8 | 0x40;
        const char* box = p.scr + SCR_O + head_off(cta >> 2) + 2048 + (lane >> 2) * 256 + (lane & 3) * 16;
        st_pkt2_if(true, box + (cta & 3) * 64, lane < 24 ? q0 : t0, lane < 24 ? q1 : t1, lane < 24 ? q2 : t2, tag);
        const uint32_t qd = SM_Q + (lane < 24 ? lane * 4 : 3 * 384 + (lane - 24) * 12), step = lane < 24 ? 384 : 4;
#pragma unroll 1
        for (int j = 0; j < 4; j++) {
            uint4 v;
            SPIN_DECL;
            do {
                __nanosleep(200);
                v = ld_pkt(box + near + j * 64);
                SPIN_CHECK(j);
            } while (__any_sync(0xffffffffu, v.w != tag));
            sts32(qd + j * 96, v.x); sts32(qd + j * 96 + step, v.y); sts32(qd + j * 96 + 2 * step, v.z);
        }
        mbar_arrive(bar_at(B_QR));
    }
    sums(cs0, cs1);
    bar_arrive<7, 288>();
    const char* const src = p.scr + SCR_Q + head_off(cta >> 2) + lane * 8 + near;
    const char* const dst = src + (cta & 3) * 192;
    const uint32_t qd = SM_Q + NB * 384 + lane * 4;
    st_pkt82_if(lane < 24, dst - near, 0, 0);
#pragma unroll 1
    for (int k = 0; k < NB; k++) {
        float S0, S1, mean, rstd;
        sums(S0, S1);
        ln_fast(shi(S1, 24), shi(S0, 24), mean, rstd);
        const uint32_t qq = pack2(fmaf(-mean, cs0, S0) * rstd, fmaf(-mean, cs1, S1) * rstd), tag = epoch * NB + k;
        st_pkt8_if(lane < 24, dst + ((int)HALF - 2 * (int)near), qq, tag);
        st_pkt8_if(lane < 24, dst, qq, tag);
        TRACES(k * 12 + 5);
        uint2 a, b, c;
        SPIN_DECL;
        do {
            a = ld_pkt8(src); b = ld_pkt8(src + 256); c = ld_pkt8(src + 512);
            SPIN_CHECK(k);
            sts32(qd, a.x); sts32(qd + 128, b.x); sts32(qd + 256, c.x);
        } while (__any_sync(0xffffffffu, a.y != tag || b.y != tag || c.y != tag));
        mbar_arrive(bar_at(B_QR));
    }
}

struct Maps { CUtensorMap k, v, q, o, g, u; };
__device__ __forceinline__ void load_role(const Params& p, const CUtensorMap* tmKV, int lane, uint32_t t0) {
    const int cta = blockIdx.x;
    t0 += phase_ns();
#pragma unroll 1
    for (int i = 1; i < 5; i++) {
        wait_ns(t0 + i * CFG(TICK0));
        if (elect_one()) l2_prefetch(p.wq + (size_t)(128 * i + cta) * 12288, 12288);
    }
    uint32_t plan[2];
#pragma unroll
    for (int i = 0; i < 2; i++) {
        const int j = lane + 32 * i, k = j >> 4, t = j & 15, u = t >> 1, jw = j - CFG(WIN);
        const int sb = k == 0 ? B_WC + (t >= 8) + (t >= 14) : t >= 12 ? B_RK + u - 5 : t >= 4 ? B_RR + t - 4 : t >= 2 ? B_RP : k > 1 ? B_RK + 3 : B_RR + t;
        const uint32_t sw = sb * 8 | (j < 18 ? 0 : (t >= 12 || u == 1 ? k - 1 : k) & 1) << 9;
        plan[i] = sw | (jw < 0 ? sw : (B_F1 + (jw & 15)) * 8 | ((jw >> 4) & 1) << 9) << 10 |
                  (slot_at(slots(k), t < 8 ? pass_nibble(k, u) : u) * 2 + (t & 1)) << 20 | (t < 10 && j >= 8 && j < 56) << 25;
    }
    bar_sync<6, 64>();
    wait_ns(t0 + kb_ns(60));
    if (elect_one()) bulk_load(ST_WD, p.wd + cta * 15360, 15360, bar_at(B_W));
#pragma unroll 1
    for (int i = 0; i < 5; i++) {
        wait_ns(t0 + kb_ns(75) + i * kb_ns(6));
        if (elect_one()) { l2_prefetch(p.wg + (128 * i + cta) * 3072, 3072); l2_prefetch(p.wu + (128 * i + cta) * 3072, 3072); }
    }
#pragma unroll 1
    for (int i = 0; i < 6; i++) {
        wait_ns(t0 + kb_ns(105) + min(i, 4) * kb_ns(10));
        if (elect_one()) l2_prefetch(p.wo + (size_t)((cta >> 2) * DH + 32 * i + 8 * (cta & 3)) * 1280, 10240);
    }
    t0 += batch_ns(0);
    int jp = 0, shift = 0;
    uint32_t earliest = t0;
    auto requested = [&](uint32_t now) {
        shift = max(max(shift - CFG(GAIN), 0), (int)(now - t0) - (jp < 12 ? CFG(LMAX0) : CFG(LMAX)));
        TRACE(128 + jp);
        t0 += tick_ns(++jp);
    };
    const int grp0 = kv_group(0, 0);
    auto group = [&](int j) { return grp0 + (j >> 4) * (NHEAD * SK / 8) + (j & 7) * 4; };
#pragma unroll 1
    for (int j = 0; j < 16 * NB; j++) {
        const uint32_t pl = __shfl_sync(0xffffffffu, j & 32 ? plan[1] : plan[0], j);
        const int jmax = min(j + CFG(PMAX), 16 * NB);
        jitter();
        uint32_t now;
        SPIN_DECL;
        while (true) {
            const bool ok = mbar_test2(SM_BAR + (pl & 511), (pl >> 9) & 1, SM_BAR + ((pl >> 10) & 511), (pl >> 19) & 1);
            now = now_ns();
            const int late = now - t0 - shift;
            if (ok && (jp > j ? (int)(now - earliest) : late) >= 0) break;
            if (late >= (jp > j ? 0 : CFG(PGRACE)) && jp < jmax) {
                if (elect_one())
                    asm volatile("cp.async.bulk.prefetch.tensor.4d.L2.global [%0, {%1, %1, %1, %2}];" ::"l"(tmKV + ((jp >> 3) & 1)), "r"(0), "r"(group(jp)) : "memory");
                requested(now);
            }
            SPIN_CHECK(j);
        }
        if (elect_one()) {
            mbar_expect_tx(bar_at(B_F1 + (j & 15)), TILE);
            tma_tile(SB + ((pl >> 20) & 31) * TILE, tmKV + ((j >> 3) & 1), group(j), bar_at(B_F1 + (j & 15)), pl >> 25 ? POL_NORMAL : POL_FIRST);
        }
        TRACE(256 + j);
        if ((j & 15) == 15) TRACES(88 + (j >> 4));
        earliest = now + CFG(VSTEP);
        if (jp == j) requested(now);
    }
}

__device__ __forceinline__ void reload_role(const Params& p, const Maps* tm, uint32_t t0) {
    const CUtensorMap* const tmK = &tm->k;
    const CUtensorMap* const tmV = &tm->v;
    const int cta = blockIdx.x;
    t0 += CFG(TICK0) + CFG(WLAG) + phase_ns();
#pragma unroll 1
    for (int i = 0; i < 5; i++) {
        wait_ns(t0 + i * CFG(TICK0));
        if (elect_one()) tma2d(ST_WQ + i * 12288, &tm->q, 48 * cta, 128 * i, bar_at(B_W));
        if (i == 1) bar_sync<5, 480>();
    }
#pragma unroll 1
    for (int i = 0, o = 0; i < 10;) {
        const uint32_t now = now_ns() - t0;
        if (o < 6 && (int)now >= kb_ns(105) + o * kb_ns(10)) {
            if (elect_one()) tma2d(ST_WO + o * 10240, &tm->o, 160 * (cta & 3), (cta >> 2) * DH + 32 * o, bar_at(B_W + 1));
            o++;
        } else if ((int)now >= kb_ns(77) + i * CFG(GSTEP) && (i < 9 || o == 6)) {
            if (elect_one()) tma2d(ST_WG + (i & 1) * 20480 + (i >> 1) * 4096, i & 1 ? &tm->u : &tm->g, (12 * cta) & ~7, 128 * (i >> 1), bar_at(B_W + 2));
            i++;
        }
    }
#pragma unroll 1
    for (int k = 0; k < NB - 1; k++) {
        mbar_wait(bar_at(B_RK), k & 1);
        if (elect_one()) {
            const uint32_t dst = SB + slot_at(slots(k), 0) * PAIR;
            mbar_expect_tx(bar_at(B_FL), PAIR);
            tma_tile(dst, tmV, kv_group(k, 0), bar_at(B_FL), POL_FIRST);
            tma_tile(dst + TILE, tmV, kv_group(k, 1), bar_at(B_FL), POL_FIRST);
        }
        mbar_wait(bar_at(B_RV), k & 1);
        uint32_t due = now_ns();
        if (elect_one()) mbar_expect_tx(bar_at(B_F3), 4 * PAIR);
#pragma unroll 1
        for (int t = 0; t < 8; t++) {
            wait_ns(due);
            due += k == NB - 2 ? CFG(RSTEP3) : CFG(RSTEP);
            if (elect_one())
                tma_tile(SB + slot_at(slots(k + 1), t >> 1) * PAIR + (t & 1) * TILE, tmK, kv_group(k + 1, t), bar_at(B_F3), POL_FIRST);
        }
        TRACE(121 + k);
    }
}

__device__ __forceinline__ void zero_role(const Params& p, int lane, unsigned ticket, uint32_t t0) {
    const int cta = blockIdx.x;
    const uint32_t epoch = __shfl_sync(0xffffffffu, ticket, 0) / NCTA + 1;
    if (lane == 0) { sts32(SM_EPOCH, epoch); mbar_arrive(bar_at(B_EP)); }
    mbar_wait(bar_at(B_EP), 0);
#pragma unroll 1
    for (int k = 0; k < NB + 2; k++) {
        lane = opaque(lane);
        const int cl = 2 * (cta & 15) + (lane & 1);
        const int col = 80 * (cta >> 4) + (cl & 2 ? 48 : 0) + (cl >> 2) + (cl & 1 ? 8 : 0);
        const char* own = p.scr + (cl >> 2) * 256 + (cl & 3) * 16;
        uint32_t v0 = 0, v1 = 0, v2 = 0;
        if (lane < 4 && k < NB) {
            const unsigned short* xp = p.x + k * DM + col;
            v0 = __ldg(xp) << 16; v1 = __ldg(xp + 16) << 16; v2 = cl & 2 ? 0 : __ldg(xp + 32) << 16;
        }
        uint4 r;
        if (k == 1) mbar_wait(bar_at(B_RK), 0);
        if (k > 1) {
            mbar_wait(bar_at(B_FIN), k & 1);
            r = lds128(SM_FIN + (lane & 1) * 16);
        }
        if (k < NB) {
            const int lg = lane >> 3, ty = (lane & 7) >> 1;
            const char* dst = own + acc_off((k - (lg >> 1)) & 3, lg != 0, cta >> 4) + ty * HALF;
            wait_ns(t0 + batch_ns(k) + CFG(ZTILE) * CFG(TICK0));
            if (lg == 0 || (lg == 1 && (ty < 2 || k == NB - 1)) || (lg == 2 && k > 0 && ty > 1)) {
                st_pkt(dst, v0, v1, v2, 0);
                asm volatile("atom.relaxed.gpu.global.add.f32 %0, [%1+12], %2;" : "=r"(v0) : "l"(dst), "f"(lane < 4 ? 1.f : 0.f) : "memory");
            }
            if (__any_sync(0xffffffffu, v0 != 0)) __trap();
            const char* cnt = p.scr + SCR_COUNT;
            if (lane < 2) asm volatile("red.relaxed.gpu.global.add.u32 [%0], 1;" ::"l"(cnt + lane * HALF) : "memory");
            const uint32_t target = ((epoch - 1) * NB + k + 1) * NCTA;
            cnt += near_half();
            SPIN_DECL;
            uint32_t v;
            do {
                __nanosleep(100);
                asm volatile("ld.relaxed.gpu.global.u32 %0, [%1];" : "=r"(v) : "l"(cnt) : "memory");
                SPIN_CHECK(v);
            } while (__any_sync(0xffffffffu, (int)(v - target) < 0));
        }
        __syncwarp();
        if (lane == 0) mbar_arrive(bar_at(B_Z));
        if (k > 1) {
            const int b = k - 2;
            const char* src = own + acc_off(b, 1, cta >> 4) + (2 + ((lane >> 1) & 1)) * HALF;
            unsigned short* o = p.out + b * DM + col + (lane >> 2) * 16;
            const bool on = !(lane & 2) && lane < (cl & 2 ? 8 : 12);
            wait_clk(clk32() + CFG(DLY_F));
            float cnt;
            SPIN_DECL;
            do {
                const uint4 v = ld_pkt(src);
                SPIN_CHECK(k);
                cnt = F(v.w) + shx(F(v.w), 2);
                const float y0 = F(v.x) + shx(F(v.x), 2), y1 = F(v.y) + shx(F(v.y), 2), y2 = F(v.z) + shx(F(v.z), 2);
                const uint32_t x01 = badd2(r.x, badd2(r.y, bmul2(pack2(y0, y1), r.w)));
                const uint32_t x2 = badd2(r.z, badd2(r.z >> 16, bmul2(pack2(y2, 0.f), r.w)));
                if (cnt == NCTA && on) *o = lane < 4 ? x01 : lane < 8 ? x01 >> 16 : x2;
            } while (__any_sync(0xffffffffu, cnt != NCTA));
            TRACES((2 * b + 1) * 6 + 4);
        }
    }
}

__host__ __device__ constexpr uint32_t desc_lo(uint32_t addr) { return ((addr & 0x3FFFFu) >> 4) | (1u << 16); }
constexpr uint32_t DESC_HI_TILE = (3072u >> 4) | (1u << 30);
constexpr uint32_t DESC_HI_VEC = 1u;
template <int TA, int AOFF, int BOFF>
__device__ __forceinline__ void wgmma_n8(float (&d)[4], uint32_t alo, uint32_t blo, int accumulate) {
    asm volatile("{\n.reg .pred p;\n.reg .b32 a, b;\n.reg .b64 da, db;\nsetp.ne.b32 p, %6, 0;\n"
                 "add.u32 a, %4, %8;\nadd.u32 b, %5, %9;\nmov.b64 da, {a, %10};\nmov.b64 db, {b, %11};\n"
                 "wgmma.mma_async.sync.aligned.m64n8k16.f32.bf16.bf16 {%0,%1,%2,%3}, da, db, p, 1, 1, %7, 0;\n}"
                 : "+f"(d[0]), "+f"(d[1]), "+f"(d[2]), "+f"(d[3])
                 : "r"(alo), "r"(blo), "r"(accumulate), "n"(TA), "n"(AOFF >> 4), "n"(BOFF >> 4), "n"(DESC_HI_TILE), "n"(DESC_HI_VEC));
}
template <int KS, int END>
__device__ __forceinline__ void qk_steps(float (&d)[4], uint32_t alo, uint32_t blo) {
    if constexpr (KS < END) {
        wgmma_n8<0, (KS >> 2) * 1024 + (KS & 3) * 32, KS * 32>(d, alo, blo, KS > 0);
        qk_steps<KS + 1, END>(d, alo, blo);
    }
}
__device__ __forceinline__ void pv_steps(float (&e)[3][4], uint32_t alo, uint32_t blo, int acc) {
    wgmma_n8<1, 0, 0>(e[0], alo, blo, acc); wgmma_n8<1, 1024, 0>(e[1], alo, blo, acc); wgmma_n8<1, 2048, 0>(e[2], alo, blo, acc);
    wgmma_n8<1, 6144, 32>(e[0], alo, blo, 1); wgmma_n8<1, 7168, 32>(e[1], alo, blo, 1); wgmma_n8<1, 8192, 32>(e[2], alo, blo, 1);
}
__device__ __forceinline__ void wg_fence() { asm volatile("wgmma.fence.sync.aligned;" ::: "memory"); }
__device__ __forceinline__ void wg_commit() { asm volatile("wgmma.commit_group.sync.aligned;" ::: "memory"); }
template <int N> __device__ __forceinline__ void wg_wait() { asm volatile("wgmma.wait_group.sync.aligned %0;" ::"n"(N) : "memory"); }
__device__ __forceinline__ void acc_ready(float (&d)[4]) { asm volatile("" : "+f"(d[0]), "+f"(d[1]), "+f"(d[2]), "+f"(d[3]) :: "memory"); }
__device__ __forceinline__ uint32_t score_pair(float (&d)[4]) {
    acc_ready(d);
    const uint32_t r = pack2(d[0], d[2]);
    return pack2(bf_lo(r) * SCALE, bf_hi(r) * SCALE);
}

__device__ __forceinline__ void attention_role(const Params& p, int w, int lane) {
    const int cta = blockIdx.x, t4 = lane & 3, g = lane >> 2;
    mbar_wait(bar_at(B_EP), 0);
    const uint32_t tag0 = lds32(SM_EPOCH) * NB;
    const char* const odst = p.scr + SCR_O + head_off(cta >> 2) + (2 * w + (g >> 2)) * 256 + (cta & 3) * 64 + (g & 3) * 16;
    const uint32_t pdst = SM_P + ((t4 + 3) & 3) * PSTR + (16 * w + g) * 2;
    auto softmax = [&](uint32_t& sc, int ps) -> uint32_t {
        const float s0 = bf_lo(sc), s1 = bf_hi(sc);
        int key = __float_as_int(fmaxf(s0, s1));
        key ^= (key >> 31) & 0x7fffffff;
        key = __reduce_max_sync(0xffffffffu, key);
        sts32(SM_MAX + w * 4, key);
        bar_sync<4, 128>();
        const uint4 mx = lds128(SM_MAX);
        key = max(max((int)mx.x, (int)mx.y), max((int)mx.z, (int)mx.w));
        key ^= (key >> 31) & 0x7fffffff;
        const float mb = __int_as_float(key) * LOG2E;
        const uint32_t pp = pack2(fast_ex2(fmaf(s0, LOG2E, -mb)), fast_ex2(fmaf(s1, LOG2E, -mb)));
        sts16(pdst + ps * 4 * PSTR, pp); sts16(pdst + ps * 4 * PSTR + 16, pp >> 16);
        fence_async();
        bar_sync<4, 128>();
        sc = pp;
        return key;
    };
    auto put_sum = [&](uint32_t pp, int ps) {
        uint32_t fs;
        asm volatile("redux.sync.add.u32 %0, %1, 0xffffffff;" : "=r"(fs) : "r"(__float2uint_rn((bf_lo(pp) + bf_hi(pp)) * 8388608.f)) : "memory");
        sts32(SM_SUM + ps * 16 + w * 4, fs);
    };
    auto aux_word = [&](uint32_t mx, const uint4& u, int k) {
        const float l = __uint2float_rn((u.x + u.y) + (u.z + u.w)) * (1.f / 8388608.f);
        return (g < 4 ? mx : (__float_as_uint(l) + 0x80u) & 0xffffff00u) | ((tag0 + k) & 0x7fu) | 0x80u;
    };
    auto send = [&](float (&e)[3][4], uint32_t aux, int ps) {
        acc_ready(e[0]); acc_ready(e[1]); acc_ready(e[2]);
        const uint32_t o0 = pack2(e[0][0], e[0][2]), o1 = pack2(e[1][0], e[1][2]), o2 = pack2(e[2][0], e[2][2]);
        st_pkt2_if(t4 == 0, odst + ps * 2048, o0, o1, o2, aux);
        mbar_arrive_if(lane == 0, bar_at(ps ? B_RV : B_PS));
    };
    mbar_wait(bar_at(B_QR), 0);
    TRACES(73);
#pragma unroll 1
    for (int it = 0; it <= NB; it++) {
        uint32_t m1 = 0;
        if (it < NB) {
            const uint32_t tab = slots(it);
            const uint32_t ka = SB + (2 * w + ((lane >> 3) & 1)) * 3072 + (lane & 7) * 128 + (((lane >> 4) ^ (lane & 7)) << 4);
            const uint32_t qa = SM_Q + it * 384 + (lane >> 3) * 16;
            uint32_t sc = 0;
#pragma unroll 1
            for (int u = 0; u < 4; u++) {
                const uint32_t base = ka + slot_at(tab, pass_nibble(it, u)) * PAIR;
                mbar_wait(bar_at(B_F1 + 2 * u + (w >> 1)), it & 1);
                float d0[4] = {}, d1[4] = {};
#pragma unroll
                for (int c = 0; c < 6; c++) {
                    uint32_t a0[4], a1[4], b[4];
                    ldsm4(b, qa + c * 64);
                    ldsm4(a0, (base ^ ((c & 1) * 64)) + (c >> 1) * 1024);
                    ldsm4(a1, (base ^ ((c & 1) * 64 + 32)) + (c >> 1) * 1024);
                    mma16816(d0, a0[0], a0[1], a0[2], a0[3], b[0], b[1]);
                    mma16816(d1, a1[0], a1[1], a1[2], a1[3], b[2], b[3]);
                }
                const uint32_t r = pack2(d0[0] + d1[0], d0[2] + d1[2]);
                mbar_arrive_if(lane == 0, bar_at(B_RR + 2 * u + (w >> 1)));
                if (t4 == ((u + 1) & 3)) sc = pack2(bf_lo(r) * SCALE, bf_hi(r) * SCALE);
            }
            m1 = softmax(sc, 0);
            put_sum(sc, 0);
        }
        if (it > 0) {
            const int k = it - 1;
            const uint32_t tab = slots(k);
            const uint32_t v0 = slot_at(tab, k < NB - 1 ? 0 : 4);
            TRACES(48 + k * 6);
            if (k > 0) mbar_wait(bar_at(B_F3), it & 1);
            mbar_wait(bar_at(B_QR), it & 1);
            fence_async();
            TRACES(49 + k * 6);
            float d[4][4] = {};
            const bool busy = k < NB - 1;
#pragma unroll
            for (int u = 0; u < 4; u++) {
                const uint32_t alo = desc_lo(SB) + slot_at(tab, u) * (PAIR >> 4), blo = desc_lo(SM_Q + 4 * 384);
                wg_fence();
                qk_steps<0, 6>(d[u], alo, blo);
                wg_commit();
                if (busy) {
                    wg_wait<1>();
                    if (u > 0) mbar_arrive_if(lane == 0, bar_at(B_RK + u - 1));
                }
                wg_fence();
                qk_steps<6, 12>(d[u], alo, blo);
                wg_commit();
                if (u < 3 && busy) wg_wait<1>();
            }
            wg_wait<2>();
            uint32_t sc = shi(score_pair(d[0]), lane & 28), s = shi(score_pair(d[1]), lane & 28);
            if (t4 == 2) sc = s;
            s = shi(score_pair(d[2]), lane & 28);
            if (t4 == 3) sc = s;
            wg_wait<0>();
            s = score_pair(d[3]);
            if (t4 == 0) sc = s;
            mbar_arrive_if(lane == 0, bar_at(B_RK + 3));
            TRACES(50 + k * 6);
            const uint32_t m2 = softmax(sc, 1);
            TRACES(51 + k * 6);
            float e[3][4] = {};
#pragma unroll
            for (int t = 0; t < 8; t++) {
                const int pr = ((t >> 1) + 1) & 3;
                if (t == 6 && k < NB - 1) mbar_wait(bar_at(B_FL), k & 1);
                wg_fence();
                pv_steps(e, desc_lo(SB + (t & 1) * TILE) + (pr ? slot_at(tab, 4 + pr) : v0) * (PAIR >> 4), desc_lo(SM_P + (4 + pr) * PSTR + (t & 1) * 64), t > 0);
                wg_commit();
                if (t < 7 && busy) wg_wait<1>();
                if (t == 1) put_sum(sc, 1);
            }
            bar_sync<4, 128>();
            const uint32_t aux = opaque(aux_word(m2, lds128(SM_SUM + 16), k));
            wg_wait<0>();
            send(e, aux, 1);
            TRACES(52 + k * 6);
        }
        if (it < NB) {
            const uint32_t tab = slots(it);
            if (it == 0) st_pkt2_if(t4 == 0, odst, 0, 0, 0, 0);
            bar_sync<4, 128>();
            const uint32_t aux = opaque(aux_word(m1, lds128(SM_SUM), it));
            float e[3][4] = {};
#pragma unroll 1
            for (int u = 0; u < 4; u++) {
                const uint32_t alo = desc_lo(SB) + slot_at(tab, 4 + u) * (PAIR >> 4), blo = desc_lo(SM_P) + u * (PSTR >> 4);
                mbar_wait(bar_at(B_F1 + 8 + 2 * u), it & 1);
                wg_fence();
                pv_steps(e, alo, blo, u > 0);
                wg_commit();
                wg_wait<1>();
                if (u == 1) mbar_arrive_if(lane == 0, bar_at(B_RP));
                mbar_wait(bar_at(B_F1 + 9 + 2 * u), it & 1);
                wg_fence();
                pv_steps(e, alo + (TILE >> 4), blo + 4, 1);
                wg_commit();
                wg_wait<1>();
            }
            wg_wait<0>();
            send(e, aux, 0);
            TRACES(53 + it * 6);
        }
    }
}

__device__ __forceinline__ void ln_finish(float s, float q, float& mean_b, float& rden) {
    const float mean = s * (1.f / DM);
    const float var = fmaxf(fmaf(q, 1.f / DM, -mean * mean), 0.f);
    mean_b = bfr(mean);
    rden = fast_rcp(bfr(fast_sqrt(bfr(bfr(var) + 1e-5f))));
}
__device__ __forceinline__ uint32_t ln_apply(uint32_t w, float mean_b, float rden) {
    const uint32_t d = bsub2(w, __byte_perm(__float_as_uint(mean_b), 0, 0x3232));
    return pack2(bf_lo(d) * rden, bf_hi(d) * rden);
}
__device__ __forceinline__ void put_x(uint32_t x01, uint32_t x2, uint32_t wa, bool e2) {
    jitter();
    sts16(wa, x01); sts16(wa + 8, x01 >> 16);
    sts16_if(!e2, wa + 16, x2);
}
__device__ __forceinline__ void get_x(uint32_t (&b)[10], uint32_t ra) {
    __syncwarp();
    const uint4 u = lds128(ra), v = lds128(ra + 16);
    const uint2 z = lds64(ra + 32);
    b[0] = u.x; b[1] = u.y; b[2] = u.z; b[3] = u.w; b[4] = v.x; b[5] = v.y; b[6] = v.z; b[7] = v.w; b[8] = z.x; b[9] = z.y;
}
__device__ __forceinline__ float fold(float a, float b, bool sel, int m) { return (sel ? b : a) + shx(sel ? a : b, m); }

__device__ __forceinline__ void chain_role(const Params& p, int w, int lane, uint32_t t0) {
    const int cta = blockIdx.x, h = cta >> 2, s = cta & 3;
    const int g = lane >> 2, t4 = lane & 3;
    const bool e1 = t4 & 1, e2 = t4 & 2;
    uint32_t wq[5][3][4], wo[3][5][4], wg[5][4], wh[5][2], wd[4][4];
    const int col0 = 80 * w + (e2 ? 48 : 0) + g + (e1 ? 8 : 0);
    const uint32_t xw = opaque(SM_X + w * 384 + 48 * (g >> 1) + (e2 ? 24 : 0) + (e1 ? 4 : 0) + 2 * (g & 1));
    const uint32_t xr = opaque(g == 1 ? SM_ONES : SM_X + w * 384 + (g == 3 ? 192 : 0) + 48 * t4);
    TRACES(75);
    sts32_if(lane < 12, SM_ONES + lane * 4, 0x3f803f80u);
    uint32_t zero = lane >> 5;
    const int mi = lane >> 3, mr = lane & 7;
    mbar_wait(bar_at(B_W), 0);
    TRACES(74);
    sts16(xw + 192, lds16(ST_X + 5120 + col0 * 2)); sts16(xw + 200, lds16(ST_X + 5120 + col0 * 2 + 32));
    sts16_if(!e2, xw + 208, lds16(ST_X + 5120 + col0 * 2 + 64));
#pragma unroll
    for (int i = 0; i < 5; i++)
#pragma unroll
        for (int mt = 0; mt < 3; mt++) ldsm4t(wq[i][mt], ST_WQ + (80 * w + 16 * i + mr + 8 * (mi >> 1)) * 96 + 32 * mt + 16 * (mi & 1), zero);
    const bool odd = cta & 1;
    const uint32_t lo = ST_WD + (mr + (odd ? 4 : 0)) * 1280 + 160 * w + 16 * (mi & 1);
    const uint32_t hi = ST_WD + ((mr & 3) + (odd ? 0 : 8)) * 1280 + 160 * w + 16 * (mi & 1);
    ldsm4t(wd[0], lo + 96 * (mi >> 1), zero);
    ldsm4t(wd[1], lo + 96 * (mi >> 1) + 32, zero);
    ldsm4t(wd[2], (mi < 2 ? lo : hi) + 64, zero);
    ldsm4t(wd[3], hi + 32 * (mi >> 1) + 96 * (mr >> 2), zero);
    fence_async();
    __syncwarp();
    mbar_arrive_if(lane == 0, bar_at(B_WC));
    mbar_wait(bar_at(B_EP), 0);
    const uint32_t near = __shfl_sync(0xffffffffu, near_half(), 0);
    uint32_t x01 = 0, x2 = 0, nx01 = 0, nx2 = 0;
#pragma unroll 1
    for (int n = -5; n < NROUND; n++) {
        const bool last = (ORD_LAST >> (n & 15)) & 1, head = !((ORD_NO_HEAD >> (n & 15)) & 1);
        const int k = (ORD_BATCH >> (2 * (n & 15))) & 3;
        if (n > -5 && n <= 0) bar_sync<7, 288>();
        else if (!last) bar_sync<2, 256>();
        TRACES(n <= 0 ? 83 + n : 95);
        const char* const slice = p.scr + acc_off(k, last, w);
        const char* const cell = opaque(slice + g * 256 + t4 * 16);
        if (n < -1) {
            const uint32_t xa = ST_X + (n + 5) * 1280, ln = opaque(lane);
            const int col0 = 80 * w + (ln & 2 ? 48 : 0) + (ln >> 2) + (ln & 1 ? 8 : 0);
            float sm = 0.f, sq = 0.f;
#pragma unroll
            for (int i = 0; i < 5; i++) {
                const uint2 c = lds64(xa + i * 256 + ln * 8);
                sm += (bf_lo(c.x) + bf_hi(c.x)) + (bf_lo(c.y) + bf_hi(c.y));
                sq = fmaf(bf_lo(c.x), bf_lo(c.x), fmaf(bf_hi(c.x), bf_hi(c.x), fmaf(bf_lo(c.y), bf_lo(c.y), fmaf(bf_hi(c.y), bf_hi(c.y), sq))));
            }
            x01 = lds16(xa + col0 * 2) | lds16(xa + col0 * 2 + 32) << 16;
            x2 = lds16(xa + col0 * 2 + 64);
#pragma unroll
            for (int o = 16; o; o >>= 1) { sm += shx(sm, o); sq += shx(sq, o); }
            float mean_b, rden;
            ln_finish(sm, sq, mean_b, rden);
            x01 = ln_apply(x01, mean_b, rden);
            x2 = ln_apply(x2, mean_b, rden);
            put_x(x01, x2, xw, e2);
        } else {
        if (n >= 0) {
          if (head) {
            if (!last || n == NROUND - 1) mbar_wait(bar_at(B_Z), (k + last) & 1);
            const char* src = p.scr + SCR_O + head_off(h) + head_near(h, near) + last * 2048 + (w & 6) * 256 + (lane & 15) * 16;
            const uint32_t tag = (lds32(SM_EPOCH) * NB + k) | 0x80u;
            mbar_wait(bar_at(last ? B_RV : B_PS), k & 1);
            if (!last && k < NB - 1) wait_ns(t0 + batch_ns(k + 1) + CFG(START));
            uint4 v, z;
            {
                SPIN_DECL;
                do {
                    v = ld_pkt(src); z = ld_pkt(src + 256);
                    SPIN_CHECK(n);
                } while (__any_sync(0xffffffffu, (((v.w ^ tag) | (z.w ^ tag)) & 0xffu) != 0));
            }
            TRACES(tr + 0);
            float a[3][4] = {};
            const uint32_t bb[3][2] = {{v.x, v.y}, {z.x, z.y}, {v.z, z.z}};
            float sa, sb, rl;
#pragma unroll
            for (int i = 0; i < 3; i++) {
                const uint32_t l0 = g < 4 ? bb[i][0] : 0, l1 = g < 4 ? bb[i][1] : 0, h0 = g < 4 ? 0 : bb[i][0], h1 = g < 4 ? 0 : bb[i][1];
#pragma unroll
                for (int mt = 0; mt < 5; mt++)
                    mma16816(a[mt % 3], wo[i][mt][0], wo[i][mt][1], wo[i][mt][2], wo[i][mt][3], mt < 3 ? l0 : h0, mt < 3 ? l1 : h1);
                if (i == 0) {
                    int key = v.w & 0xffffff00u;
                    key ^= (key >> 31) & 0x7fffffff;
                    key = __reduce_max_sync(0xffffffffu, key);
                    key ^= (key >> 31) & 0x7fffffff;
                    const float ws = fast_ex2((F(v.w & 0xffffff00u) - __int_as_float(key)) * LOG2E);
                    sa = shi(ws, e1 ? 8 : 0); sb = shi(ws, e1 ? 12 : 4);
                    rl = ws * F(z.w & 0xffffff00u);
                    rl += shx(rl, 4);
                }
                if (i == 1) rl += shx(rl, 8);
            }
            float y[3];
#pragma unroll
            for (int j = 2; j < 5; j++) {
                const int mt = j % 3;
                y[mt] = fold(fmaf(a[mt][0], sa, a[mt][1] * sb), fmaf(a[mt][2], sa, a[mt][3] * sb), e1, 1);
            }
            const uint32_t pa = SM_PO + w * 512 + lane * 16;
            if (w < 2) {
                const char* dst = opaque(cell + s * 16384);
                rl = fast_rcp(rl);
                bar_sync<1, 256>();
                const uint4 c1 = lds128(pa), c2 = lds128(pa + 1024), c3 = lds128(pa + 2048);
                red_cell2_if(true, dst, ((y[0] + F(c1.x)) + (F(c2.x) + F(c3.x))) * rl, ((y[1] + F(c1.y)) + (F(c2.y) + F(c3.y))) * rl,
                             ((y[2] + F(c1.z)) + (F(c2.z) + F(c3.z))) * rl);
            } else {
                stsf4(pa - 1024, y[0], y[1], y[2], 0.f);
                bar_sync<1, 256>();
            }
            TRACES(tr + 1);
            if ((ORD_NO_TAIL >> n) & 1) continue;
            const uint32_t tsend = clk32();
            if (n == 0) {
                st_pkt2_if(lane < 4, p.scr + SCR_O + head_off(h) + 2048 + w * 256 + s * 64 + lane * 16, 0, 0, 0, 0);
                __syncwarp();
            } else if (!last) {
                const char* nsrc = p.scr + acc_off(k - 1, 1, w) + near + g * 256 + t4 * 16;
                SPIN_DECL;
                do {
                    v = ld_pkt(nsrc);
                    SPIN_CHECK(n);
                    nx01 = pack2(F(v.x), F(v.y)); nx2 = pack2(F(v.z), 0.f);
                } while (__any_sync(0xffffffffu, v.w != FULL_A));
            }
            wait_clk(tsend + (w < 2 ? 0 : 60) + (n < QUIET ? CFG(DLY_AL) : CFG(DLY_A)));
            {
                SPIN_DECL;
                do {
                    v = ld_pkt(cell + near);
                    SPIN_CHECK(n);
                    x01 = pack2(F(v.x), F(v.y));
                    x2 = pack2(F(v.z), 0.f);
                    put_x(x01, x2, xw, e2);
                } while (__any_sync(0xffffffffu, v.w != FULL_A));
            }
            TRACES(tr + 2);
          } else { x01 = nx01; x2 = nx2; put_x(x01, x2, xw, e2); }
        } else {
            mbar_wait(bar_at(B_W + 1), 0);
            const uint32_t ln = opaque(lane);
            const int mi = ln >> 3, mr = ln & 7;
            uint32_t zero = ln >> 5;
            TRACES(76);
#pragma unroll
            for (int i = 0; i < 3; i++) {
                const int d = 16 * (w >> 1) + (mr >> 1) + 8 * (mr & 1) + (i < 2 ? 64 * (mi >> 1) + 4 * i : 128 + 4 * (mi >> 1));
#pragma unroll
                for (int mt = 0; mt < 5; mt++) ldsm4t(wo[i][mt], ST_WO + d * 320 + 160 * (w & 1) + 32 * mt + 16 * (mi & 1), zero);
            }
            fence_async();
            __syncwarp();
            mbar_arrive_if(lane == 0, bar_at(B_WC + 1));
            mbar_wait(bar_at(B_W + 2), 0);
            TRACES(77);
#pragma unroll
            for (int i = 0; i < 5; i++) {
                const uint32_t ga = ST_WG + (mi & 1) * 20480 + (80 * w + 16 * i + mr + 8 * (mi >> 1)) * 32;
                uint32_t r[4];
                ldsm4t(wg[i], ga + (odd ? 16 : 0), zero);
                ldsm4t(r, ga + (odd ? 0 : 16), zero);
#pragma unroll
                for (int kh = 0; kh < 2; kh++) {
                    const uint32_t moved = __shfl_xor_sync(0xffffffffu, odd ? r[2 * kh] : r[2 * kh + 1], 16);
                    wh[i][kh] = (g < 4) == odd ? moved : odd ? r[2 * kh + 1] : r[2 * kh];
                }
            }
            fence_async();
            __syncwarp();
            mbar_arrive_if(lane == 0, bar_at(B_WC + 2));
            TRACES(72);
            x01 = 0x3f803f80u; x2 = 0x3f80u;
            put_x(x01, x2, xw, e2);
        }
        {
            uint32_t b[10];
            get_x(b, xr);
            float a[2][4] = {};
#pragma unroll
            for (int i = 0; i < 5; i++) {
                mma16816(a[0], wg[i][0], wg[i][1], wg[i][2], wg[i][3], b[2 * i], b[2 * i + 1]);
                mma16816(a[1], wh[i][0], b[2 * i], wh[i][1], b[2 * i + 1], b[2 * i], b[2 * i + 1]);
            }
            stsf(SM_PG + (w >> 2) * 512 + (g + 8 * t4) * 16 + (w & 3) * 4, e2 ? (e1 ? a[1][2] : a[1][0]) : (e1 ? a[0][2] : a[0][0]));
            const uint2 cs = lds64(SM_CSG + lane * 48);
            const char* dst = opaque(cell + 3 * HALF - near);
            bar_sync<2, 256>();
            const float S = sum8(lds128(SM_PG + lane * 16), lds128(SM_PG + 512 + lane * 16));
            const float sx = shi(S, 25), sq = shi(S, 24), Su = shi(S, lane + (lane < 16 ? 8 : 4));
            if (n < 0) {
                if (w == 0) stsf2(SM_CSG + lane * 48, S, Su);
            } else {
                float mean_b, rden;
                ln_fast(sx, sq, mean_b, rden);
                const float gv = bfr(fmaf(-mean_b, F(cs.x), S) * rden), uv = bfr(fmaf(-mean_b, F(cs.y), Su) * rden);
                const float sg = fast_rcp(1.f + fast_ex2(-LOG2E * gv));
                const uint32_t hb = pack2(bfr(gv * sg) * uv, 0.f);
                const uint32_t b0 = __byte_perm(shi(hb, 2 * t4), shi(hb, 2 * t4 + 1), 0x5410);
                const uint32_t b1 = __byte_perm(shi(hb, e1 ? 18 : 16), shi(hb, e1 ? 19 : 17), 0x5410);
                const bool up = g >= 4;
                const uint32_t l0 = up ? 0 : b0, h0 = up ? b0 : 0;
                const uint32_t m1 = up == e2 ? b1 : 0;
                float d[3][4] = {};
                mma16816(d[0], wd[0][0], wd[0][1], wd[0][2], wd[0][3], l0, h0);
                mma16816(d[1], wd[1][0], wd[1][1], wd[1][2], wd[1][3], l0, h0);
                mma16816(d[2], wd[2][0], wd[2][1], wd[2][2], wd[2][3], l0, up ? 0 : m1);
                mma1688(d[0], wd[3][0], wd[3][1], m1);
                mma1688(d[1], wd[3][2], wd[3][3], m1);
                red_cell(dst, e1 ? d[0][2] : d[0][0], e1 ? d[1][2] : d[1][0], e1 ? d[2][2] : d[2][0]);
                const uint32_t tsend = clk32();
                TRACES(tr + 3);
                if (last && w != cta >> 4) continue;
                const float sgr = shi(sg, 27);
                const uint32_t sg2 = pack2(sgr, sgr);
                const uint32_t n01 = opaque(pack2((bf_lo(x01) - mean_b) * rden, (bf_hi(x01) - mean_b) * rden));
                const uint32_t n2 = opaque(pack2((bf_lo(x2) - mean_b) * rden, 0.f));
                if (last) {
                    sts128_if(lane >> 1 == (cta & 15), SM_FIN + (lane & 1) * 16, x01, n01, __byte_perm(x2, n2, 0x5410), sg2);
                    mbar_arrive_if(lane >> 1 == (cta & 15), bar_at(B_FIN));
                    __syncwarp();
                    continue;
                }
                wait_clk(tsend + (n < QUIET ? CFG(DLY_BL) : CFG(DLY_B)));
                const uint32_t r01 = x01, r2 = x2;
                float cnt;
                SPIN_DECL;
                do {
                    const uint4 v = ld_pkt(cell + 2 * HALF), z = ld_pkt(cell + 3 * HALF);
                    SPIN_CHECK(n);
                    cnt = F(v.w) + F(z.w);
                    x01 = badd2(r01, badd2(n01, bmul2(pack2(F(v.x) + F(z.x), F(v.y) + F(z.y)), sg2)));
                    x2 = badd2(r2, badd2(n2, bmul2(pack2(F(v.z) + F(z.z), 0.f), sg2)));
                    put_x(x01, x2, xw, e2);
                } while (__any_sync(0xffffffffu, cnt != NCTA));
                TRACES(tr + 4);
            }
        }
        }
        {
            uint32_t b[10];
            get_x(b, xr);
            float a[3][4] = {};
            const float f0 = bf_lo(x01), f1 = bf_hi(x01), f2 = e2 ? 0.f : bf_lo(x2);
            float st;
#pragma unroll
            for (int i = 0; i < 5; i++) {
#pragma unroll
                for (int mt = 0; mt < 3; mt++) {
                    mma16816(a[mt], wq[i][mt][0], wq[i][mt][1], wq[i][mt][2], wq[i][mt][3], b[2 * i], b[2 * i + 1]);
                    if (i == 0 && mt == 0) st = fold(fmaf(f0, f0, fmaf(f1, f1, f2 * f2)), (f0 + f1) + f2, g & 1, 4);
                }
                if (i < 4) st += shx(st, i < 2 ? 1 << i : 2 << i);
            }
            const uint32_t pa = SM_PQ + (w >> 2) * 1024 + (g & 1) * 512 + ((e2 ? 16 : 0) + (e1 ? 4 : 0) + (g >> 1)) * 16 + (w & 3) * 4;
            stsf(pa + 128, e2 ? st : e1 ? a[1][2] : a[1][0]);
            stsf(pa, e2 ? (e1 ? a[2][2] : a[2][0]) : (e1 ? a[0][2] : a[0][0]));
            bar_sync<3, 288>();
            if (n >= 0 && w == cta >> 4) {
                red_cell2_if(lane >> 1 == (cta & 15), cell + (acc_off(k, 1, 0) - acc_off(k, 0, 0)), f0, f1, f2);
                __syncwarp();
            }
        }
    }
}

template <int ID> __device__ __forceinline__ void role_exit() { asm volatile("exit; // %0" ::"n"(ID)); }
constexpr int NTHREADS = 512;
#define STR2(x) #x
#define STR(x) STR2(x)
__global__ void __launch_bounds__(NTHREADS, 1)
decode_kernel(const Params p, const __grid_constant__ Maps tm) {
    extern __shared__ __align__(1024) unsigned char smem[];
    if (threadIdx.x == 0) l2_prefetch(p.wq + (size_t)blockIdx.x * 12288, 12288);
    const uint32_t t0 = now_ns() - CFG(LEAD);
    const int lane = threadIdx.x & 31;
    const int warp = __reduce_max_sync(0xffffffffu, threadIdx.x >> 5);
    if (warp < 8) {
        asm volatile("setmaxnreg.inc.sync.aligned.u32 " STR(CFG_REG_CHAIN) ";");
        bar_arrive<5, 480 + 0>();
        const uint32_t vote = probe_near(p, warp, lane);
        bar_sync<2, 256 + 32>();
        sts32(SM_NEAR + warp * 4, vote);
        mbar_arrive_if(lane == 0, bar_at(B_EP));
        chain_role(p, warp, __shfl_sync(0xffffffffu, lane, lane), t0);
        role_exit<3>();
    } else if (warp < 12) {
        asm volatile("setmaxnreg.dec.sync.aligned.u32 " STR(CFG_REG_ATT) ";");
        if (elect_one()) {
#pragma unroll 1
            for (int i = warp - 8; i < NBAR; i += 4)
                if (i < B_W || i >= B_WC) mbar_init(bar_at(i), i == B_FIN ? 2 : i == B_EP ? 9 : i == B_QR ? 32 : i == B_PS || i == B_RP ? 4 : i >= B_F3 ? 1 : i >= B_WC ? 8 : i < B_RR || i > B_RV ? 1 : i < B_RK ? 2 : 4);
            asm volatile("fence.mbarrier_init.release.cluster;" ::: "memory");
            fence_async();
        }
        bar_sync<5, 480>();
        attention_role(p, warp - 8, lane);
        role_exit<2>();
    } else {
        asm volatile("setmaxnreg.dec.sync.aligned.u32 " STR(CFG_REG_HELP) ";");
        if (warp == 12) {
            load_role(p, &tm.k, lane, t0);
            role_exit<0>();
        } else {
            if (warp == 14) {
                if (smem_u32(smem) != SB) __trap();
                if (elect_one()) {
                    asm volatile("prefetch.tensormap [%0];" ::"l"(&tm.q) : "memory");
                    mbar_init(bar_at(B_W), 1); mbar_init(bar_at(B_W + 1), 1); mbar_init(bar_at(B_W + 2), 1);
                    asm volatile("fence.mbarrier_init.release.cluster;" ::: "memory");
                    fence_async();
                    mbar_expect_tx(bar_at(B_W), 61440 + 15360 + 6400); mbar_expect_tx(bar_at(B_W + 1), 61440); mbar_expect_tx(bar_at(B_W + 2), 40960);
                    bulk_load(ST_X, p.x, 5120, bar_at(B_W));
                    bulk_load(ST_X + 5120, p.wr, 1280, bar_at(B_W));
                }
                reload_role(p, &tm, t0);
            } else {
                unsigned ticket = 0;
                if (warp == 15 && lane == 0) asm volatile("atom.relaxed.gpu.global.add.u32 %0, [%1], 1;" : "=r"(ticket) : "l"(&g_epoch) : "memory");
                if (warp == 13 && elect_one()) {
                    asm volatile("prefetch.tensormap [%0];" ::"l"(&tm.g) : "memory");
                    asm volatile("prefetch.tensormap [%0];" ::"l"(&tm.u) : "memory");
                    asm volatile("prefetch.tensormap [%0];" ::"l"(&tm.o) : "memory");
                    asm volatile("prefetch.tensormap [%0];" ::"l"(&tm.k) : "memory");
                    asm volatile("prefetch.tensormap [%0];" ::"l"(&tm.v) : "memory");
                }
                bar_sync<5, 480>();
                if (warp == 13) { bar_arrive<6, 64>(); q_role(p, lane); }
                else { bar_arrive<2, 256 + 32>(); zero_role(p, lane, ticket, t0); }
            }
            role_exit<1>();
        }
    }
}

typedef CUresult (*EncodeFn)(CUtensorMap*, CUtensorMapDataType, cuuint32_t, void*, const cuuint64_t*, const cuuint64_t*,
                             const cuuint32_t*, const cuuint32_t*, CUtensorMapInterleave, CUtensorMapSwizzle,
                             CUtensorMapL2promotion, CUtensorMapFloatOOBfill);

bool make_map(EncodeFn fn, CUtensorMap* m, const void* ptr, uint64_t cols, uint64_t rows, uint32_t bc, uint32_t br) {
    cuuint64_t dims[2] = {cols, rows};
    cuuint64_t strides[1] = {cols * 2};
    cuuint32_t box[2] = {bc, br};
    cuuint32_t es[2] = {1, 1};
    return fn(m, CU_TENSOR_MAP_DATA_TYPE_BFLOAT16, 2, const_cast<void*>(ptr), dims, strides, box, es, CU_TENSOR_MAP_INTERLEAVE_NONE,
              CU_TENSOR_MAP_SWIZZLE_NONE, CU_TENSOR_MAP_L2_PROMOTION_L2_128B, CU_TENSOR_MAP_FLOAT_OOB_FILL_NONE) == CUDA_SUCCESS;
}

bool make_kv_map(EncodeFn fn, CUtensorMap* m, const void* ptr) {
    cuuint64_t dims[4] = {64, 8, 3, (cuuint64_t)NB * NHEAD * SK / 8};
    cuuint64_t strides[3] = {DH * 2, 128, 8 * DH * 2};
    cuuint32_t box[4] = {64, 8, 3, 4};
    cuuint32_t es[4] = {1, 1, 1, 1};
    return fn(m, CU_TENSOR_MAP_DATA_TYPE_BFLOAT16, 4, const_cast<void*>(ptr), dims, strides, box, es, CU_TENSOR_MAP_INTERLEAVE_NONE,
              CU_TENSOR_MAP_SWIZZLE_128B, CU_TENSOR_MAP_L2_PROMOTION_L2_128B, CU_TENSOR_MAP_FLOAT_OOB_FILL_NONE) == CUDA_SUCCESS;
}

}

extern "C" void kernel_launch(void* const* d_in, const int* in_sizes, int n_in, void* d_out, int out_size) {
    (void)in_sizes; (void)n_in; (void)out_size;
    static EncodeFn fn = nullptr;
    static const char* scr = nullptr;
    if (!fn) {
        void* f = nullptr;
        cudaDriverEntryPointQueryResult qr;
        if (cudaGetDriverEntryPoint("cuTensorMapEncodeTiled", &f, cudaEnableDefault, &qr) != cudaSuccess || !f) return;
        void* sp = nullptr;
        if (cudaGetSymbolAddress(&sp, g_scratch) != cudaSuccess) return;
        scr = (const char*)(((uintptr_t)sp + (2 << 20) - 1) & ~(uintptr_t)((2 << 20) - 1));
        fn = (EncodeFn)f;
        cudaFuncSetAttribute(decode_kernel, cudaFuncAttributeMaxDynamicSharedMemorySize, SMEM_BYTES);
    }
    Maps tm;
    if (!make_kv_map(fn, &tm.k, d_in[1]) || !make_kv_map(fn, &tm.v, d_in[2])) return;
    if (!make_map(fn, &tm.q, d_in[3], NHEAD * DH, DM, 48, 128) || !make_map(fn, &tm.o, d_in[4], DM, NHEAD * DH, 160, 32)) return;
    if (!make_map(fn, &tm.g, d_in[7], FF, DM, 16, 128) || !make_map(fn, &tm.u, d_in[8], FF, DM, 16, 128)) return;
    Params p;
    p.x = (const unsigned short*)d_in[0];
    p.wq = (const char*)d_in[3];
    p.wo = (const char*)d_in[4];
    p.wr = (const unsigned short*)d_in[6];
    p.wg = (const char*)d_in[7];
    p.wu = (const char*)d_in[8];
    p.wd = (const char*)d_in[9];
    p.out = (unsigned short*)d_out;
    p.scr = scr;
    decode_kernel<<<NCTA, NTHREADS, SMEM_BYTES>>>(p, tm);
}
```

```cpp
#include <cuda_runtime.h>
#include <cuda_bf16.h>
#include <cuda.h>
#include <stdint.h>

namespace {

constexpr int NB = 4, DM = 640, NHEAD = 32, DH = 192, SK = 4096, WIN = 1024, FF = 1536;
constexpr int NCTA = 128;
constexpr int TILE = 12288, PAIR = 2 * TILE;

#define CFG_LIST(X) \
    X(TICK0, 476)        \
    X(TICK, 492)        \
    X(LEAD, 450)        \
    X(STAG, 500)        \
    X(WLAG, 350)        \
    X(GSTEP, 750)        \
    X(WIN, 5)        \
    X(PMAX, 2)        \
    X(PGRACE, 50)        \
    X(LMAX0, 150)        \
    X(LMAX, 200) \
    X(GAIN, 5)        \
    X(VSTEP, 250)        \
    X(RSTEP, 640)        \
    X(RSTEP3, 450) \
    X(ZTILE, 11)        \
    X(START, 1)        \
    X(DLY_A, 410)        \
    X(DLY_AL, 100) \
    X(DLY_B, 570) \
    X(DLY_BL, 950) \
    X(DLY_F, 290) \
    X(FLIP, 0) \

#define X(n, v) constexpr int CFG_##n = v;
CFG_LIST(X)
#undef X
#define CFG(n) CFG_##n
constexpr int QUIET = 8;
#define CFG_REG_CHAIN 216
#define CFG_REG_ATT 48
#define CFG_REG_HELP 32
constexpr int KB_KV0 = 165;
__device__ __forceinline__ int kb_ns(int kb) { return kb * CFG(TICK0) / 12; }
__device__ __forceinline__ int tick_ns(int j) { return j <= 16 ? CFG(TICK0) : CFG(TICK); }
__device__ __forceinline__ int batch_ns(int k) { return kb_ns(KB_KV0) + (k ? 16 * (CFG(TICK0) + (k - 1) * CFG(TICK)) : 0); }

__device__ __forceinline__ uint32_t slots(int k) { return k & 2 ? (k & 1 ? 0x21304768u : 0x76835214u) : (k & 1 ? 0x21480765u : 0x76543210u); }
__device__ __forceinline__ int pass_nibble(int k, int u) { return k > 0 ? 4 + (u & 1) : u; }
__device__ __forceinline__ uint32_t slot_at(uint32_t tab, int u) { return (tab >> (4 * u)) & 15; }

constexpr int NROUND = 11;
constexpr uint32_t ORD_BATCH = 0x3b9910, ORD_LAST = 0x6da, ORD_NO_HEAD = 0x248, ORD_NO_TAIL = 0x092;

constexpr uint32_t SB = 1024;
constexpr uint32_t SM_BAR = SB + 9 * PAIR;
constexpr int B_F1 = 0;
constexpr int B_RR = 24;
constexpr int B_RK = 32;
constexpr int B_RV = 36;
constexpr int B_Z = 37;
constexpr int B_EP = 38;
constexpr int B_W = 39;
constexpr int B_WC = 42;
constexpr int B_FIN = 45;
constexpr int B_F3 = 46;
constexpr int B_PS = 48;
constexpr int B_RP = 49;
constexpr int B_FL = 50;
constexpr int B_QR = 51;
constexpr int NBAR = 52;
__host__ __device__ constexpr uint32_t bar_at(int i) { return SM_BAR + 8 * i; }
constexpr uint32_t SM_EPOCH = SM_BAR + 416;
constexpr uint32_t SM_MAX = SM_EPOCH + 16;
constexpr uint32_t SM_SUM = SM_MAX + 16;
constexpr uint32_t SM_NEAR = SM_SUM + 32;
constexpr uint32_t SM_FIN = SM_NEAR + 32;
constexpr uint32_t SM_Q = SM_FIN + 32;
constexpr uint32_t PSTR = 144;
constexpr uint32_t SM_P = SM_Q + 5 * 384;
constexpr uint32_t SM_X = SM_P + 8 * PSTR;
constexpr uint32_t SM_CSG = SM_X + 40;
constexpr uint32_t SM_ONES = SM_X + 8 * 384;
constexpr uint32_t SM_PG = SM_ONES + 48;
constexpr uint32_t SM_PO = SM_PG + 1024;
constexpr uint32_t SM_PQ = SM_PO;
constexpr int SMEM_BYTES = SM_PO + 3072 - SB;
static_assert(SMEM_BYTES <= 232448 && SM_Q % 16 == 0 && SM_P % 16 == 0 && SM_X % 16 == 0 && SM_PO % 16 == 0, "smem");
constexpr uint32_t ST_WQ = SB, ST_WD = SB + 3 * PAIR, ST_WO = SB + 4 * PAIR, ST_WG = SB + 7 * PAIR, ST_X = ST_WG + 40960;

__device__ unsigned g_epoch;
__device__ unsigned char g_scratch[4 << 20];
constexpr uint32_t HALF = 4096, SCR_O = 1 << 16, SCR_Q = 1 << 17, SCR_COUNT = 3 << 16;
__device__ __forceinline__ uint32_t acc_off(int k, int layer, int w) {
    return (k & 1) << 6 | layer << 7 | (w & 1) << 11 | (w >> 1) << 14 | (k + layer == NB) << 18;
}
__device__ __forceinline__ uint32_t head_off(int h) { return (h & 3) << 14 | (h & 4) << 16 | (h & 8) << 17 | (h & 16) << 9; }
__device__ __forceinline__ uint32_t head_near(int h, uint32_t near) { return near ^ HALF ^ (h & 16) << 8; }
constexpr uint32_t FULL_A = 0x42040000u;

struct Params {
    const char* wq;
    const unsigned short* x;
    const char* wo;
    const unsigned short* wr;
    const char* wg;
    const char* wu;
    const char* wd;
    unsigned short* out;
    const char* scr;
};

__device__ __forceinline__ uint32_t smem_u32(const void* p) { return (uint32_t)__cvta_generic_to_shared(p); }
__device__ __forceinline__ void mbar_init(uint32_t a, uint32_t c) { asm volatile("mbarrier.init.shared::cta.b64 [%0], %1;" ::"r"(a), "r"(c) : "memory"); }
__device__ __forceinline__ void mbar_expect_tx(uint32_t a, uint32_t b) {
    asm volatile("mbarrier.arrive.expect_tx.shared::cta.b64 _, [%0], %1;" ::"r"(a), "r"(b) : "memory");
}
__device__ __forceinline__ void mbar_arrive(uint32_t a) { asm volatile("mbarrier.arrive.shared::cta.b64 _, [%0];" ::"r"(a) : "memory"); }
constexpr uint32_t SPIN_LIMIT = 1u << 22;
#define SPIN_DECL uint32_t spins = 0
#define SPIN_CHECK(info) { if (++spins > SPIN_LIMIT) __trap(); }
__device__ __forceinline__ void jitter() {}
__device__ __forceinline__ void mbar_wait(uint32_t a, uint32_t parity) {
    jitter();
    uint32_t ok;
    SPIN_DECL;
    while (true) {
        asm volatile("{\n.reg .pred p;\nmbarrier.try_wait.parity.shared::cta.b64 p, [%1], %2;\nselp.u32 %0, 1, 0, p;\n}"
                     : "=r"(ok) : "r"(a), "r"(parity) : "memory");
        if (ok) break;
        SPIN_CHECK((a - SM_BAR) / 8 * 10 + parity);
    }
    jitter();
}
__device__ __forceinline__ bool mbar_test2(uint32_t a, uint32_t pa, uint32_t b, uint32_t pb) {
    uint32_t ok;
    asm volatile("{\n.reg .pred p, q;\nmbarrier.test_wait.parity.shared::cta.b64 p, [%1], %2;\n"
                 "mbarrier.test_wait.parity.shared::cta.b64 q, [%3], %4;\nand.pred p, p, q;\nvote.sync.all.pred p, p, 0xffffffff;\nselp.u32 %0, 1, 0, p;\n}"
                 : "=r"(ok) : "r"(a), "r"(pa), "r"(b), "r"(pb) : "memory");
    return ok;
}
__device__ __forceinline__ uint32_t now_ns() { uint32_t t; asm volatile("mov.u32 %0, %%globaltimer_lo;" : "=r"(t) :: "memory"); return t; }
__device__ __forceinline__ uint32_t clk32() { uint32_t c; asm volatile("mov.u32 %0, %%clock;" : "=r"(c) :: "memory"); return c; }
__device__ __forceinline__ void wait_ns(uint32_t t) { jitter(); while ((int)(now_ns() - t) < 0) {} }
__device__ __forceinline__ void wait_clk(uint32_t t) { jitter(); while ((int)(clk32() - t) < 0) {} }
__device__ __forceinline__ bool elect_one() {
    uint32_t e;
    asm volatile("{\n.reg .pred p;\nelect.sync _|p, 0xffffffff;\nselp.u32 %0, 1, 0, p;\n}" : "=r"(e));
    return e;
}
constexpr uint64_t POL_FIRST = 0x12F0000000000000ull, POL_NORMAL = 0x1000000000000000ull;
__device__ __forceinline__ void tma_tile(uint32_t dst, const CUtensorMap* tm, int group, uint32_t bar, uint64_t pol) {
    asm volatile("cp.async.bulk.tensor.4d.shared::cluster.global.mbarrier::complete_tx::bytes.L2::cache_hint"
                 " [%0], [%1, {%3, %3, %3, %4}], [%2], %5;"
                 ::"r"(dst), "l"(tm), "r"(bar), "r"(0), "r"(group), "l"(pol) : "memory");
}
__device__ __forceinline__ void tma2d(uint32_t dst, const CUtensorMap* tm, int x, int y, uint32_t bar) {
    asm volatile("cp.async.bulk.tensor.2d.shared::cluster.global.mbarrier::complete_tx::bytes [%0], [%1, {%3, %4}], [%2];"
                 ::"r"(dst), "l"(tm), "r"(bar), "r"(x), "r"(y) : "memory");
}
__device__ __forceinline__ void bulk_load(uint32_t dst, const void* src, uint32_t bytes, uint32_t bar) {
    asm volatile("cp.async.bulk.shared::cluster.global.mbarrier::complete_tx::bytes [%0], [%1], %2, [%3];"
                 ::"r"(dst), "l"(src), "r"(bytes), "r"(bar) : "memory");
}
__device__ __forceinline__ void l2_prefetch(const void* p, uint32_t bytes) {
    asm volatile("cp.async.bulk.prefetch.L2.global [%0], %1;" ::"l"(p), "r"(bytes) : "memory");
}
__device__ __forceinline__ void mma16816(float (&c)[4], uint32_t a0, uint32_t a1, uint32_t a2, uint32_t a3, uint32_t b0, uint32_t b1) {
    asm volatile("mma.sync.aligned.m16n8k16.row.col.f32.bf16.bf16.f32 {%0,%1,%2,%3}, {%4,%5,%6,%7}, {%8,%9}, {%0,%1,%2,%3};"
                 : "+f"(c[0]), "+f"(c[1]), "+f"(c[2]), "+f"(c[3]) : "r"(a0), "r"(a1), "r"(a2), "r"(a3), "r"(b0), "r"(b1));
}
__device__ __forceinline__ void mma1688(float (&c)[4], uint32_t a0, uint32_t a1, uint32_t b0) {
    asm volatile("mma.sync.aligned.m16n8k8.row.col.f32.bf16.bf16.f32 {%0,%1,%2,%3}, {%4,%5}, {%6}, {%0,%1,%2,%3};"
                 : "+f"(c[0]), "+f"(c[1]), "+f"(c[2]), "+f"(c[3]) : "r"(a0), "r"(a1), "r"(b0));
}
__device__ __forceinline__ void ldsm4(uint32_t (&r)[4], uint32_t a) {
    asm volatile("ldmatrix.sync.aligned.m8n8.x4.shared.b16 {%0,%1,%2,%3}, [%4];"
                 : "=r"(r[0]), "=r"(r[1]), "=r"(r[2]), "=r"(r[3]) : "r"(a) : "memory");
}
__device__ __forceinline__ void ldsm4t(uint32_t (&r)[4], uint32_t a, uint32_t& zero) {
    asm volatile("ldmatrix.sync.aligned.m8n8.x4.trans.shared.b16 {%0,%1,%2,%3}, [%4];"
                 : "=r"(r[0]), "=r"(r[1]), "=r"(r[2]), "=r"(r[3]) : "r"(a + zero) : "memory");
    zero &= r[3];
}
__device__ __forceinline__ uint4 ld_pkt(const void* p) {
    uint4 v;
    asm volatile("{\n.reg .b128 t;\nld.relaxed.gpu.global.b128 t, [%4];\nmov.b128 {%0,%1,%2,%3}, t;\n}"
                 : "=r"(v.x), "=r"(v.y), "=r"(v.z), "=r"(v.w) : "l"(p) : "memory");
    return v;
}
__device__ __forceinline__ void st_pkt(const void* p, uint32_t a, uint32_t b, uint32_t c, uint32_t d) {
    asm volatile("{\n.reg .b128 t;\nmov.b128 t, {%1,%2,%3,%4};\nst.relaxed.gpu.global.b128 [%0], t;\n}"
                 ::"l"(p), "r"(a), "r"(b), "r"(c), "r"(d) : "memory");
}
__device__ __forceinline__ uint2 ld_pkt8(const void* p) {
    uint2 v;
    asm volatile("{\n.reg .b64 t;\nld.relaxed.gpu.global.b64 t, [%2];\nmov.b64 {%0,%1}, t;\n}" : "=r"(v.x), "=r"(v.y) : "l"(p) : "memory");
    return v;
}
__device__ __forceinline__ void red_cell(const char* p, float a, float b, float c) {
    jitter();
    asm volatile("red.relaxed.gpu.global.add.v4.f32 [%0], {%1,%2,%3,%4};" ::"l"(p), "f"(a), "f"(b), "f"(c), "f"(1.0f) : "memory");
}
#define PRED(n) "{\n.reg .pred p;\nsetp.ne.u32 p, %" #n ", 0;\n"
__device__ __forceinline__ void red_cell2_if(bool on, const char* p, float a, float b, float c) {
    jitter();
    asm volatile(PRED(5) "@p red.relaxed.gpu.global.add.v4.f32 [%0], {%1,%2,%3,%4};\n@p red.relaxed.gpu.global.add.v4.f32 [%0+4096], {%1,%2,%3,%4};\n}"
                 ::"l"(p), "f"(a), "f"(b), "f"(c), "f"(1.0f), "r"((uint32_t)on) : "memory");
}
__device__ __forceinline__ void st_pkt8_if(bool on, const void* p, uint32_t a, uint32_t b) {
    jitter();
    asm volatile(PRED(3) ".reg .b64 t;\nmov.b64 t, {%1,%2};\n@p st.relaxed.gpu.global.b64 [%0], t;\n}" ::"l"(p), "r"(a), "r"(b), "r"((uint32_t)on) : "memory");
}
__device__ __forceinline__ void st_pkt82_if(bool on, const void* p, uint32_t a, uint32_t b) {
    asm volatile(PRED(3) ".reg .b64 t;\nmov.b64 t, {%1,%2};\n@p st.relaxed.gpu.global.b64 [%0], t;\n@p st.relaxed.gpu.global.b64 [%0+4096], t;\n}"
                 ::"l"(p), "r"(a), "r"(b), "r"((uint32_t)on) : "memory");
}
__device__ __forceinline__ void st_pkt2_if(bool on, const void* p, uint32_t a, uint32_t b, uint32_t c, uint32_t d) {
    jitter();
    asm volatile(PRED(5) ".reg .b128 t;\nmov.b128 t, {%1,%2,%3,%4};\n@p st.relaxed.gpu.global.b128 [%0], t;\n@p st.relaxed.gpu.global.b128 [%0+4096], t;\n}"
                 ::"l"(p), "r"(a), "r"(b), "r"(c), "r"(d), "r"((uint32_t)on) : "memory");
}
__device__ __forceinline__ void mbar_arrive_if(bool on, uint32_t a) {
    jitter();
    asm volatile(PRED(1) "@p mbarrier.arrive.shared::cta.b64 _, [%0];\n}" ::"r"(a), "r"((uint32_t)on) : "memory");
}
__device__ __forceinline__ void sts16_if(bool on, uint32_t a, uint32_t v) {
    asm volatile(PRED(2) "@p st.shared.u16 [%0], %1;\n}" ::"r"(a), "h"((unsigned short)v), "r"((uint32_t)on) : "memory");
}
__device__ __forceinline__ void sts32_if(bool on, uint32_t a, uint32_t v) {
    asm volatile(PRED(2) "@p st.shared.u32 [%0], %1;\n}" ::"r"(a), "r"(v), "r"((uint32_t)on) : "memory");
}
__device__ __forceinline__ void sts128_if(bool on, uint32_t a, uint32_t x, uint32_t y, uint32_t z, uint32_t w) {
    jitter();
    asm volatile(PRED(5) "@p st.shared.v4.u32 [%0], {%1,%2,%3,%4};\n}" ::"r"(a), "r"(x), "r"(y), "r"(z), "r"(w), "r"((uint32_t)on) : "memory");
}
__device__ __forceinline__ float fast_rcp(float x) { float r; asm("rcp.approx.ftz.f32 %0, %1;" : "=f"(r) : "f"(x)); return r; }
__device__ __forceinline__ float fast_sqrt(float x) { float r; asm("sqrt.approx.ftz.f32 %0, %1;" : "=f"(r) : "f"(x)); return r; }
__device__ __forceinline__ float fast_ex2(float x) { float r; asm("ex2.approx.ftz.f32 %0, %1;" : "=f"(r) : "f"(x)); return r; }
__device__ __forceinline__ uint32_t pack2(float lo, float hi) {
    uint32_t r;
    asm("cvt.rn.bf16x2.f32 %0, %1, %2;" : "=r"(r) : "f"(hi), "f"(lo));
    return r;
}
__device__ __forceinline__ float bfr(float x) { return __uint_as_float(pack2(0.f, x)); }
__device__ __forceinline__ uint32_t badd2(uint32_t a, uint32_t b) { uint32_t r; asm("add.rn.bf16x2 %0, %1, %2;" : "=r"(r) : "r"(a), "r"(b)); return r; }
__device__ __forceinline__ uint32_t bsub2(uint32_t a, uint32_t b) { uint32_t r; asm("sub.rn.bf16x2 %0, %1, %2;" : "=r"(r) : "r"(a), "r"(b)); return r; }
__device__ __forceinline__ uint32_t bmul2(uint32_t a, uint32_t b) { uint32_t r; asm("mul.rn.bf16x2 %0, %1, %2;" : "=r"(r) : "r"(a), "r"(b)); return r; }
__device__ __forceinline__ float bf_lo(uint32_t w) { return __uint_as_float(w << 16); }
__device__ __forceinline__ float bf_hi(uint32_t w) { return __uint_as_float(w & 0xffff0000u); }
__device__ __forceinline__ float F(uint32_t t) { return __uint_as_float(t); }
__device__ __forceinline__ uint32_t lds16(uint32_t a) { unsigned short h; asm volatile("ld.shared.u16 %0, [%1];" : "=h"(h) : "r"(a) : "memory"); return h; }
__device__ __forceinline__ uint32_t lds32(uint32_t a) { uint32_t v; asm volatile("ld.shared.u32 %0, [%1];" : "=r"(v) : "r"(a) : "memory"); return v; }
__device__ __forceinline__ uint2 lds64(uint32_t a) {
    uint2 v; asm volatile("ld.shared.v2.u32 {%0,%1}, [%2];" : "=r"(v.x), "=r"(v.y) : "r"(a) : "memory"); return v;
}
__device__ __forceinline__ uint4 lds128(uint32_t a) {
    uint4 v; asm volatile("ld.shared.v4.u32 {%0,%1,%2,%3}, [%4];" : "=r"(v.x), "=r"(v.y), "=r"(v.z), "=r"(v.w) : "r"(a) : "memory"); return v;
}
__device__ __forceinline__ float sum8(const uint4& u, const uint4& v) {
    return ((F(u.x) + F(u.y)) + (F(u.z) + F(u.w))) + ((F(v.x) + F(v.y)) + (F(v.z) + F(v.w)));
}
__device__ __forceinline__ void sts16(uint32_t a, uint32_t v) { asm volatile("st.shared.u16 [%0], %1;" ::"r"(a), "h"((unsigned short)v) : "memory"); }
__device__ __forceinline__ void sts32(uint32_t a, uint32_t v) { asm volatile("st.shared.u32 [%0], %1;" ::"r"(a), "r"(v) : "memory"); }
__device__ __forceinline__ void stsf(uint32_t a, float v) { asm volatile("st.shared.f32 [%0], %1;" ::"r"(a), "f"(v) : "memory"); }
__device__ __forceinline__ void stsf2(uint32_t a, float x, float y) { asm volatile("st.shared.v2.f32 [%0], {%1,%2};" ::"r"(a), "f"(x), "f"(y) : "memory"); }
__device__ __forceinline__ void stsf4(uint32_t a, float x, float y, float z, float w) {
    asm volatile("st.shared.v4.f32 [%0], {%1,%2,%3,%4};" ::"r"(a), "f"(x), "f"(y), "f"(z), "f"(w) : "memory");
}
template <int ID, int N> __device__ __forceinline__ void bar_sync() { jitter(); asm volatile("bar.sync %0, %1;" ::"n"(ID), "n"(N) : "memory"); jitter(); }
template <int ID, int N> __device__ __forceinline__ void bar_arrive() { jitter(); asm volatile("bar.arrive %0, %1;" ::"n"(ID), "n"(N) : "memory"); jitter(); }
__device__ __forceinline__ void fence_async() { asm volatile("fence.proxy.async.shared::cta;" ::: "memory"); }
__device__ __forceinline__ float shx(float v, int m) { return __shfl_xor_sync(0xffffffffu, v, m); }
__device__ __forceinline__ float shi(float v, int l) { return __shfl_sync(0xffffffffu, v, l); }
__device__ __forceinline__ uint32_t shi(uint32_t v, int l) { return __shfl_sync(0xffffffffu, v, l); }
__device__ __forceinline__ uint32_t opaque(uint32_t x) { asm volatile("mov.u32 %0, %0;" : "+r"(x)); return x; }
__device__ __forceinline__ const char* opaque(const char* x) { asm volatile("mov.u64 %0, %0;" : "+l"(x)); return x; }
constexpr float LOG2E = 1.4426950408889634f, SCALE = 0.07216878364870322f;

#define TRACE(idx) do {} while (0)
#define TRACES(slot) do {} while (0)

__device__ __forceinline__ uint32_t probe_near(const Params& p, int w, int lane) {
    const int cta = blockIdx.x;
    const char* pr = p.scr + SCR_O + head_off(cta >> 2) + 2048 + w * 256 + (cta & 3) * 64;
    st_pkt2_if(lane < 4, pr + lane * 16, 0, 0, 0, 0);
    uint32_t best0 = ~0u, best1 = ~0u;
#pragma unroll 1
    for (int i = w & 1; i < 6 + (w & 1); i++) {
        uint32_t c = clk32(), v = 0;
        if (lane == 0) asm volatile("atom.relaxed.gpu.global.add.u32 %0, [%1], 1;" : "=r"(v) : "l"(pr + (i & 1) * HALF) : "memory");
        c += __shfl_sync(0xffffffffu, v, 0) >> 16;
        c = clk32() - c;
        if (i & 1) best1 = min(best1, c); else best0 = min(best0, c);
    }
    return min(best0, 0xffffu) | min(best1, 0xffffu) << 16;
}
__device__ __forceinline__ uint32_t near_half() {
    const uint4 a = lds128(SM_NEAR), b = lds128(SM_NEAR + 16);
    const uint32_t m = __vminu2(__vminu2(__vminu2(a.x, a.y), __vminu2(a.z, a.w)), __vminu2(__vminu2(b.x, b.y), __vminu2(b.z, b.w)));
    return head_near(blockIdx.x >> 2, ((m & 0xffffu) > m >> 16) != (CFG(FLIP) != 0) ? HALF : 0);
}

__device__ __forceinline__ int kv_group(int k, int t) {
    const int cta = blockIdx.x;
    return ((k * NHEAD + (cta >> 2)) * SK + (SK - WIN) + (cta & 3) * 256 + t * 32) / 8;
}
__device__ __forceinline__ uint32_t phase_ns() { return (((blockIdx.x >> 2) * 13) & 31) * CFG(STAG) / 32; }

__device__ __forceinline__ void ln_fast(float s, float q, float& mean, float& rstd) {
    mean = s * (1.f / DM);
    asm("rsqrt.approx.ftz.f32 %0, %1;" : "=f"(rstd) : "f"(fmaxf(fmaf(-mean, mean, fmaf(q, 1.f / DM, 1e-5f)), 1e-5f)));
}
__device__ __forceinline__ void q_role(const Params& p, int lane) {
    const int cta = blockIdx.x;
    mbar_wait(bar_at(B_EP), 0);
    const uint32_t epoch = lds32(SM_EPOCH), near = head_near(cta >> 2, near_half());
    auto sums = [&](float& S0, float& S1) {
        bar_sync<3, 288>();
        const uint32_t ra = SM_PQ + lane * 16;
        S0 = sum8(lds128(ra), lds128(ra + 1024)); S1 = sum8(lds128(ra + 512), lds128(ra + 1536));
    };
    float cs0, cs1;
    {
        uint32_t q0 = 0, q1 = 0, q2 = 0, q3 = 0;
#pragma unroll 1
        for (int r = 0; r < NB; r++) {
            sums(cs0, cs1);
            bar_arrive<7, 288>();
            q0 = q1; q1 = q2; q2 = q3; q3 = pack2(cs0, cs1);
        }
        const uint32_t t0 = shi(q3, 3 * lane - 72), t1 = shi(q3, 3 * lane - 71), t2 = shi(q3, 3 * lane - 70), tag = epoch << 8 | 0x40;
        const char* box = p.scr + SCR_O + head_off(cta >> 2) + 2048 + (lane >> 2) * 256 + (lane & 3) * 16;
        st_pkt2_if(true, box + (cta & 3) * 64, lane < 24 ? q0 : t0, lane < 24 ? q1 : t1, lane < 24 ? q2 : t2, tag);
        const uint32_t qd = SM_Q + (lane < 24 ? lane * 4 : 3 * 384 + (lane - 24) * 12), step = lane < 24 ? 384 : 4;
#pragma unroll 1
        for (int j = 0; j < 4; j++) {
            uint4 v;
            SPIN_DECL;
            do {
                __nanosleep(200);
                v = ld_pkt(box + near + j * 64);
                SPIN_CHECK(j);
            } while (__any_sync(0xffffffffu, v.w != tag));
            sts32(qd + j * 96, v.x); sts32(qd + j * 96 + step, v.y); sts32(qd + j * 96 + 2 * step, v.z);
        }
        mbar_arrive(bar_at(B_QR));
    }
    sums(cs0, cs1);
    bar_arrive<7, 288>();
    const char* const src = p.scr + SCR_Q + head_off(cta >> 2) + lane * 8 + near;
    const char* const dst = src + (cta & 3) * 192;
    const uint32_t qd = SM_Q + NB * 384 + lane * 4;
    st_pkt82_if(lane < 24, dst - near, 0, 0);
#pragma unroll 1
    for (int k = 0; k < NB; k++) {
        float S0, S1, mean, rstd;
        sums(S0, S1);
        ln_fast(shi(S1, 24), shi(S0, 24), mean, rstd);
        const uint32_t qq = pack2(fmaf(-mean, cs0, S0) * rstd, fmaf(-mean, cs1, S1) * rstd), tag = epoch * NB + k;
        st_pkt8_if(lane < 24, dst + ((int)HALF - 2 * (int)near), qq, tag);
        st_pkt8_if(lane < 24, dst, qq, tag);
        TRACES(k * 12 + 5);
        uint2 a, b, c;
        SPIN_DECL;
        do {
            a = ld_pkt8(src); b = ld_pkt8(src + 256); c = ld_pkt8(src + 512);
            SPIN_CHECK(k);
            sts32(qd, a.x); sts32(qd + 128, b.x); sts32(qd + 256, c.x);
        } while (__any_sync(0xffffffffu, a.y != tag || b.y != tag || c.y != tag));
        mbar_arrive(bar_at(B_QR));
    }
}

struct Maps { CUtensorMap k, v, q, o, g, u; };
__device__ __forceinline__ void load_role(const Params& p, const CUtensorMap* tmKV, int lane, uint32_t t0) {
    const int cta = blockIdx.x;
    t0 += phase_ns();
#pragma unroll 1
    for (int i = 1; i < 5; i++) {
        wait_ns(t0 + i * CFG(TICK0));
        if (elect_one()) l2_prefetch(p.wq + (size_t)(128 * i + cta) * 12288, 12288);
        TRACE(230 + i);
    }
    uint32_t plan[2];
#pragma unroll
    for (int i = 0; i < 2; i++) {
        const int j = lane + 32 * i, k = j >> 4, t = j & 15, u = t >> 1, jw = j - CFG(WIN);
        const int sb = k == 0 ? B_WC + (t >= 8) + (t >= 14) : t >= 12 ? B_RK + u - 5 : t >= 4 ? B_RR + t - 4 : t >= 2 ? B_RP : k > 1 ? B_RK + 3 : B_RR + t;
        const uint32_t sw = sb * 8 | (j < 18 ? 0 : (t >= 12 || u == 1 ? k - 1 : k) & 1) << 9;
        plan[i] = sw | (jw < 0 ? sw : (B_F1 + (jw & 15)) * 8 | ((jw >> 4) & 1) << 9) << 10 |
                  (slot_at(slots(k), t < 8 ? pass_nibble(k, u) : u) * 2 + (t & 1)) << 20 | (t < 10 && j >= 8 && j < 56) << 25;
    }
    bar_sync<6, 64>();
    wait_ns(t0 + kb_ns(60));
    if (elect_one()) bulk_load(ST_WD, p.wd + cta * 15360, 15360, bar_at(B_W));
    TRACE(235);
#pragma unroll 1
    for (int i = 0; i < 5; i++) {
        wait_ns(t0 + kb_ns(75) + i * kb_ns(6));
        if (elect_one()) { l2_prefetch(p.wg + (128 * i + cta) * 3072, 3072); l2_prefetch(p.wu + (128 * i + cta) * 3072, 3072); }
    }
#pragma unroll 1
    for (int i = 0; i < 6; i++) {
        wait_ns(t0 + kb_ns(105) + min(i, 4) * kb_ns(10));
        if (elect_one()) l2_prefetch(p.wo + (size_t)((cta >> 2) * DH + 32 * i + 8 * (cta & 3)) * 1280, 10240);
    }
    t0 += batch_ns(0);
    int jp = 0, shift = 0;
    uint32_t earliest = t0;
    auto requested = [&](uint32_t now) {
        shift = max(max(shift - CFG(GAIN), 0), (int)(now - t0) - (jp < 12 ? CFG(LMAX0) : CFG(LMAX)));
        TRACE(128 + jp);
        t0 += tick_ns(++jp);
    };
    const int grp0 = kv_group(0, 0);
    auto group = [&](int j) { return grp0 + (j >> 4) * (NHEAD * SK / 8) + (j & 7) * 4; };
#pragma unroll 1
    for (int j = 0; j < 16 * NB; j++) {
        const uint32_t pl = __shfl_sync(0xffffffffu, j & 32 ? plan[1] : plan[0], j);
        const int jmax = min(j + CFG(PMAX), 16 * NB);
        jitter();
        uint32_t now;
        SPIN_DECL;
        while (true) {
            const bool ok = mbar_test2(SM_BAR + (pl & 511), (pl >> 9) & 1, SM_BAR + ((pl >> 10) & 511), (pl >> 19) & 1);
            now = now_ns();
            const int late = now - t0 - shift;
            if (ok && (jp > j ? (int)(now - earliest) : late) >= 0) break;
            if (late >= (jp > j ? 0 : CFG(PGRACE)) && jp < jmax) {
                if (elect_one())
                    asm volatile("cp.async.bulk.prefetch.tensor.4d.L2.global [%0, {%1, %1, %1, %2}];" ::"l"(tmKV + ((jp >> 3) & 1)), "r"(0), "r"(group(jp)) : "memory");
                requested(now);
            }
            SPIN_CHECK(j);
        }
        if (elect_one()) {
            mbar_expect_tx(bar_at(B_F1 + (j & 15)), TILE);
            tma_tile(SB + ((pl >> 20) & 31) * TILE, tmKV + ((j >> 3) & 1), group(j), bar_at(B_F1 + (j & 15)), pl >> 25 ? POL_NORMAL : POL_FIRST);
        }
        TRACE(256 + j);
        if ((j & 15) == 15) TRACES(88 + (j >> 4));
        earliest = now + CFG(VSTEP);
        if (jp == j) requested(now);
    }
}

__device__ __forceinline__ void reload_role(const Params& p, const Maps* tm, uint32_t t0) {
    const CUtensorMap* const tmK = &tm->k;
    const CUtensorMap* const tmV = &tm->v;
    const int cta = blockIdx.x;
    t0 += CFG(TICK0) + CFG(WLAG) + phase_ns();
#pragma unroll 1
    for (int i = 0; i < 5; i++) {
        wait_ns(t0 + i * CFG(TICK0));
        if (elect_one()) tma2d(ST_WQ + i * 12288, &tm->q, 48 * cta, 128 * i, bar_at(B_W));
        TRACE(240 + i);
        if (i == 1) bar_sync<5, 480>();
    }
#pragma unroll 1
    for (int i = 0, o = 0; i < 10;) {
        const uint32_t now = now_ns() - t0;
        if (o < 6 && (int)now >= kb_ns(105) + o * kb_ns(10)) {
            if (elect_one()) tma2d(ST_WO + o * 10240, &tm->o, 160 * (cta & 3), (cta >> 2) * DH + 32 * o, bar_at(B_W + 1));
            o++;
        } else if ((int)now >= kb_ns(77) + i * CFG(GSTEP) && (i < 9 || o == 6)) {
            if (elect_one()) tma2d(ST_WG + (i & 1) * 20480 + (i >> 1) * 4096, i & 1 ? &tm->u : &tm->g, (12 * cta) & ~7, 128 * (i >> 1), bar_at(B_W + 2));
            i++;
        }
    }
#pragma unroll 1
    for (int k = 0; k < NB - 1; k++) {
        mbar_wait(bar_at(B_RK), k & 1);
        if (elect_one()) {
            const uint32_t dst = SB + slot_at(slots(k), 0) * PAIR;
            mbar_expect_tx(bar_at(B_FL), PAIR);
            tma_tile(dst, tmV, kv_group(k, 0), bar_at(B_FL), POL_FIRST);
            tma_tile(dst + TILE, tmV, kv_group(k, 1), bar_at(B_FL), POL_FIRST);
        }
        mbar_wait(bar_at(B_RV), k & 1);
        uint32_t due = now_ns();
        if (elect_one()) mbar_expect_tx(bar_at(B_F3), 4 * PAIR);
#pragma unroll 1
        for (int t = 0; t < 8; t++) {
            wait_ns(due);
            due += k == NB - 2 ? CFG(RSTEP3) : CFG(RSTEP);
            if (elect_one())
                tma_tile(SB + slot_at(slots(k + 1), t >> 1) * PAIR + (t & 1) * TILE, tmK, kv_group(k + 1, t), bar_at(B_F3), POL_FIRST);
        }
        TRACE(121 + k);
    }
}

__device__ __forceinline__ void zero_role(const Params& p, int lane, uint32_t t0) {
    const int cta = blockIdx.x;
    unsigned ticket = 0;
    if (lane == 0) ticket = atomicAdd(&g_epoch, 1u);
    const uint32_t epoch = __shfl_sync(0xffffffffu, ticket, 0) / NCTA + 1;
    if (lane == 0) { sts32(SM_EPOCH, epoch); mbar_arrive(bar_at(B_EP)); }
    mbar_wait(bar_at(B_EP), 0);
#pragma unroll 1
    for (int k = 0; k < NB + 2; k++) {
        lane = opaque(lane);
        const int cl = 2 * (cta & 15) + (lane & 1);
        const int col = 80 * (cta >> 4) + (cl & 2 ? 48 : 0) + (cl >> 2) + (cl & 1 ? 8 : 0);
        const char* own = p.scr + (cl >> 2) * 256 + (cl & 3) * 16;
        uint32_t v0 = 0, v1 = 0, v2 = 0;
        if (lane < 4 && k < NB) {
            const unsigned short* xp = p.x + k * DM + col;
            v0 = __ldg(xp) << 16; v1 = __ldg(xp + 16) << 16; v2 = cl & 2 ? 0 : __ldg(xp + 32) << 16;
        }
        uint4 r;
        if (k == 1) mbar_wait(bar_at(B_RK), 0);
        if (k > 1) {
            mbar_wait(bar_at(B_FIN), k & 1);
            r = lds128(SM_FIN + (lane & 1) * 16);
        }
        if (k < NB) {
            const int lg = lane >> 3, ty = (lane & 7) >> 1;
            const char* dst = own + acc_off((k - (lg >> 1)) & 3, lg != 0, cta >> 4) + ty * HALF;
            wait_ns(t0 + batch_ns(k) + CFG(ZTILE) * CFG(TICK0));
            if (lg == 0 || (lg == 1 && (ty < 2 || k == NB - 1)) || (lg == 2 && k > 0 && ty > 1)) {
                st_pkt(dst, v0, v1, v2, ~0u);
                asm volatile("atom.relaxed.gpu.global.exch.b32 %0, [%1+12], %2;" : "=r"(v0) : "l"(dst), "r"(lane < 4 ? 0x3f800000u : 0u) : "memory");
                v0 = ~v0;
            }
            if (__any_sync(0xffffffffu, v0 != 0)) __trap();
            const char* cnt = p.scr + SCR_COUNT;
            if (lane < 2) asm volatile("red.relaxed.gpu.global.add.u32 [%0], 1;" ::"l"(cnt + lane * HALF) : "memory");
            const uint32_t target = ((epoch - 1) * NB + k + 1) * NCTA;
            cnt += near_half();
            SPIN_DECL;
            uint32_t v;
            do {
                __nanosleep(100);
                asm volatile("ld.relaxed.gpu.global.u32 %0, [%1];" : "=r"(v) : "l"(cnt) : "memory");
                SPIN_CHECK(v);
            } while (__any_sync(0xffffffffu, (int)(v - target) < 0));
        }
        __syncwarp();
        if (lane == 0) mbar_arrive(bar_at(B_Z));
        if (k > 1) {
            const int b = k - 2;
            const char* src = own + acc_off(b, 1, cta >> 4) + (2 + ((lane >> 1) & 1)) * HALF;
            unsigned short* o = p.out + b * DM + col + (lane >> 2) * 16;
            const bool on = !(lane & 2) && lane < (cl & 2 ? 8 : 12);
            wait_clk(clk32() + CFG(DLY_F));
            float cnt;
            SPIN_DECL;
            do {
                const uint4 v = ld_pkt(src);
                SPIN_CHECK(k);
                cnt = F(v.w) + shx(F(v.w), 2);
                const float y0 = F(v.x) + shx(F(v.x), 2), y1 = F(v.y) + shx(F(v.y), 2), y2 = F(v.z) + shx(F(v.z), 2);
                const uint32_t x01 = badd2(r.x, badd2(r.y, bmul2(pack2(y0, y1), r.w)));
                const uint32_t x2 = badd2(r.z, badd2(r.z >> 16, bmul2(pack2(y2, 0.f), r.w)));
                if (cnt == NCTA && on) *o = lane < 4 ? x01 : lane < 8 ? x01 >> 16 : x2;
            } while (__any_sync(0xffffffffu, cnt != NCTA));
            TRACES((2 * b + 1) * 6 + 4);
        }
    }
}

__host__ __device__ constexpr uint32_t desc_lo(uint32_t addr) { return ((addr & 0x3FFFFu) >> 4) | (1u << 16); }
constexpr uint32_t DESC_HI_TILE = (3072u >> 4) | (1u << 30);
constexpr uint32_t DESC_HI_VEC = 1u;
template <int TA, int AOFF, int BOFF>
__device__ __forceinline__ void wgmma_n8(float (&d)[4], uint32_t alo, uint32_t blo, int accumulate) {
    asm volatile("{\n.reg .pred p;\n.reg .b32 a, b;\n.reg .b64 da, db;\nsetp.ne.b32 p, %6, 0;\n"
                 "add.u32 a, %4, %8;\nadd.u32 b, %5, %9;\nmov.b64 da, {a, %10};\nmov.b64 db, {b, %11};\n"
                 "wgmma.mma_async.sync.aligned.m64n8k16.f32.bf16.bf16 {%0,%1,%2,%3}, da, db, p, 1, 1, %7, 0;\n}"
                 : "+f"(d[0]), "+f"(d[1]), "+f"(d[2]), "+f"(d[3])
                 : "r"(alo), "r"(blo), "r"(accumulate), "n"(TA), "n"(AOFF >> 4), "n"(BOFF >> 4), "n"(DESC_HI_TILE), "n"(DESC_HI_VEC));
}
template <int KS, int END>
__device__ __forceinline__ void qk_steps(float (&d)[4], uint32_t alo, uint32_t blo) {
    if constexpr (KS < END) {
        wgmma_n8<0, (KS >> 2) * 1024 + (KS & 3) * 32, KS * 32>(d, alo, blo, KS > 0);
        qk_steps<KS + 1, END>(d, alo, blo);
    }
}
__device__ __forceinline__ void pv_steps(float (&e)[3][4], uint32_t alo, uint32_t blo, int acc) {
    wgmma_n8<1, 0, 0>(e[0], alo, blo, acc); wgmma_n8<1, 1024, 0>(e[1], alo, blo, acc); wgmma_n8<1, 2048, 0>(e[2], alo, blo, acc);
    wgmma_n8<1, 6144, 32>(e[0], alo, blo, 1); wgmma_n8<1, 7168, 32>(e[1], alo, blo, 1); wgmma_n8<1, 8192, 32>(e[2], alo, blo, 1);
}
__device__ __forceinline__ void wg_fence() { asm volatile("wgmma.fence.sync.aligned;" ::: "memory"); }
__device__ __forceinline__ void wg_commit() { asm volatile("wgmma.commit_group.sync.aligned;" ::: "memory"); }
template <int N> __device__ __forceinline__ void wg_wait() { asm volatile("wgmma.wait_group.sync.aligned %0;" ::"n"(N) : "memory"); }
__device__ __forceinline__ void acc_ready(float (&d)[4]) { asm volatile("" : "+f"(d[0]), "+f"(d[1]), "+f"(d[2]), "+f"(d[3]) :: "memory"); }
__device__ __forceinline__ uint32_t score_pair(float (&d)[4]) {
    acc_ready(d);
    const uint32_t r = pack2(d[0], d[2]);
    return pack2(bf_lo(r) * SCALE, bf_hi(r) * SCALE);
}

__device__ __forceinline__ void attention_role(const Params& p, int w, int lane) {
    const int cta = blockIdx.x, t4 = lane & 3, g = lane >> 2;
    mbar_wait(bar_at(B_EP), 0);
    const uint32_t tag0 = lds32(SM_EPOCH) * NB;
    const char* const odst = p.scr + SCR_O + head_off(cta >> 2) + (2 * w + (g >> 2)) * 256 + (cta & 3) * 64 + (g & 3) * 16;
    const uint32_t pdst = SM_P + ((t4 + 3) & 3) * PSTR + (16 * w + g) * 2;
    auto softmax = [&](uint32_t& sc, int ps) -> uint32_t {
        const float s0 = bf_lo(sc), s1 = bf_hi(sc);
        int key = __float_as_int(fmaxf(s0, s1));
        key ^= (key >> 31) & 0x7fffffff;
        key = __reduce_max_sync(0xffffffffu, key);
        sts32(SM_MAX + w * 4, key);
        bar_sync<4, 128>();
        const uint4 mx = lds128(SM_MAX);
        key = max(max((int)mx.x, (int)mx.y), max((int)mx.z, (int)mx.w));
        key ^= (key >> 31) & 0x7fffffff;
        const float mb = __int_as_float(key) * LOG2E;
        const uint32_t pp = pack2(fast_ex2(fmaf(s0, LOG2E, -mb)), fast_ex2(fmaf(s1, LOG2E, -mb)));
        sts16(pdst + ps * 4 * PSTR, pp); sts16(pdst + ps * 4 * PSTR + 16, pp >> 16);
        fence_async();
        bar_sync<4, 128>();
        sc = pp;
        return key;
    };
    auto put_sum = [&](uint32_t pp, int ps) {
        uint32_t fs;
        asm volatile("redux.sync.add.u32 %0, %1, 0xffffffff;" : "=r"(fs) : "r"(__float2uint_rn((bf_lo(pp) + bf_hi(pp)) * 8388608.f)) : "memory");
        sts32(SM_SUM + ps * 16 + w * 4, fs);
    };
    auto aux_word = [&](uint32_t mx, const uint4& u, int k) {
        const float l = __uint2float_rn((u.x + u.y) + (u.z + u.w)) * (1.f / 8388608.f);
        return (g < 4 ? mx : (__float_as_uint(l) + 0x80u) & 0xffffff00u) | ((tag0 + k) & 0x7fu) | 0x80u;
    };
    auto send = [&](float (&e)[3][4], uint32_t aux, int ps) {
        acc_ready(e[0]); acc_ready(e[1]); acc_ready(e[2]);
        const uint32_t o0 = pack2(e[0][0], e[0][2]), o1 = pack2(e[1][0], e[1][2]), o2 = pack2(e[2][0], e[2][2]);
        st_pkt2_if(t4 == 0, odst + ps * 2048, o0, o1, o2, aux);
        mbar_arrive_if(lane == 0, bar_at(ps ? B_RV : B_PS));
    };
    mbar_wait(bar_at(B_QR), 0);
    TRACES(73);
#pragma unroll 1
    for (int it = 0; it <= NB; it++) {
        uint32_t m1 = 0;
        if (it < NB) {
            const uint32_t tab = slots(it);
            const uint32_t ka = SB + (2 * w + ((lane >> 3) & 1)) * 3072 + (lane & 7) * 128 + (((lane >> 4) ^ (lane & 7)) << 4);
            const uint32_t qa = SM_Q + it * 384 + (lane >> 3) * 16;
            uint32_t sc = 0;
#pragma unroll 1
            for (int u = 0; u < 4; u++) {
                const uint32_t base = ka + slot_at(tab, pass_nibble(it, u)) * PAIR;
                mbar_wait(bar_at(B_F1 + 2 * u + (w >> 1)), it & 1);
                float d0[4] = {}, d1[4] = {};
#pragma unroll
                for (int c = 0; c < 6; c++) {
                    uint32_t a0[4], a1[4], b[4];
                    ldsm4(b, qa + c * 64);
                    ldsm4(a0, (base ^ ((c & 1) * 64)) + (c >> 1) * 1024);
                    ldsm4(a1, (base ^ ((c & 1) * 64 + 32)) + (c >> 1) * 1024);
                    mma16816(d0, a0[0], a0[1], a0[2], a0[3], b[0], b[1]);
                    mma16816(d1, a1[0], a1[1], a1[2], a1[3], b[2], b[3]);
                }
                const uint32_t r = pack2(d0[0] + d1[0], d0[2] + d1[2]);
                mbar_arrive_if(lane == 0, bar_at(B_RR + 2 * u + (w >> 1)));
                if (t4 == ((u + 1) & 3)) sc = pack2(bf_lo(r) * SCALE, bf_hi(r) * SCALE);
            }
            m1 = softmax(sc, 0);
            put_sum(sc, 0);
        }
        if (it > 0) {
            const int k = it - 1;
            const uint32_t tab = slots(k);
            const uint32_t v0 = slot_at(tab, k < NB - 1 ? 0 : 4);
            TRACES(48 + k * 6);
            if (k > 0) mbar_wait(bar_at(B_F3), it & 1);
            mbar_wait(bar_at(B_QR), it & 1);
            fence_async();
            TRACES(49 + k * 6);
            float d[4][4] = {};
            const bool busy = k < NB - 1;
#pragma unroll
            for (int u = 0; u < 4; u++) {
                const uint32_t alo = desc_lo(SB) + slot_at(tab, u) * (PAIR >> 4), blo = desc_lo(SM_Q + 4 * 384);
                wg_fence();
                qk_steps<0, 6>(d[u], alo, blo);
                wg_commit();
                if (busy) {
                    wg_wait<1>();
                    if (u > 0) mbar_arrive_if(lane == 0, bar_at(B_RK + u - 1));
                }
                wg_fence();
                qk_steps<6, 12>(d[u], alo, blo);
                wg_commit();
                if (u < 3 && busy) wg_wait<1>();
            }
            wg_wait<2>();
            uint32_t sc = shi(score_pair(d[0]), lane & 28), s = shi(score_pair(d[1]), lane & 28);
            if (t4 == 2) sc = s;
            s = shi(score_pair(d[2]), lane & 28);
            if (t4 == 3) sc = s;
            wg_wait<0>();
            s = score_pair(d[3]);
            if (t4 == 0) sc = s;
            mbar_arrive_if(lane == 0, bar_at(B_RK + 3));
            TRACES(50 + k * 6);
            const uint32_t m2 = softmax(sc, 1);
            TRACES(51 + k * 6);
            float e[3][4] = {};
#pragma unroll
            for (int t = 0; t < 8; t++) {
                const int pr = ((t >> 1) + 1) & 3;
                if (t == 6 && k < NB - 1) mbar_wait(bar_at(B_FL), k & 1);
                wg_fence();
                pv_steps(e, desc_lo(SB + (t & 1) * TILE) + (pr ? slot_at(tab, 4 + pr) : v0) * (PAIR >> 4), desc_lo(SM_P + (4 + pr) * PSTR + (t & 1) * 64), t > 0);
                wg_commit();
                if (t < 7 && busy) wg_wait<1>();
                if (t == 1) put_sum(sc, 1);
            }
            bar_sync<4, 128>();
            const uint32_t aux = opaque(aux_word(m2, lds128(SM_SUM + 16), k));
            wg_wait<0>();
            send(e, aux, 1);
            TRACES(52 + k * 6);
        }
        if (it < NB) {
            const uint32_t tab = slots(it);
            if (it == 0) st_pkt2_if(t4 == 0, odst, 0, 0, 0, 0);
            bar_sync<4, 128>();
            const uint32_t aux = opaque(aux_word(m1, lds128(SM_SUM), it));
            float e[3][4] = {};
#pragma unroll 1
            for (int u = 0; u < 4; u++) {
                const uint32_t alo = desc_lo(SB) + slot_at(tab, 4 + u) * (PAIR >> 4), blo = desc_lo(SM_P) + u * (PSTR >> 4);
                mbar_wait(bar_at(B_F1 + 8 + 2 * u), it & 1);
                wg_fence();
                pv_steps(e, alo, blo, u > 0);
                wg_commit();
                wg_wait<1>();
                if (u == 1) mbar_arrive_if(lane == 0, bar_at(B_RP));
                mbar_wait(bar_at(B_F1 + 9 + 2 * u), it & 1);
                wg_fence();
                pv_steps(e, alo + (TILE >> 4), blo + 4, 1);
                wg_commit();
                wg_wait<1>();
            }
            wg_wait<0>();
            send(e, aux, 0);
            TRACES(53 + it * 6);
        }
    }
}

__device__ __forceinline__ void ln_finish(float s, float q, float& mean_b, float& rden) {
    const float mean = s * (1.f / DM);
    const float var = fmaxf(fmaf(q, 1.f / DM, -mean * mean), 0.f);
    mean_b = bfr(mean);
    rden = fast_rcp(bfr(fast_sqrt(bfr(bfr(var) + 1e-5f))));
}
__device__ __forceinline__ uint32_t ln_apply(uint32_t w, float mean_b, float rden) {
    const uint32_t d = bsub2(w, __byte_perm(__float_as_uint(mean_b), 0, 0x3232));
    return pack2(bf_lo(d) * rden, bf_hi(d) * rden);
}
__device__ __forceinline__ void put_x(uint32_t x01, uint32_t x2, uint32_t wa, bool e2) {
    jitter();
    sts16(wa, x01); sts16(wa + 8, x01 >> 16);
    sts16_if(!e2, wa + 16, x2);
}
__device__ __forceinline__ void get_x(uint32_t (&b)[10], uint32_t ra) {
    __syncwarp();
    const uint4 u = lds128(ra), v = lds128(ra + 16);
    const uint2 z = lds64(ra + 32);
    b[0] = u.x; b[1] = u.y; b[2] = u.z; b[3] = u.w; b[4] = v.x; b[5] = v.y; b[6] = v.z; b[7] = v.w; b[8] = z.x; b[9] = z.y;
}
__device__ __forceinline__ float fold(float a, float b, bool sel, int m) { return (sel ? b : a) + shx(sel ? a : b, m); }

__device__ __forceinline__ void chain_role(const Params& p, int w, int lane, uint32_t t0) {
    const int cta = blockIdx.x, h = cta >> 2, s = cta & 3;
    const int g = lane >> 2, t4 = lane & 3;
    const bool e1 = t4 & 1, e2 = t4 & 2;
    uint32_t wq[5][3][4], wo[3][5][4], wg[5][4], wh[5][2], wd[4][4];
    const int col0 = 80 * w + (e2 ? 48 : 0) + g + (e1 ? 8 : 0);
    const uint32_t xw = opaque(SM_X + w * 384 + 48 * (g >> 1) + (e2 ? 24 : 0) + (e1 ? 4 : 0) + 2 * (g & 1));
    const uint32_t xr = opaque(g == 1 ? SM_ONES : SM_X + w * 384 + (g == 3 ? 192 : 0) + 48 * t4);
    TRACES(75);
    sts32_if(lane < 12, SM_ONES + lane * 4, 0x3f803f80u);
    uint32_t zero = lane >> 5;
    const int mi = lane >> 3, mr = lane & 7;
    mbar_wait(bar_at(B_W), 0);
    TRACES(74);
    sts16(xw + 192, lds16(ST_X + 5120 + col0 * 2)); sts16(xw + 200, lds16(ST_X + 5120 + col0 * 2 + 32));
    sts16_if(!e2, xw + 208, lds16(ST_X + 5120 + col0 * 2 + 64));
#pragma unroll
    for (int i = 0; i < 5; i++)
#pragma unroll
        for (int mt = 0; mt < 3; mt++) ldsm4t(wq[i][mt], ST_WQ + (80 * w + 16 * i + mr + 8 * (mi >> 1)) * 96 + 32 * mt + 16 * (mi & 1), zero);
    const bool odd = cta & 1;
    const uint32_t lo = ST_WD + (mr + (odd ? 4 : 0)) * 1280 + 160 * w + 16 * (mi & 1);
    const uint32_t hi = ST_WD + ((mr & 3) + (odd ? 0 : 8)) * 1280 + 160 * w + 16 * (mi & 1);
    ldsm4t(wd[0], lo + 96 * (mi >> 1), zero);
    ldsm4t(wd[1], lo + 96 * (mi >> 1) + 32, zero);
    ldsm4t(wd[2], (mi < 2 ? lo : hi) + 64, zero);
    ldsm4t(wd[3], hi + 32 * (mi >> 1) + 96 * (mr >> 2), zero);
    fence_async();
    __syncwarp();
    mbar_arrive_if(lane == 0, bar_at(B_WC));
    mbar_wait(bar_at(B_EP), 0);
    const uint32_t near = __shfl_sync(0xffffffffu, near_half(), 0);
    uint32_t x01 = 0, x2 = 0, nx01 = 0, nx2 = 0;
#pragma unroll 1
    for (int n = -5; n < NROUND; n++) {
        const bool last = (ORD_LAST >> (n & 15)) & 1, head = !((ORD_NO_HEAD >> (n & 15)) & 1);
        const int k = (ORD_BATCH >> (2 * (n & 15))) & 3;
        if (n > -5 && n <= 0) bar_sync<7, 288>();
        else if (!last) bar_sync<2, 256>();
        TRACES(n <= 0 ? 83 + n : 95);
        const char* const slice = p.scr + acc_off(k, last, w);
        const char* const cell = opaque(slice + g * 256 + t4 * 16);
        if (n < -1) {
            const uint32_t xa = ST_X + (n + 5) * 1280, ln = opaque(lane);
            const int col0 = 80 * w + (ln & 2 ? 48 : 0) + (ln >> 2) + (ln & 1 ? 8 : 0);
            float sm = 0.f, sq = 0.f;
#pragma unroll
            for (int i = 0; i < 5; i++) {
                const uint2 c = lds64(xa + i * 256 + ln * 8);
                sm += (bf_lo(c.x) + bf_hi(c.x)) + (bf_lo(c.y) + bf_hi(c.y));
                sq = fmaf(bf_lo(c.x), bf_lo(c.x), fmaf(bf_hi(c.x), bf_hi(c.x), fmaf(bf_lo(c.y), bf_lo(c.y), fmaf(bf_hi(c.y), bf_hi(c.y), sq))));
            }
            x01 = lds16(xa + col0 * 2) | lds16(xa + col0 * 2 + 32) << 16;
            x2 = lds16(xa + col0 * 2 + 64);
#pragma unroll
            for (int o = 16; o; o >>= 1) { sm += shx(sm, o); sq += shx(sq, o); }
            float mean_b, rden;
            ln_finish(sm, sq, mean_b, rden);
            x01 = ln_apply(x01, mean_b, rden);
            x2 = ln_apply(x2, mean_b, rden);
            put_x(x01, x2, xw, e2);
        } else {
        if (n >= 0) {
          if (head) {
            if (!last || n == NROUND - 1) mbar_wait(bar_at(B_Z), (k + last) & 1);
            const char* src = p.scr + SCR_O + head_off(h) + head_near(h, near) + last * 2048 + (w & 6) * 256 + (lane & 15) * 16;
            const uint32_t tag = (lds32(SM_EPOCH) * NB + k) | 0x80u;
            mbar_wait(bar_at(last ? B_RV : B_PS), k & 1);
            if (!last && k < NB - 1) wait_ns(t0 + batch_ns(k + 1) + CFG(START));
            uint4 v, z;
            {
                SPIN_DECL;
                do {
                    v = ld_pkt(src); z = ld_pkt(src + 256);
                    SPIN_CHECK(n);
                } while (__any_sync(0xffffffffu, (((v.w ^ tag) | (z.w ^ tag)) & 0xffu) != 0));
            }
            TRACES(tr + 0);
            float a[3][4] = {};
            const uint32_t bb[3][2] = {{v.x, v.y}, {z.x, z.y}, {v.z, z.z}};
            float sa, sb, rl;
#pragma unroll
            for (int i = 0; i < 3; i++) {
                const uint32_t l0 = g < 4 ? bb[i][0] : 0, l1 = g < 4 ? bb[i][1] : 0, h0 = g < 4 ? 0 : bb[i][0], h1 = g < 4 ? 0 : bb[i][1];
#pragma unroll
                for (int mt = 0; mt < 5; mt++)
                    mma16816(a[mt % 3], wo[i][mt][0], wo[i][mt][1], wo[i][mt][2], wo[i][mt][3], mt < 3 ? l0 : h0, mt < 3 ? l1 : h1);
                if (i == 0) {
                    int key = v.w & 0xffffff00u;
                    key ^= (key >> 31) & 0x7fffffff;
                    key = __reduce_max_sync(0xffffffffu, key);
                    key ^= (key >> 31) & 0x7fffffff;
                    const float ws = fast_ex2((F(v.w & 0xffffff00u) - __int_as_float(key)) * LOG2E);
                    sa = shi(ws, e1 ? 8 : 0); sb = shi(ws, e1 ? 12 : 4);
                    rl = ws * F(z.w & 0xffffff00u);
                    rl += shx(rl, 4);
                }
                if (i == 1) rl += shx(rl, 8);
            }
            float y[3];
#pragma unroll
            for (int j = 2; j < 5; j++) {
                const int mt = j % 3;
                y[mt] = fold(fmaf(a[mt][0], sa, a[mt][1] * sb), fmaf(a[mt][2], sa, a[mt][3] * sb), e1, 1);
            }
            const uint32_t pa = SM_PO + w * 512 + lane * 16;
            if (w < 2) {
                const char* dst = opaque(cell + s * 16384);
                rl = fast_rcp(rl);
                bar_sync<1, 256>();
                const uint4 c1 = lds128(pa), c2 = lds128(pa + 1024), c3 = lds128(pa + 2048);
                red_cell2_if(true, dst, ((y[0] + F(c1.x)) + (F(c2.x) + F(c3.x))) * rl, ((y[1] + F(c1.y)) + (F(c2.y) + F(c3.y))) * rl,
                             ((y[2] + F(c1.z)) + (F(c2.z) + F(c3.z))) * rl);
            } else {
                stsf4(pa - 1024, y[0], y[1], y[2], 0.f);
                bar_sync<1, 256>();
            }
            TRACES(tr + 1);
            if ((ORD_NO_TAIL >> n) & 1) continue;
            const uint32_t tsend = clk32();
            if (n == 0) {
                st_pkt2_if(lane < 4, p.scr + SCR_O + head_off(h) + 2048 + w * 256 + s * 64 + lane * 16, 0, 0, 0, 0);
                __syncwarp();
            } else if (!last) {
                const char* nsrc = p.scr + acc_off(k - 1, 1, w) + near + g * 256 + t4 * 16;
                SPIN_DECL;
                do {
                    v = ld_pkt(nsrc);
                    SPIN_CHECK(n);
                    nx01 = pack2(F(v.x), F(v.y)); nx2 = pack2(F(v.z), 0.f);
                } while (__any_sync(0xffffffffu, v.w != FULL_A));
            }
            wait_clk(tsend + (w < 2 ? 0 : 60) + (n < QUIET ? CFG(DLY_AL) : CFG(DLY_A)));
            {
                SPIN_DECL;
                do {
                    v = ld_pkt(cell + near);
                    SPIN_CHECK(n);
                    x01 = pack2(F(v.x), F(v.y));
                    x2 = pack2(F(v.z), 0.f);
                    put_x(x01, x2, xw, e2);
                } while (__any_sync(0xffffffffu, v.w != FULL_A));
            }
            TRACES(tr + 2);
          } else { x01 = nx01; x2 = nx2; put_x(x01, x2, xw, e2); }
        } else {
            mbar_wait(bar_at(B_W + 1), 0);
            const uint32_t ln = opaque(lane);
            const int mi = ln >> 3, mr = ln & 7;
            uint32_t zero = ln >> 5;
            TRACES(76);
#pragma unroll
            for (int i = 0; i < 3; i++) {
                const int d = 16 * (w >> 1) + (mr >> 1) + 8 * (mr & 1) + (i < 2 ? 64 * (mi >> 1) + 4 * i : 128 + 4 * (mi >> 1));
#pragma unroll
                for (int mt = 0; mt < 5; mt++) ldsm4t(wo[i][mt], ST_WO + d * 320 + 160 * (w & 1) + 32 * mt + 16 * (mi & 1), zero);
            }
            fence_async();
            __syncwarp();
            mbar_arrive_if(lane == 0, bar_at(B_WC + 1));
            mbar_wait(bar_at(B_W + 2), 0);
            TRACES(77);
#pragma unroll
            for (int i = 0; i < 5; i++) {
                const uint32_t ga = ST_WG + (mi & 1) * 20480 + (80 * w + 16 * i + mr + 8 * (mi >> 1)) * 32;
                uint32_t r[4];
                ldsm4t(wg[i], ga + (odd ? 16 : 0), zero);
                ldsm4t(r, ga + (odd ? 0 : 16), zero);
#pragma unroll
                for (int kh = 0; kh < 2; kh++) {
                    const uint32_t moved = __shfl_xor_sync(0xffffffffu, odd ? r[2 * kh] : r[2 * kh + 1], 16);
                    wh[i][kh] = (g < 4) == odd ? moved : odd ? r[2 * kh + 1] : r[2 * kh];
                }
            }
            fence_async();
            __syncwarp();
            mbar_arrive_if(lane == 0, bar_at(B_WC + 2));
            TRACES(72);
            x01 = 0x3f803f80u; x2 = 0x3f80u;
            put_x(x01, x2, xw, e2);
        }
        {
            uint32_t b[10];
            get_x(b, xr);
            float a[2][4] = {};
#pragma unroll
            for (int i = 0; i < 5; i++) {
                mma16816(a[0], wg[i][0], wg[i][1], wg[i][2], wg[i][3], b[2 * i], b[2 * i + 1]);
                mma16816(a[1], wh[i][0], b[2 * i], wh[i][1], b[2 * i + 1], b[2 * i], b[2 * i + 1]);
            }
            stsf(SM_PG + (w >> 2) * 512 + (g + 8 * t4) * 16 + (w & 3) * 4, e2 ? (e1 ? a[1][2] : a[1][0]) : (e1 ? a[0][2] : a[0][0]));
            const uint2 cs = lds64(SM_CSG + lane * 48);
            const char* dst = opaque(cell + 3 * HALF - near);
            bar_sync<2, 256>();
            const float S = sum8(lds128(SM_PG + lane * 16), lds128(SM_PG + 512 + lane * 16));
            const float sx = shi(S, 25), sq = shi(S, 24), Su = shi(S, lane + (lane < 16 ? 8 : 4));
            if (n < 0) {
                if (w == 0) stsf2(SM_CSG + lane * 48, S, Su);
            } else {
                float mean_b, rden;
                ln_fast(sx, sq, mean_b, rden);
                const float gv = bfr(fmaf(-mean_b, F(cs.x), S) * rden), uv = bfr(fmaf(-mean_b, F(cs.y), Su) * rden);
                const float sg = fast_rcp(1.f + fast_ex2(-LOG2E * gv));
                const uint32_t hb = pack2(bfr(gv * sg) * uv, 0.f);
                const uint32_t b0 = __byte_perm(shi(hb, 2 * t4), shi(hb, 2 * t4 + 1), 0x5410);
                const uint32_t b1 = __byte_perm(shi(hb, e1 ? 18 : 16), shi(hb, e1 ? 19 : 17), 0x5410);
                const bool up = g >= 4;
                const uint32_t l0 = up ? 0 : b0, h0 = up ? b0 : 0;
                const uint32_t m1 = up == e2 ? b1 : 0;
                float d[3][4] = {};
                mma16816(d[0], wd[0][0], wd[0][1], wd[0][2], wd[0][3], l0, h0);
                mma16816(d[1], wd[1][0], wd[1][1], wd[1][2], wd[1][3], l0, h0);
                mma16816(d[2], wd[2][0], wd[2][1], wd[2][2], wd[2][3], l0, up ? 0 : m1);
                mma1688(d[0], wd[3][0], wd[3][1], m1);
                mma1688(d[1], wd[3][2], wd[3][3], m1);
                red_cell(dst, e1 ? d[0][2] : d[0][0], e1 ? d[1][2] : d[1][0], e1 ? d[2][2] : d[2][0]);
                const uint32_t tsend = clk32();
                TRACES(tr + 3);
                if (last && w != cta >> 4) continue;
                const float sgr = shi(sg, 27);
                const uint32_t sg2 = pack2(sgr, sgr);
                const uint32_t n01 = opaque(pack2((bf_lo(x01) - mean_b) * rden, (bf_hi(x01) - mean_b) * rden));
                const uint32_t n2 = opaque(pack2((bf_lo(x2) - mean_b) * rden, 0.f));
                if (last) {
                    sts128_if(lane >> 1 == (cta & 15), SM_FIN + (lane & 1) * 16, x01, n01, __byte_perm(x2, n2, 0x5410), sg2);
                    mbar_arrive_if(lane >> 1 == (cta & 15), bar_at(B_FIN));
                    __syncwarp();
                    continue;
                }
                wait_clk(tsend + (n < QUIET ? CFG(DLY_BL) : CFG(DLY_B)));
                const uint32_t r01 = x01, r2 = x2;
                float cnt;
                SPIN_DECL;
                do {
                    const uint4 v = ld_pkt(cell + 2 * HALF), z = ld_pkt(cell + 3 * HALF);
                    SPIN_CHECK(n);
                    cnt = F(v.w) + F(z.w);
                    x01 = badd2(r01, badd2(n01, bmul2(pack2(F(v.x) + F(z.x), F(v.y) + F(z.y)), sg2)));
                    x2 = badd2(r2, badd2(n2, bmul2(pack2(F(v.z) + F(z.z), 0.f), sg2)));
                    put_x(x01, x2, xw, e2);
                } while (__any_sync(0xffffffffu, cnt != NCTA));
                TRACES(tr + 4);
            }
        }
        }
        {
            uint32_t b[10];
            get_x(b, xr);
            float a[3][4] = {};
            const float f0 = bf_lo(x01), f1 = bf_hi(x01), f2 = e2 ? 0.f : bf_lo(x2);
            float st;
#pragma unroll
            for (int i = 0; i < 5; i++) {
#pragma unroll
                for (int mt = 0; mt < 3; mt++) {
                    mma16816(a[mt], wq[i][mt][0], wq[i][mt][1], wq[i][mt][2], wq[i][mt][3], b[2 * i], b[2 * i + 1]);
                    if (i == 0 && mt == 0) st = fold(fmaf(f0, f0, fmaf(f1, f1, f2 * f2)), (f0 + f1) + f2, g & 1, 4);
                }
                if (i < 4) st += shx(st, i < 2 ? 1 << i : 2 << i);
            }
            const uint32_t pa = SM_PQ + (w >> 2) * 1024 + (g & 1) * 512 + ((e2 ? 16 : 0) + (e1 ? 4 : 0) + (g >> 1)) * 16 + (w & 3) * 4;
            stsf(pa + 128, e2 ? st : e1 ? a[1][2] : a[1][0]);
            stsf(pa, e2 ? (e1 ? a[2][2] : a[2][0]) : (e1 ? a[0][2] : a[0][0]));
            bar_sync<3, 288>();
            if (n >= 0 && w == cta >> 4) {
                red_cell2_if(lane >> 1 == (cta & 15), cell + (acc_off(k, 1, 0) - acc_off(k, 0, 0)), f0, f1, f2);
                __syncwarp();
            }
        }
    }
}

__host__ __device__ constexpr int bar_count(int i) {
    return i < 16 ? 1 : i < B_RR ? 0 : i < B_RK ? 2 : i <= B_RV ? 4 : i == B_Z ? 1 : i == B_EP ? 9 : i < B_WC ? 0 : i < B_FIN ? 8 :
           i == B_FIN ? 2 : i == B_PS || i == B_RP ? 4 : i == B_QR ? 32 : 1;
}
template <int I, int END> __device__ __forceinline__ void init_bars() {
    if constexpr (I < END) {
        if (bar_count(I)) mbar_init(bar_at(I), bar_count(I));
        init_bars<I + 1, END>();
    }
}
template <int ID> __device__ __forceinline__ void role_exit() { asm volatile("exit; // %0" ::"n"(ID)); }
constexpr int NTHREADS = 512;
#define STR2(x) #x
#define STR(x) STR2(x)
__global__ void __launch_bounds__(NTHREADS, 1)
decode_kernel(const Params p, const __grid_constant__ Maps tm) {
    extern __shared__ __align__(1024) unsigned char smem[];
    if (threadIdx.x == 0) l2_prefetch(p.wq + (size_t)blockIdx.x * 12288, 12288);
    const uint32_t t0 = now_ns() - CFG(LEAD);
    const int lane = threadIdx.x & 31;
    const int warp = __reduce_max_sync(0xffffffffu, threadIdx.x >> 5);
    if (warp < 8) {
        asm volatile("setmaxnreg.inc.sync.aligned.u32 " STR(CFG_REG_CHAIN) ";");
        bar_arrive<5, 480 + 0>();
        const uint32_t vote = probe_near(p, warp, lane);
        bar_sync<2, 256 + 32>();
        sts32(SM_NEAR + warp * 4, vote);
        mbar_arrive_if(lane == 0, bar_at(B_EP));
        chain_role(p, warp, __shfl_sync(0xffffffffu, lane, lane), t0);
        role_exit<3>();
    } else if (warp < 12) {
        asm volatile("setmaxnreg.dec.sync.aligned.u32 " STR(CFG_REG_ATT) ";");
        if (elect_one()) {
            if (warp == 8) init_bars<0, 12>();
            else if (warp == 9) init_bars<12, 30>();
            else if (warp == 10) init_bars<30, 42>();
            else init_bars<42, NBAR>();
            asm volatile("fence.mbarrier_init.release.cluster;" ::: "memory");
            fence_async();
        }
        if (warp == 8) TRACE(236);
        bar_sync<5, 480>();
        if (warp == 8) TRACE(237);
        attention_role(p, warp - 8, lane);
        role_exit<2>();
    } else {
        asm volatile("setmaxnreg.dec.sync.aligned.u32 " STR(CFG_REG_HELP) ";");
        if (warp == 12) {
            load_role(p, &tm.k, lane, t0);
            role_exit<0>();
        } else {
            if (warp == 14) {
                if (smem_u32(smem) != SB) __trap();
                if (elect_one()) {
                    asm volatile("prefetch.tensormap [%0];" ::"l"(&tm.q) : "memory");
                    mbar_init(bar_at(B_W), 1); mbar_init(bar_at(B_W + 1), 1); mbar_init(bar_at(B_W + 2), 1);
                    asm volatile("fence.mbarrier_init.release.cluster;" ::: "memory");
                    fence_async();
                    mbar_expect_tx(bar_at(B_W), 61440 + 15360 + 6400); mbar_expect_tx(bar_at(B_W + 1), 61440); mbar_expect_tx(bar_at(B_W + 2), 40960);
                    bulk_load(ST_X, p.x, 5120, bar_at(B_W));
                    bulk_load(ST_X + 5120, p.wr, 1280, bar_at(B_W));
                }
                TRACE(238);
                reload_role(p, &tm, t0);
            } else {
                if (warp == 13 && elect_one()) {
                    asm volatile("prefetch.tensormap [%0];" ::"l"(&tm.g) : "memory");
                    asm volatile("prefetch.tensormap [%0];" ::"l"(&tm.u) : "memory");
                    asm volatile("prefetch.tensormap [%0];" ::"l"(&tm.o) : "memory");
                    asm volatile("prefetch.tensormap [%0];" ::"l"(&tm.k) : "memory");
                    asm volatile("prefetch.tensormap [%0];" ::"l"(&tm.v) : "memory");
                }
                TRACE(233 + warp);
                bar_sync<5, 480>();
                if (warp == 13) { bar_arrive<6, 64>(); q_role(p, lane); }
                else { bar_arrive<2, 256 + 32>(); zero_role(p, lane, t0); }
            }
            role_exit<1>();
        }
    }
}

typedef CUresult (*EncodeFn)(CUtensorMap*, CUtensorMapDataType, cuuint32_t, void*, const cuuint64_t*, const cuuint64_t*,
                             const cuuint32_t*, const cuuint32_t*, CUtensorMapInterleave, CUtensorMapSwizzle,
                             CUtensorMapL2promotion, CUtensorMapFloatOOBfill);

bool make_map(EncodeFn fn, CUtensorMap* m, const void* ptr, uint64_t cols, uint64_t rows, uint32_t bc, uint32_t br) {
    cuuint64_t dims[2] = {cols, rows};
    cuuint64_t strides[1] = {cols * 2};
    cuuint32_t box[2] = {bc, br};
    cuuint32_t es[2] = {1, 1};
    return fn(m, CU_TENSOR_MAP_DATA_TYPE_BFLOAT16, 2, const_cast<void*>(ptr), dims, strides, box, es, CU_TENSOR_MAP_INTERLEAVE_NONE,
              CU_TENSOR_MAP_SWIZZLE_NONE, CU_TENSOR_MAP_L2_PROMOTION_L2_128B, CU_TENSOR_MAP_FLOAT_OOB_FILL_NONE) == CUDA_SUCCESS;
}

bool make_kv_map(EncodeFn fn, CUtensorMap* m, const void* ptr) {
    cuuint64_t dims[4] = {64, 8, 3, (cuuint64_t)NB * NHEAD * SK / 8};
    cuuint64_t strides[3] = {DH * 2, 128, 8 * DH * 2};
    cuuint32_t box[4] = {64, 8, 3, 4};
    cuuint32_t es[4] = {1, 1, 1, 1};
    return fn(m, CU_TENSOR_MAP_DATA_TYPE_BFLOAT16, 4, const_cast<void*>(ptr), dims, strides, box, es, CU_TENSOR_MAP_INTERLEAVE_NONE,
              CU_TENSOR_MAP_SWIZZLE_128B, CU_TENSOR_MAP_L2_PROMOTION_L2_128B, CU_TENSOR_MAP_FLOAT_OOB_FILL_NONE) == CUDA_SUCCESS;
}

}

extern "C" void kernel_launch(void* const* d_in, const int* in_sizes, int n_in, void* d_out, int out_size) {
    (void)in_sizes; (void)n_in; (void)out_size;
    static EncodeFn fn = nullptr;
    static const char* scr = nullptr;
    if (!fn) {
        void* f = nullptr;
        cudaDriverEntryPointQueryResult qr;
        if (cudaGetDriverEntryPoint("cuTensorMapEncodeTiled", &f, cudaEnableDefault, &qr) != cudaSuccess || !f) return;
        void* sp = nullptr;
        if (cudaGetSymbolAddress(&sp, g_scratch) != cudaSuccess) return;
        scr = (const char*)(((uintptr_t)sp + (2 << 20) - 1) & ~(uintptr_t)((2 << 20) - 1));
        fn = (EncodeFn)f;
        cudaFuncSetAttribute(decode_kernel, cudaFuncAttributeMaxDynamicSharedMemorySize, SMEM_BYTES);
    }
    Maps tm;
    if (!make_kv_map(fn, &tm.k, d_in[1]) || !make_kv_map(fn, &tm.v, d_in[2])) return;
    if (!make_map(fn, &tm.q, d_in[3], NHEAD * DH, DM, 48, 128) || !make_map(fn, &tm.o, d_in[4], DM, NHEAD * DH, 160, 32)) return;
    if (!make_map(fn, &tm.g, d_in[7], FF, DM, 16, 128) || !make_map(fn, &tm.u, d_in[8], FF, DM, 16, 128)) return;
    Params p;
    p.x = (const unsigned short*)d_in[0];
    p.wq = (const char*)d_in[3];
    p.wo = (const char*)d_in[4];
    p.wr = (const unsigned short*)d_in[6];
    p.wg = (const char*)d_in[7];
    p.wu = (const char*)d_in[8];
    p.wd = (const char*)d_in[9];
    p.out = (unsigned short*)d_out;
    p.scr = scr;
    decode_kernel<<<NCTA, NTHREADS, SMEM_BYTES>>>(p, tm);
}
```

```cpp
#include <cuda_runtime.h>
#include <cuda_bf16.h>
#include <cuda.h>
#include <stdint.h>

namespace {

constexpr int NB = 4, DM = 640, NHEAD = 32, DH = 192, SK = 4096, WIN = 1024, FF = 1536;
constexpr int NCTA = 128;
constexpr int TILE = 12288, PAIR = 2 * TILE;

#define CFG_LIST(X) \
    X(TICK0, 476)        \
    X(TICK, 492)        \
    X(LEAD, 450)        \
    X(STAG, 500)        \
    X(WLAG, 350)        \
    X(GSTEP, 750)        \
    X(WIN, 5)        \
    X(PMAX, 2)        \
    X(PGRACE, 50)        \
    X(LMAX0, 150)        \
    X(LMAX, 120) \
    X(GAIN, 5)        \
    X(VSTEP, 150)        \
    X(RSTEP, 670)        \
    X(RSTEP3, 450) \
    X(ZTILE, 11)        \
    X(DLY_A, 410)        \
    X(DLY_AL, 100) \
    X(DLY_B, 570) \
    X(DLY_BL, 950) \
    X(DLY_F, 290) \
    X(FLIP, 0) \

#define X(n, v) constexpr int CFG_##n = v;
CFG_LIST(X)
#undef X
#define CFG(n) CFG_##n
constexpr int QUIET = 8;
#define CFG_REG_CHAIN 216
#define CFG_REG_ATT 48
#define CFG_REG_HELP 32
constexpr int KB_KV0 = 165;
__device__ __forceinline__ int kb_ns(int kb) { return kb * CFG(TICK0) / 12; }
__device__ __forceinline__ int tick_ns(int j) { return j <= 16 ? CFG(TICK0) : CFG(TICK); }
__device__ __forceinline__ int batch_ns(int k) { return kb_ns(KB_KV0) + (k ? 16 * (CFG(TICK0) + (k - 1) * CFG(TICK)) : 0); }

__device__ __forceinline__ uint32_t slots(int k) { return k & 2 ? (k & 1 ? 0x21304768u : 0x76835214u) : (k & 1 ? 0x21480765u : 0x76543210u); }
__device__ __forceinline__ int pass_nibble(int k, int u) { return k > 0 ? 4 + (u & 1) : u; }
__device__ __forceinline__ uint32_t slot_at(uint32_t tab, int u) { return (tab >> (4 * u)) & 15; }

constexpr int NROUND = 11;
constexpr uint32_t ORD_BATCH = 0x3b9910, ORD_LAST = 0x6da, ORD_NO_HEAD = 0x248, ORD_NO_TAIL = 0x092;

constexpr uint32_t SB = 1024;
constexpr uint32_t SM_BAR = SB + 9 * PAIR;
constexpr int B_F1 = 0;
constexpr int B_RR = 24;
constexpr int B_RK = 32;
constexpr int B_RV = 36;
constexpr int B_Z = 37;
constexpr int B_EP = 38;
constexpr int B_W = 39;
constexpr int B_WC = 42;
constexpr int B_FIN = 45;
constexpr int B_F3 = 46;
constexpr int B_PS = 48;
constexpr int B_RP = 49;
constexpr int B_FL = 50;
constexpr int B_QR = 51;
constexpr int NBAR = 52;
__host__ __device__ constexpr uint32_t bar_at(int i) { return SM_BAR + 8 * i; }
constexpr uint32_t SM_EPOCH = SM_BAR + 416;
constexpr uint32_t SM_MAX = SM_EPOCH + 16;
constexpr uint32_t SM_SUM = SM_MAX + 16;
constexpr uint32_t SM_NEAR = SM_SUM + 32;
constexpr uint32_t SM_FIN = SM_NEAR + 32;
constexpr uint32_t SM_Q = SM_FIN + 32;
constexpr uint32_t PSTR = 144;
constexpr uint32_t SM_P = SM_Q + 5 * 384;
constexpr uint32_t SM_X = SM_P + 8 * PSTR;
constexpr uint32_t SM_CSG = SM_X + 40;
constexpr uint32_t SM_ONES = SM_X + 8 * 384;
constexpr uint32_t SM_PG = SM_ONES + 48;
constexpr uint32_t SM_PO = SM_PG + 1024;
constexpr uint32_t SM_PQ = SM_PO;
constexpr int SMEM_BYTES = SM_PO + 3072 - SB;
static_assert(SMEM_BYTES <= 232448 && SM_Q % 16 == 0 && SM_P % 16 == 0 && SM_X % 16 == 0 && SM_PO % 16 == 0, "smem");
constexpr uint32_t ST_WQ = SB, ST_WD = SB + 3 * PAIR, ST_WO = SB + 4 * PAIR, ST_WG = SB + 7 * PAIR, ST_X = ST_WG + 40960;

__device__ unsigned g_epoch;
__device__ unsigned char g_scratch[4 << 20];
constexpr uint32_t HALF = 4096, SCR_O = 1 << 16, SCR_Q = 1 << 17, SCR_COUNT = 3 << 16;
__device__ __forceinline__ uint32_t acc_off(int k, int layer, int w) {
    return (k & 1) << 6 | layer << 7 | (w & 1) << 11 | (w >> 1) << 14 | (k + layer == NB) << 18;
}
__device__ __forceinline__ uint32_t head_off(int h) { return (h & 3) << 14 | (h & 4) << 16 | (h & 8) << 17 | (h & 16) << 9; }
__device__ __forceinline__ uint32_t head_near(int h, uint32_t near) { return near ^ HALF ^ (h & 16) << 8; }
constexpr uint32_t FULL_A = 0x42040000u;

struct Params {
    const char* wq;
    const unsigned short* x;
    const char* wo;
    const unsigned short* wr;
    const char* wg;
    const char* wu;
    const char* wd;
    unsigned short* out;
    const char* scr;
};

__device__ __forceinline__ uint32_t smem_u32(const void* p) { return (uint32_t)__cvta_generic_to_shared(p); }
__device__ __forceinline__ void mbar_init(uint32_t a, uint32_t c) { asm volatile("mbarrier.init.shared::cta.b64 [%0], %1;" ::"r"(a), "r"(c) : "memory"); }
__device__ __forceinline__ void mbar_expect_tx(uint32_t a, uint32_t b) {
    asm volatile("mbarrier.arrive.expect_tx.shared::cta.b64 _, [%0], %1;" ::"r"(a), "r"(b) : "memory");
}
__device__ __forceinline__ void mbar_arrive(uint32_t a) { asm volatile("mbarrier.arrive.shared::cta.b64 _, [%0];" ::"r"(a) : "memory"); }
constexpr uint32_t SPIN_LIMIT = 1u << 22;
#define SPIN_DECL uint32_t spins = 0
#define SPIN_CHECK(info) { if (++spins > SPIN_LIMIT) __trap(); }
__device__ __forceinline__ void jitter() {}
__device__ __forceinline__ void mbar_wait(uint32_t a, uint32_t parity) {
    jitter();
    uint32_t ok;
    SPIN_DECL;
    while (true) {
        asm volatile("{\n.reg .pred p;\nmbarrier.try_wait.parity.shared::cta.b64 p, [%1], %2;\nselp.u32 %0, 1, 0, p;\n}"
                     : "=r"(ok) : "r"(a), "r"(parity) : "memory");
        if (ok) break;
        SPIN_CHECK((a - SM_BAR) / 8 * 10 + parity);
    }
    jitter();
}
__device__ __forceinline__ bool mbar_test2(uint32_t a, uint32_t pa, uint32_t b, uint32_t pb) {
    uint32_t ok;
    asm volatile("{\n.reg .pred p, q;\nmbarrier.test_wait.parity.shared::cta.b64 p, [%1], %2;\n"
                 "mbarrier.test_wait.parity.shared::cta.b64 q, [%3], %4;\nand.pred p, p, q;\nvote.sync.all.pred p, p, 0xffffffff;\nselp.u32 %0, 1, 0, p;\n}"
                 : "=r"(ok) : "r"(a), "r"(pa), "r"(b), "r"(pb) : "memory");
    return ok;
}
__device__ __forceinline__ uint32_t now_ns() { uint32_t t; asm volatile("mov.u32 %0, %%globaltimer_lo;" : "=r"(t) :: "memory"); return t; }
__device__ __forceinline__ uint32_t clk32() { uint32_t c; asm volatile("mov.u32 %0, %%clock;" : "=r"(c) :: "memory"); return c; }
__device__ __forceinline__ void wait_ns(uint32_t t) { jitter(); while ((int)(now_ns() - t) < 0) {} }
__device__ __forceinline__ void wait_clk(uint32_t t) { jitter(); while ((int)(clk32() - t) < 0) {} }
__device__ __forceinline__ bool elect_one() {
    uint32_t e;
    asm volatile("{\n.reg .pred p;\nelect.sync _|p, 0xffffffff;\nselp.u32 %0, 1, 0, p;\n}" : "=r"(e));
    return e;
}
constexpr uint64_t POL_FIRST = 0x12F0000000000000ull, POL_NORMAL = 0x1000000000000000ull;
__device__ __forceinline__ void tma_tile(uint32_t dst, const CUtensorMap* tm, int group, uint32_t bar, uint64_t pol) {
    asm volatile("cp.async.bulk.tensor.4d.shared::cluster.global.mbarrier::complete_tx::bytes.L2::cache_hint"
                 " [%0], [%1, {%3, %3, %3, %4}], [%2], %5;"
                 ::"r"(dst), "l"(tm), "r"(bar), "r"(0), "r"(group), "l"(pol) : "memory");
}
__device__ __forceinline__ void tma2d(uint32_t dst, const CUtensorMap* tm, int x, int y, uint32_t bar) {
    asm volatile("cp.async.bulk.tensor.2d.shared::cluster.global.mbarrier::complete_tx::bytes [%0], [%1, {%3, %4}], [%2];"
                 ::"r"(dst), "l"(tm), "r"(bar), "r"(x), "r"(y) : "memory");
}
__device__ __forceinline__ void bulk_load(uint32_t dst, const void* src, uint32_t bytes, uint32_t bar) {
    asm volatile("cp.async.bulk.shared::cluster.global.mbarrier::complete_tx::bytes [%0], [%1], %2, [%3];"
                 ::"r"(dst), "l"(src), "r"(bytes), "r"(bar) : "memory");
}
__device__ __forceinline__ void l2_prefetch(const void* p, uint32_t bytes) {
    asm volatile("cp.async.bulk.prefetch.L2.global [%0], %1;" ::"l"(p), "r"(bytes) : "memory");
}
__device__ __forceinline__ void mma16816(float (&c)[4], uint32_t a0, uint32_t a1, uint32_t a2, uint32_t a3, uint32_t b0, uint32_t b1) {
    asm volatile("mma.sync.aligned.m16n8k16.row.col.f32.bf16.bf16.f32 {%0,%1,%2,%3}, {%4,%5,%6,%7}, {%8,%9}, {%0,%1,%2,%3};"
                 : "+f"(c[0]), "+f"(c[1]), "+f"(c[2]), "+f"(c[3]) : "r"(a0), "r"(a1), "r"(a2), "r"(a3), "r"(b0), "r"(b1));
}
__device__ __forceinline__ void mma1688(float (&c)[4], uint32_t a0, uint32_t a1, uint32_t b0) {
    asm volatile("mma.sync.aligned.m16n8k8.row.col.f32.bf16.bf16.f32 {%0,%1,%2,%3}, {%4,%5}, {%6}, {%0,%1,%2,%3};"
                 : "+f"(c[0]), "+f"(c[1]), "+f"(c[2]), "+f"(c[3]) : "r"(a0), "r"(a1), "r"(b0));
}
__device__ __forceinline__ void ldsm4(uint32_t (&r)[4], uint32_t a) {
    asm volatile("ldmatrix.sync.aligned.m8n8.x4.shared.b16 {%0,%1,%2,%3}, [%4];"
                 : "=r"(r[0]), "=r"(r[1]), "=r"(r[2]), "=r"(r[3]) : "r"(a) : "memory");
}
__device__ __forceinline__ void ldsm4t(uint32_t (&r)[4], uint32_t a, uint32_t& zero) {
    asm volatile("ldmatrix.sync.aligned.m8n8.x4.trans.shared.b16 {%0,%1,%2,%3}, [%4];"
                 : "=r"(r[0]), "=r"(r[1]), "=r"(r[2]), "=r"(r[3]) : "r"(a + zero) : "memory");
    zero &= r[3];
}
__device__ __forceinline__ uint4 ld_pkt(const void* p) {
    uint4 v;
    asm volatile("{\n.reg .b128 t;\nld.relaxed.gpu.global.b128 t, [%4];\nmov.b128 {%0,%1,%2,%3}, t;\n}"
                 : "=r"(v.x), "=r"(v.y), "=r"(v.z), "=r"(v.w) : "l"(p) : "memory");
    return v;
}
__device__ __forceinline__ void st_pkt(const void* p, uint32_t a, uint32_t b, uint32_t c, uint32_t d) {
    asm volatile("{\n.reg .b128 t;\nmov.b128 t, {%1,%2,%3,%4};\nst.relaxed.gpu.global.b128 [%0], t;\n}"
                 ::"l"(p), "r"(a), "r"(b), "r"(c), "r"(d) : "memory");
}
__device__ __forceinline__ uint2 ld_pkt8(const void* p) {
    uint2 v;
    asm volatile("{\n.reg .b64 t;\nld.relaxed.gpu.global.b64 t, [%2];\nmov.b64 {%0,%1}, t;\n}" : "=r"(v.x), "=r"(v.y) : "l"(p) : "memory");
    return v;
}
__device__ __forceinline__ void red_cell(const char* p, float a, float b, float c) {
    jitter();
    asm volatile("red.relaxed.gpu.global.add.v4.f32 [%0], {%1,%2,%3,%4};" ::"l"(p), "f"(a), "f"(b), "f"(c), "f"(1.0f) : "memory");
}
#define PRED(n) "{\n.reg .pred p;\nsetp.ne.u32 p, %" #n ", 0;\n"
__device__ __forceinline__ void red_cell2_if(bool on, const char* p, float a, float b, float c) {
    jitter();
    asm volatile(PRED(5) "@p red.relaxed.gpu.global.add.v4.f32 [%0], {%1,%2,%3,%4};\n@p red.relaxed.gpu.global.add.v4.f32 [%0+4096], {%1,%2,%3,%4};\n}"
                 ::"l"(p), "f"(a), "f"(b), "f"(c), "f"(1.0f), "r"((uint32_t)on) : "memory");
}
__device__ __forceinline__ void st_pkt8_if(bool on, const void* p, uint32_t a, uint32_t b) {
    jitter();
    asm volatile(PRED(3) ".reg .b64 t;\nmov.b64 t, {%1,%2};\n@p st.relaxed.gpu.global.b64 [%0], t;\n}" ::"l"(p), "r"(a), "r"(b), "r"((uint32_t)on) : "memory");
}
__device__ __forceinline__ void st_pkt82_if(bool on, const void* p, uint32_t a, uint32_t b) {
    asm volatile(PRED(3) ".reg .b64 t;\nmov.b64 t, {%1,%2};\n@p st.relaxed.gpu.global.b64 [%0], t;\n@p st.relaxed.gpu.global.b64 [%0+4096], t;\n}"
                 ::"l"(p), "r"(a), "r"(b), "r"((uint32_t)on) : "memory");
}
__device__ __forceinline__ void st_pkt2_if(bool on, const void* p, uint32_t a, uint32_t b, uint32_t c, uint32_t d) {
    jitter();
    asm volatile(PRED(5) ".reg .b128 t;\nmov.b128 t, {%1,%2,%3,%4};\n@p st.relaxed.gpu.global.b128 [%0], t;\n@p st.relaxed.gpu.global.b128 [%0+4096], t;\n}"
                 ::"l"(p), "r"(a), "r"(b), "r"(c), "r"(d), "r"((uint32_t)on) : "memory");
}
__device__ __forceinline__ void mbar_arrive_if(bool on, uint32_t a) {
    jitter();
    asm volatile(PRED(1) "@p mbarrier.arrive.shared::cta.b64 _, [%0];\n}" ::"r"(a), "r"((uint32_t)on) : "memory");
}
__device__ __forceinline__ void sts16_if(bool on, uint32_t a, uint32_t v) {
    asm volatile(PRED(2) "@p st.shared.u16 [%0], %1;\n}" ::"r"(a), "h"((unsigned short)v), "r"((uint32_t)on) : "memory");
}
__device__ __forceinline__ void sts32_if(bool on, uint32_t a, uint32_t v) {
    asm volatile(PRED(2) "@p st.shared.u32 [%0], %1;\n}" ::"r"(a), "r"(v), "r"((uint32_t)on) : "memory");
}
__device__ __forceinline__ void sts128_if(bool on, uint32_t a, uint32_t x, uint32_t y, uint32_t z, uint32_t w) {
    jitter();
    asm volatile(PRED(5) "@p st.shared.v4.u32 [%0], {%1,%2,%3,%4};\n}" ::"r"(a), "r"(x), "r"(y), "r"(z), "r"(w), "r"((uint32_t)on) : "memory");
}
__device__ __forceinline__ float fast_rcp(float x) { float r; asm("rcp.approx.ftz.f32 %0, %1;" : "=f"(r) : "f"(x)); return r; }
__device__ __forceinline__ float fast_sqrt(float x) { float r; asm("sqrt.approx.ftz.f32 %0, %1;" : "=f"(r) : "f"(x)); return r; }
__device__ __forceinline__ float fast_ex2(float x) { float r; asm("ex2.approx.ftz.f32 %0, %1;" : "=f"(r) : "f"(x)); return r; }
__device__ __forceinline__ uint32_t pack2(float lo, float hi) {
    uint32_t r;
    asm("cvt.rn.bf16x2.f32 %0, %1, %2;" : "=r"(r) : "f"(hi), "f"(lo));
    return r;
}
__device__ __forceinline__ float bfr(float x) { return __uint_as_float(pack2(0.f, x)); }
__device__ __forceinline__ uint32_t badd2(uint32_t a, uint32_t b) { uint32_t r; asm("add.rn.bf16x2 %0, %1, %2;" : "=r"(r) : "r"(a), "r"(b)); return r; }
__device__ __forceinline__ uint32_t bsub2(uint32_t a, uint32_t b) { uint32_t r; asm("sub.rn.bf16x2 %0, %1, %2;" : "=r"(r) : "r"(a), "r"(b)); return r; }
__device__ __forceinline__ uint32_t bmul2(uint32_t a, uint32_t b) { uint32_t r; asm("mul.rn.bf16x2 %0, %1, %2;" : "=r"(r) : "r"(a), "r"(b)); return r; }
__device__ __forceinline__ float bf_lo(uint32_t w) { return __uint_as_float(w << 16); }
__device__ __forceinline__ float bf_hi(uint32_t w) { return __uint_as_float(w & 0xffff0000u); }
__device__ __forceinline__ float F(uint32_t t) { return __uint_as_float(t); }
__device__ __forceinline__ uint32_t lds16(uint32_t a) { unsigned short h; asm volatile("ld.shared.u16 %0, [%1];" : "=h"(h) : "r"(a) : "memory"); return h; }
__device__ __forceinline__ uint32_t lds32(uint32_t a) { uint32_t v; asm volatile("ld.shared.u32 %0, [%1];" : "=r"(v) : "r"(a) : "memory"); return v; }
__device__ __forceinline__ uint2 lds64(uint32_t a) {
    uint2 v; asm volatile("ld.shared.v2.u32 {%0,%1}, [%2];" : "=r"(v.x), "=r"(v.y) : "r"(a) : "memory"); return v;
}
__device__ __forceinline__ uint4 lds128(uint32_t a) {
    uint4 v; asm volatile("ld.shared.v4.u32 {%0,%1,%2,%3}, [%4];" : "=r"(v.x), "=r"(v.y), "=r"(v.z), "=r"(v.w) : "r"(a) : "memory"); return v;
}
__device__ __forceinline__ float sum8(const uint4& u, const uint4& v) {
    return ((F(u.x) + F(u.y)) + (F(u.z) + F(u.w))) + ((F(v.x) + F(v.y)) + (F(v.z) + F(v.w)));
}
__device__ __forceinline__ void sts16(uint32_t a, uint32_t v) { asm volatile("st.shared.u16 [%0], %1;" ::"r"(a), "h"((unsigned short)v) : "memory"); }
__device__ __forceinline__ void sts32(uint32_t a, uint32_t v) { asm volatile("st.shared.u32 [%0], %1;" ::"r"(a), "r"(v) : "memory"); }
__device__ __forceinline__ void stsf(uint32_t a, float v) { asm volatile("st.shared.f32 [%0], %1;" ::"r"(a), "f"(v) : "memory"); }
__device__ __forceinline__ void stsf2(uint32_t a, float x, float y) { asm volatile("st.shared.v2.f32 [%0], {%1,%2};" ::"r"(a), "f"(x), "f"(y) : "memory"); }
__device__ __forceinline__ void stsf4(uint32_t a, float x, float y, float z, float w) {
    asm volatile("st.shared.v4.f32 [%0], {%1,%2,%3,%4};" ::"r"(a), "f"(x), "f"(y), "f"(z), "f"(w) : "memory");
}
template <int ID, int N> __device__ __forceinline__ void bar_sync() { jitter(); asm volatile("bar.sync %0, %1;" ::"n"(ID), "n"(N) : "memory"); jitter(); }
template <int ID, int N> __device__ __forceinline__ void bar_arrive() { jitter(); asm volatile("bar.arrive %0, %1;" ::"n"(ID), "n"(N) : "memory"); jitter(); }
__device__ __forceinline__ void fence_async() { asm volatile("fence.proxy.async.shared::cta;" ::: "memory"); }
__device__ __forceinline__ float shx(float v, int m) { return __shfl_xor_sync(0xffffffffu, v, m); }
__device__ __forceinline__ float shi(float v, int l) { return __shfl_sync(0xffffffffu, v, l); }
__device__ __forceinline__ uint32_t shi(uint32_t v, int l) { return __shfl_sync(0xffffffffu, v, l); }
__device__ __forceinline__ uint32_t opaque(uint32_t x) { asm volatile("mov.u32 %0, %0;" : "+r"(x)); return x; }
__device__ __forceinline__ const char* opaque(const char* x) { asm volatile("mov.u64 %0, %0;" : "+l"(x)); return x; }
constexpr float LOG2E = 1.4426950408889634f, SCALE = 0.07216878364870322f;

#define TRACE(idx) do {} while (0)
#define TRACES(slot) do {} while (0)

__device__ __forceinline__ uint32_t probe_near(const Params& p, int w, int lane) {
    const int cta = blockIdx.x;
    const char* pr = p.scr + SCR_O + head_off(cta >> 2) + 2048 + w * 256 + (cta & 3) * 64;
    st_pkt2_if(lane < 4, pr + lane * 16, 0, 0, 0, 0);
    uint32_t best0 = ~0u, best1 = ~0u;
#pragma unroll 1
    for (int i = w & 1; i < 6 + (w & 1); i++) {
        uint32_t c = clk32(), v = 0;
        if (lane == 0) asm volatile("atom.relaxed.gpu.global.add.u32 %0, [%1], 1;" : "=r"(v) : "l"(pr + (i & 1) * HALF) : "memory");
        c += __shfl_sync(0xffffffffu, v, 0) >> 16;
        c = clk32() - c;
        if (i & 1) best1 = min(best1, c); else best0 = min(best0, c);
    }
    return min(best0, 0xffffu) | min(best1, 0xffffu) << 16;
}
__device__ __forceinline__ uint32_t near_half() {
    const uint4 a = lds128(SM_NEAR), b = lds128(SM_NEAR + 16);
    const uint32_t m = __vminu2(__vminu2(__vminu2(a.x, a.y), __vminu2(a.z, a.w)), __vminu2(__vminu2(b.x, b.y), __vminu2(b.z, b.w)));
    return head_near(blockIdx.x >> 2, ((m & 0xffffu) > m >> 16) != (CFG(FLIP) != 0) ? HALF : 0);
}

__device__ __forceinline__ int kv_group(int k, int t) {
    const int cta = blockIdx.x;
    return ((k * NHEAD + (cta >> 2)) * SK + (SK - WIN) + (cta & 3) * 256 + t * 32) / 8;
}
__device__ __forceinline__ uint32_t phase_ns() { return (((blockIdx.x >> 2) * 13) & 31) * CFG(STAG) / 32; }

__device__ __forceinline__ void ln_fast(float s, float q, float& mean, float& rstd) {
    mean = s * (1.f / DM);
    asm("rsqrt.approx.ftz.f32 %0, %1;" : "=f"(rstd) : "f"(fmaxf(fmaf(-mean, mean, fmaf(q, 1.f / DM, 1e-5f)), 1e-5f)));
}
__device__ __forceinline__ void q_role(const Params& p, int lane) {
    const int cta = blockIdx.x;
    mbar_wait(bar_at(B_EP), 0);
    const uint32_t epoch = lds32(SM_EPOCH), near = head_near(cta >> 2, near_half());
    auto sums = [&](float& S0, float& S1) {
        bar_sync<3, 288>();
        const uint32_t ra = SM_PQ + lane * 16;
        S0 = sum8(lds128(ra), lds128(ra + 1024)); S1 = sum8(lds128(ra + 512), lds128(ra + 1536));
    };
    float cs0, cs1;
    {
        uint32_t q0 = 0, q1 = 0, q2 = 0, q3 = 0;
#pragma unroll 1
        for (int r = 0; r < NB; r++) {
            sums(cs0, cs1);
            bar_arrive<7, 288>();
            q0 = q1; q1 = q2; q2 = q3; q3 = pack2(cs0, cs1);
        }
        const uint32_t t0 = shi(q3, 3 * lane - 72), t1 = shi(q3, 3 * lane - 71), t2 = shi(q3, 3 * lane - 70), tag = epoch << 8 | 0x40;
        const char* box = p.scr + SCR_O + head_off(cta >> 2) + 2048 + (lane >> 2) * 256 + (lane & 3) * 16;
        st_pkt2_if(true, box + (cta & 3) * 64, lane < 24 ? q0 : t0, lane < 24 ? q1 : t1, lane < 24 ? q2 : t2, tag);
        const uint32_t qd = SM_Q + (lane < 24 ? lane * 4 : 3 * 384 + (lane - 24) * 12), step = lane < 24 ? 384 : 4;
#pragma unroll 1
        for (int j = 0; j < 4; j++) {
            uint4 v;
            SPIN_DECL;
            do {
                __nanosleep(200);
                v = ld_pkt(box + near + j * 64);
                SPIN_CHECK(j);
            } while (__any_sync(0xffffffffu, v.w != tag));
            sts32(qd + j * 96, v.x); sts32(qd + j * 96 + step, v.y); sts32(qd + j * 96 + 2 * step, v.z);
        }
        mbar_arrive(bar_at(B_QR));
    }
    sums(cs0, cs1);
    bar_arrive<7, 288>();
    const char* const src = p.scr + SCR_Q + head_off(cta >> 2) + lane * 8 + near;
    const char* const dst = src + (cta & 3) * 192;
    const uint32_t qd = SM_Q + NB * 384 + lane * 4;
    st_pkt82_if(lane < 24, dst - near, 0, 0);
#pragma unroll 1
    for (int k = 0; k < NB; k++) {
        float S0, S1, mean, rstd;
        sums(S0, S1);
        ln_fast(shi(S1, 24), shi(S0, 24), mean, rstd);
        const uint32_t qq = pack2(fmaf(-mean, cs0, S0) * rstd, fmaf(-mean, cs1, S1) * rstd), tag = epoch * NB + k;
        st_pkt8_if(lane < 24, dst + ((int)HALF - 2 * (int)near), qq, tag);
        st_pkt8_if(lane < 24, dst, qq, tag);
        TRACES(k * 12 + 5);
        uint2 a, b, c;
        SPIN_DECL;
        do {
            a = ld_pkt8(src); b = ld_pkt8(src + 256); c = ld_pkt8(src + 512);
            SPIN_CHECK(k);
            sts32(qd, a.x); sts32(qd + 128, b.x); sts32(qd + 256, c.x);
        } while (__any_sync(0xffffffffu, a.y != tag || b.y != tag || c.y != tag));
        mbar_arrive(bar_at(B_QR));
    }
}

struct Maps { CUtensorMap k, v, q, o, g, u; };
__device__ __forceinline__ void load_role(const Params& p, const CUtensorMap* tmKV, int lane, uint32_t t0) {
    const int cta = blockIdx.x;
    t0 += phase_ns();
#pragma unroll 1
    for (int i = 1; i < 5; i++) {
        wait_ns(t0 + i * CFG(TICK0));
        if (elect_one()) l2_prefetch(p.wq + (size_t)(128 * i + cta) * 12288, 12288);
        TRACE(230 + i);
    }
    uint32_t plan[2];
#pragma unroll
    for (int i = 0; i < 2; i++) {
        const int j = lane + 32 * i, k = j >> 4, t = j & 15, u = t >> 1, jw = j - CFG(WIN);
        const int sb = k == 0 ? B_WC + (t >= 8) + (t >= 14) : t >= 12 ? B_RK + u - 5 : t >= 4 ? B_RR + t - 4 : t >= 2 ? B_RP : k > 1 ? B_RK + 3 : B_RR + t;
        const uint32_t sw = sb * 8 | (j < 18 ? 0 : (t >= 12 || u == 1 ? k - 1 : k) & 1) << 9;
        plan[i] = sw | (jw < 0 ? sw : (B_F1 + (jw & 15)) * 8 | ((jw >> 4) & 1) << 9) << 10 |
                  (slot_at(slots(k), t < 8 ? pass_nibble(k, u) : u) * 2 + (t & 1)) << 20 | (t < 10 && j >= 8 && j < 56) << 25;
    }
    bar_sync<6, 64>();
    wait_ns(t0 + kb_ns(60));
    if (elect_one()) bulk_load(ST_WD, p.wd + cta * 15360, 15360, bar_at(B_W));
    TRACE(235);
#pragma unroll 1
    for (int i = 0; i < 5; i++) {
        wait_ns(t0 + kb_ns(75) + i * kb_ns(6));
        if (elect_one()) { l2_prefetch(p.wg + (128 * i + cta) * 3072, 3072); l2_prefetch(p.wu + (128 * i + cta) * 3072, 3072); }
    }
#pragma unroll 1
    for (int i = 0; i < 6; i++) {
        wait_ns(t0 + kb_ns(105) + min(i, 4) * kb_ns(10));
        if (elect_one()) l2_prefetch(p.wo + (size_t)((cta >> 2) * DH + 32 * i + 8 * (cta & 3)) * 1280, 10240);
    }
    t0 += batch_ns(0);
    int jp = 0, shift = 0;
    uint32_t earliest = t0;
    auto requested = [&](uint32_t now) {
        shift = max(max(shift - CFG(GAIN), 0), (int)(now - t0) - (jp < 12 ? CFG(LMAX0) : CFG(LMAX)));
        TRACE(128 + jp);
        t0 += tick_ns(++jp);
    };
    const int grp0 = kv_group(0, 0);
    auto group = [&](int j) { return grp0 + (j >> 4) * (NHEAD * SK / 8) + (j & 7) * 4; };
#pragma unroll 1
    for (int j = 0; j < 16 * NB; j++) {
        const uint32_t pl = __shfl_sync(0xffffffffu, j & 32 ? plan[1] : plan[0], j);
        const int jmax = min(j + CFG(PMAX), 16 * NB);
        jitter();
        uint32_t now;
        SPIN_DECL;
        while (true) {
            const bool ok = mbar_test2(SM_BAR + (pl & 511), (pl >> 9) & 1, SM_BAR + ((pl >> 10) & 511), (pl >> 19) & 1);
            now = now_ns();
            const int late = now - t0 - shift;
            if (ok && (jp > j ? (int)(now - earliest) : late) >= 0) break;
            if (late >= (jp > j ? 0 : CFG(PGRACE)) && jp < jmax) {
                if (elect_one())
                    asm volatile("cp.async.bulk.prefetch.tensor.4d.L2.global [%0, {%1, %1, %1, %2}];" ::"l"(tmKV + ((jp >> 3) & 1)), "r"(0), "r"(group(jp)) : "memory");
                requested(now);
            }
            SPIN_CHECK(j);
        }
        if (elect_one()) {
            mbar_expect_tx(bar_at(B_F1 + (j & 15)), TILE);
            tma_tile(SB + ((pl >> 20) & 31) * TILE, tmKV + ((j >> 3) & 1), group(j), bar_at(B_F1 + (j & 15)), pl >> 25 ? POL_NORMAL : POL_FIRST);
        }
        TRACE(256 + j);
        if ((j & 15) == 15) TRACES(88 + (j >> 4));
        earliest = now + CFG(VSTEP);
        if (jp == j) requested(now);
    }
}

__device__ __forceinline__ void reload_role(const Params& p, const Maps* tm, uint32_t t0) {
    const CUtensorMap* const tmK = &tm->k;
    const CUtensorMap* const tmV = &tm->v;
    const int cta = blockIdx.x;
    t0 += CFG(TICK0) + CFG(WLAG) + phase_ns();
#pragma unroll 1
    for (int i = 0; i < 5; i++) {
        wait_ns(t0 + i * CFG(TICK0));
        if (elect_one()) tma2d(ST_WQ + i * 12288, &tm->q, 48 * cta, 128 * i, bar_at(B_W));
        TRACE(240 + i);
        if (i == 1) bar_sync<5, 480>();
    }
#pragma unroll 1
    for (int i = 0, o = 0; i < 10;) {
        const uint32_t now = now_ns() - t0;
        if (o < 6 && (int)now >= kb_ns(105) + o * kb_ns(10)) {
            if (elect_one()) tma2d(ST_WO + o * 10240, &tm->o, 160 * (cta & 3), (cta >> 2) * DH + 32 * o, bar_at(B_W + 1));
            o++;
        } else if ((int)now >= kb_ns(77) + i * CFG(GSTEP) && (i < 9 || o == 6)) {
            if (elect_one()) tma2d(ST_WG + (i & 1) * 20480 + (i >> 1) * 4096, i & 1 ? &tm->u : &tm->g, (12 * cta) & ~7, 128 * (i >> 1), bar_at(B_W + 2));
            i++;
        }
    }
#pragma unroll 1
    for (int k = 0; k < NB - 1; k++) {
        mbar_wait(bar_at(B_RK), k & 1);
        if (elect_one()) {
            const uint32_t dst = SB + slot_at(slots(k), 0) * PAIR;
            mbar_expect_tx(bar_at(B_FL), PAIR);
            tma_tile(dst, tmV, kv_group(k, 0), bar_at(B_FL), POL_FIRST);
            tma_tile(dst + TILE, tmV, kv_group(k, 1), bar_at(B_FL), POL_FIRST);
        }
        mbar_wait(bar_at(B_RV), k & 1);
        uint32_t due = now_ns();
        if (elect_one()) mbar_expect_tx(bar_at(B_F3), 4 * PAIR);
#pragma unroll 1
        for (int t = 0; t < 8; t++) {
            wait_ns(due);
            due += k == NB - 2 ? CFG(RSTEP3) : CFG(RSTEP);
            if (elect_one())
                tma_tile(SB + slot_at(slots(k + 1), t >> 1) * PAIR + (t & 1) * TILE, tmK, kv_group(k + 1, t), bar_at(B_F3), POL_FIRST);
        }
        TRACE(121 + k);
    }
}

__device__ __forceinline__ void zero_role(const Params& p, int lane, uint32_t t0) {
    const int cta = blockIdx.x;
    unsigned ticket = 0;
    if (lane == 0) ticket = atomicAdd(&g_epoch, 1u);
    const uint32_t epoch = __shfl_sync(0xffffffffu, ticket, 0) / NCTA + 1;
    if (lane == 0) { sts32(SM_EPOCH, epoch); mbar_arrive(bar_at(B_EP)); }
    mbar_wait(bar_at(B_EP), 0);
#pragma unroll 1
    for (int k = 0; k < NB + 2; k++) {
        lane = opaque(lane);
        const int cl = 2 * (cta & 15) + (lane & 1);
        const int col = 80 * (cta >> 4) + (cl & 2 ? 48 : 0) + (cl >> 2) + (cl & 1 ? 8 : 0);
        const char* own = p.scr + (cl >> 2) * 256 + (cl & 3) * 16;
        uint32_t v0 = 0, v1 = 0, v2 = 0;
        if (lane < 4 && k < NB) {
            const unsigned short* xp = p.x + k * DM + col;
            v0 = __ldg(xp) << 16; v1 = __ldg(xp + 16) << 16; v2 = cl & 2 ? 0 : __ldg(xp + 32) << 16;
        }
        uint4 r;
        if (k == 1) mbar_wait(bar_at(B_RK), 0);
        if (k > 1) {
            mbar_wait(bar_at(B_FIN), k & 1);
            r = lds128(SM_FIN + (lane & 1) * 16);
        }
        if (k < NB) {
            const int lg = lane >> 3, ty = (lane & 7) >> 1;
            const char* dst = own + acc_off((k - (lg >> 1)) & 3, lg != 0, cta >> 4) + ty * HALF;
            wait_ns(t0 + batch_ns(k) + CFG(ZTILE) * CFG(TICK0));
            if (lg == 0 || (lg == 1 && (ty < 2 || k == NB - 1)) || (lg == 2 && k > 0 && ty > 1)) {
                st_pkt(dst, v0, v1, v2, ~0u);
                asm volatile("atom.relaxed.gpu.global.exch.b32 %0, [%1+12], %2;" : "=r"(v0) : "l"(dst), "r"(lane < 4 ? 0x3f800000u : 0u) : "memory");
                v0 = ~v0;
            }
            if (__any_sync(0xffffffffu, v0 != 0)) __trap();
            const char* cnt = p.scr + SCR_COUNT;
            if (lane < 2) asm volatile("red.relaxed.gpu.global.add.u32 [%0], 1;" ::"l"(cnt + lane * HALF) : "memory");
            const uint32_t target = ((epoch - 1) * NB + k + 1) * NCTA;
            cnt += near_half();
            SPIN_DECL;
            uint32_t v;
            do {
                __nanosleep(100);
                asm volatile("ld.relaxed.gpu.global.u32 %0, [%1];" : "=r"(v) : "l"(cnt) : "memory");
                SPIN_CHECK(v);
            } while (__any_sync(0xffffffffu, (int)(v - target) < 0));
        }
        __syncwarp();
        if (lane == 0) mbar_arrive(bar_at(B_Z));
        if (k > 1) {
            const int b = k - 2;
            const char* src = own + acc_off(b, 1, cta >> 4) + (2 + ((lane >> 1) & 1)) * HALF;
            unsigned short* o = p.out + b * DM + col + (lane >> 2) * 16;
            const bool on = !(lane & 2) && lane < (cl & 2 ? 8 : 12);
            wait_clk(clk32() + CFG(DLY_F));
            float cnt;
            SPIN_DECL;
            do {
                const uint4 v = ld_pkt(src);
                SPIN_CHECK(k);
                cnt = F(v.w) + shx(F(v.w), 2);
                const float y0 = F(v.x) + shx(F(v.x), 2), y1 = F(v.y) + shx(F(v.y), 2), y2 = F(v.z) + shx(F(v.z), 2);
                const uint32_t x01 = badd2(r.x, badd2(r.y, bmul2(pack2(y0, y1), r.w)));
                const uint32_t x2 = badd2(r.z, badd2(r.z >> 16, bmul2(pack2(y2, 0.f), r.w)));
                if (cnt == NCTA && on) *o = lane < 4 ? x01 : lane < 8 ? x01 >> 16 : x2;
            } while (__any_sync(0xffffffffu, cnt != NCTA));
            TRACES((2 * b + 1) * 6 + 4);
        }
    }
}

__host__ __device__ constexpr uint32_t desc_lo(uint32_t addr) { return ((addr & 0x3FFFFu) >> 4) | (1u << 16); }
constexpr uint32_t DESC_HI_TILE = (3072u >> 4) | (1u << 30);
constexpr uint32_t DESC_HI_VEC = 1u;
template <int TA, int AOFF, int BOFF>
__device__ __forceinline__ void wgmma_n8(float (&d)[4], uint32_t alo, uint32_t blo, int accumulate) {
    asm volatile("{\n.reg .pred p;\n.reg .b32 a, b;\n.reg .b64 da, db;\nsetp.ne.b32 p, %6, 0;\n"
                 "add.u32 a, %4, %8;\nadd.u32 b, %5, %9;\nmov.b64 da, {a, %10};\nmov.b64 db, {b, %11};\n"
                 "wgmma.mma_async.sync.aligned.m64n8k16.f32.bf16.bf16 {%0,%1,%2,%3}, da, db, p, 1, 1, %7, 0;\n}"
                 : "+f"(d[0]), "+f"(d[1]), "+f"(d[2]), "+f"(d[3])
                 : "r"(alo), "r"(blo), "r"(accumulate), "n"(TA), "n"(AOFF >> 4), "n"(BOFF >> 4), "n"(DESC_HI_TILE), "n"(DESC_HI_VEC));
}
template <int KS, int END>
__device__ __forceinline__ void qk_steps(float (&d)[4], uint32_t alo, uint32_t blo) {
    if constexpr (KS < END) {
        wgmma_n8<0, (KS >> 2) * 1024 + (KS & 3) * 32, KS * 32>(d, alo, blo, KS > 0);
        qk_steps<KS + 1, END>(d, alo, blo);
    }
}
__device__ __forceinline__ void pv_steps(float (&e)[3][4], uint32_t alo, uint32_t blo, int acc) {
    wgmma_n8<1, 0, 0>(e[0], alo, blo, acc); wgmma_n8<1, 1024, 0>(e[1], alo, blo, acc); wgmma_n8<1, 2048, 0>(e[2], alo, blo, acc);
    wgmma_n8<1, 6144, 32>(e[0], alo, blo, 1); wgmma_n8<1, 7168, 32>(e[1], alo, blo, 1); wgmma_n8<1, 8192, 32>(e[2], alo, blo, 1);
}
__device__ __forceinline__ void wg_fence() { asm volatile("wgmma.fence.sync.aligned;" ::: "memory"); }
__device__ __forceinline__ void wg_commit() { asm volatile("wgmma.commit_group.sync.aligned;" ::: "memory"); }
template <int N> __device__ __forceinline__ void wg_wait() { asm volatile("wgmma.wait_group.sync.aligned %0;" ::"n"(N) : "memory"); }
__device__ __forceinline__ void acc_ready(float (&d)[4]) { asm volatile("" : "+f"(d[0]), "+f"(d[1]), "+f"(d[2]), "+f"(d[3]) :: "memory"); }
__device__ __forceinline__ uint32_t score_pair(float (&d)[4]) {
    acc_ready(d);
    const uint32_t r = pack2(d[0], d[2]);
    return pack2(bf_lo(r) * SCALE, bf_hi(r) * SCALE);
}

__device__ __forceinline__ void attention_role(const Params& p, int w, int lane) {
    const int cta = blockIdx.x, t4 = lane & 3, g = lane >> 2;
    mbar_wait(bar_at(B_EP), 0);
    const uint32_t tag0 = lds32(SM_EPOCH) * NB;
    const char* const odst = p.scr + SCR_O + head_off(cta >> 2) + (2 * w + (g >> 2)) * 256 + (cta & 3) * 64 + (g & 3) * 16;
    const uint32_t pdst = SM_P + ((t4 + 3) & 3) * PSTR + (16 * w + g) * 2;
    auto softmax = [&](uint32_t& sc, int ps) -> uint32_t {
        const float s0 = bf_lo(sc), s1 = bf_hi(sc);
        int key = __float_as_int(fmaxf(s0, s1));
        key ^= (key >> 31) & 0x7fffffff;
        key = __reduce_max_sync(0xffffffffu, key);
        sts32(SM_MAX + w * 4, key);
        bar_sync<4, 128>();
        const uint4 mx = lds128(SM_MAX);
        key = max(max((int)mx.x, (int)mx.y), max((int)mx.z, (int)mx.w));
        key ^= (key >> 31) & 0x7fffffff;
        const float mb = __int_as_float(key) * LOG2E;
        const uint32_t pp = pack2(fast_ex2(fmaf(s0, LOG2E, -mb)), fast_ex2(fmaf(s1, LOG2E, -mb)));
        sts16(pdst + ps * 4 * PSTR, pp); sts16(pdst + ps * 4 * PSTR + 16, pp >> 16);
        fence_async();
        bar_sync<4, 128>();
        sc = pp;
        return key;
    };
    auto put_sum = [&](uint32_t pp, int ps) {
        uint32_t fs;
        asm volatile("redux.sync.add.u32 %0, %1, 0xffffffff;" : "=r"(fs) : "r"(__float2uint_rn((bf_lo(pp) + bf_hi(pp)) * 8388608.f)) : "memory");
        sts32(SM_SUM + ps * 16 + w * 4, fs);
    };
    auto aux_word = [&](uint32_t mx, const uint4& u, int k) {
        const float l = __uint2float_rn((u.x + u.y) + (u.z + u.w)) * (1.f / 8388608.f);
        return (g < 4 ? mx : (__float_as_uint(l) + 0x80u) & 0xffffff00u) | ((tag0 + k) & 0x7fu) | 0x80u;
    };
    auto send = [&](float (&e)[3][4], uint32_t aux, int ps) {
        acc_ready(e[0]); acc_ready(e[1]); acc_ready(e[2]);
        const uint32_t o0 = pack2(e[0][0], e[0][2]), o1 = pack2(e[1][0], e[1][2]), o2 = pack2(e[2][0], e[2][2]);
        st_pkt2_if(t4 == 0, odst + ps * 2048, o0, o1, o2, aux);
        mbar_arrive_if(lane == 0, bar_at(ps ? B_RV : B_PS));
    };
    mbar_wait(bar_at(B_QR), 0);
    TRACES(73);
#pragma unroll 1
    for (int it = 0; it <= NB; it++) {
        uint32_t m1 = 0;
        if (it < NB) {
            const uint32_t tab = slots(it);
            const uint32_t ka = SB + (2 * w + ((lane >> 3) & 1)) * 3072 + (lane & 7) * 128 + (((lane >> 4) ^ (lane & 7)) << 4);
            const uint32_t qa = SM_Q + it * 384 + (lane >> 3) * 16;
            uint32_t sc = 0;
#pragma unroll 1
            for (int u = 0; u < 4; u++) {
                const uint32_t base = ka + slot_at(tab, pass_nibble(it, u)) * PAIR;
                mbar_wait(bar_at(B_F1 + 2 * u + (w >> 1)), it & 1);
                float d0[4] = {}, d1[4] = {};
#pragma unroll
                for (int c = 0; c < 6; c++) {
                    uint32_t a0[4], a1[4], b[4];
                    ldsm4(b, qa + c * 64);
                    ldsm4(a0, (base ^ ((c & 1) * 64)) + (c >> 1) * 1024);
                    ldsm4(a1, (base ^ ((c & 1) * 64 + 32)) + (c >> 1) * 1024);
                    mma16816(d0, a0[0], a0[1], a0[2], a0[3], b[0], b[1]);
                    mma16816(d1, a1[0], a1[1], a1[2], a1[3], b[2], b[3]);
                }
                const uint32_t r = pack2(d0[0] + d1[0], d0[2] + d1[2]);
                mbar_arrive_if(lane == 0, bar_at(B_RR + 2 * u + (w >> 1)));
                if (t4 == ((u + 1) & 3)) sc = pack2(bf_lo(r) * SCALE, bf_hi(r) * SCALE);
            }
            m1 = softmax(sc, 0);
            put_sum(sc, 0);
        }
        if (it > 0) {
            const int k = it - 1;
            const uint32_t tab = slots(k);
            const uint32_t v0 = slot_at(tab, k < NB - 1 ? 0 : 4);
            TRACES(48 + k * 6);
            if (k > 0) mbar_wait(bar_at(B_F3), it & 1);
            mbar_wait(bar_at(B_QR), it & 1);
            fence_async();
            TRACES(49 + k * 6);
            float d[4][4] = {};
            const bool busy = k < NB - 1;
#pragma unroll
            for (int u = 0; u < 4; u++) {
                const uint32_t alo = desc_lo(SB) + slot_at(tab, u) * (PAIR >> 4), blo = desc_lo(SM_Q + 4 * 384);
                wg_fence();
                qk_steps<0, 6>(d[u], alo, blo);
                wg_commit();
                if (busy) {
                    wg_wait<1>();
                    if (u > 0) mbar_arrive_if(lane == 0, bar_at(B_RK + u - 1));
                }
                wg_fence();
                qk_steps<6, 12>(d[u], alo, blo);
                wg_commit();
                if (u < 3 && busy) wg_wait<1>();
            }
            wg_wait<2>();
            uint32_t sc = shi(score_pair(d[0]), lane & 28), s = shi(score_pair(d[1]), lane & 28);
            if (t4 == 2) sc = s;
            s = shi(score_pair(d[2]), lane & 28);
            if (t4 == 3) sc = s;
            wg_wait<0>();
            s = score_pair(d[3]);
            if (t4 == 0) sc = s;
            mbar_arrive_if(lane == 0, bar_at(B_RK + 3));
            TRACES(50 + k * 6);
            const uint32_t m2 = softmax(sc, 1);
            TRACES(51 + k * 6);
            float e[3][4] = {};
#pragma unroll
            for (int t = 0; t < 8; t++) {
                const int pr = ((t >> 1) + 1) & 3;
                if (t == 6 && k < NB - 1) mbar_wait(bar_at(B_FL), k & 1);
                wg_fence();
                pv_steps(e, desc_lo(SB + (t & 1) * TILE) + (pr ? slot_at(tab, 4 + pr) : v0) * (PAIR >> 4), desc_lo(SM_P + (4 + pr) * PSTR + (t & 1) * 64), t > 0);
                wg_commit();
                if (t < 7 && busy) wg_wait<1>();
                if (t == 1) put_sum(sc, 1);
            }
            bar_sync<4, 128>();
            const uint32_t aux = opaque(aux_word(m2, lds128(SM_SUM + 16), k));
            wg_wait<0>();
            send(e, aux, 1);
            TRACES(52 + k * 6);
        }
        if (it < NB) {
            const uint32_t tab = slots(it);
            if (it == 0) st_pkt2_if(t4 == 0, odst, 0, 0, 0, 0);
            bar_sync<4, 128>();
            const uint32_t aux = opaque(aux_word(m1, lds128(SM_SUM), it));
            float e[3][4] = {};
#pragma unroll 1
            for (int u = 0; u < 4; u++) {
                const uint32_t alo = desc_lo(SB) + slot_at(tab, 4 + u) * (PAIR >> 4), blo = desc_lo(SM_P) + u * (PSTR >> 4);
                mbar_wait(bar_at(B_F1 + 8 + 2 * u), it & 1);
                wg_fence();
                pv_steps(e, alo, blo, u > 0);
                wg_commit();
                wg_wait<1>();
                if (u == 1) mbar_arrive_if(lane == 0, bar_at(B_RP));
                mbar_wait(bar_at(B_F1 + 9 + 2 * u), it & 1);
                wg_fence();
                pv_steps(e, alo + (TILE >> 4), blo + 4, 1);
                wg_commit();
                wg_wait<1>();
            }
            wg_wait<0>();
            send(e, aux, 0);
            TRACES(53 + it * 6);
        }
    }
}

__device__ __forceinline__ void ln_finish(float s, float q, float& mean_b, float& rden) {
    const float mean = s * (1.f / DM);
    const float var = fmaxf(fmaf(q, 1.f / DM, -mean * mean), 0.f);
    mean_b = bfr(mean);
    rden = fast_rcp(bfr(fast_sqrt(bfr(bfr(var) + 1e-5f))));
}
__device__ __forceinline__ uint32_t ln_apply(uint32_t w, float mean_b, float rden) {
    const uint32_t d = bsub2(w, __byte_perm(__float_as_uint(mean_b), 0, 0x3232));
    return pack2(bf_lo(d) * rden, bf_hi(d) * rden);
}
__device__ __forceinline__ void put_x(uint32_t x01, uint32_t x2, uint32_t wa, bool e2) {
    jitter();
    sts16(wa, x01); sts16(wa + 8, x01 >> 16);
    sts16_if(!e2, wa + 16, x2);
}
__device__ __forceinline__ void get_x(uint32_t (&b)[10], uint32_t ra) {
    __syncwarp();
    const uint4 u = lds128(ra), v = lds128(ra + 16);
    const uint2 z = lds64(ra + 32);
    b[0] = u.x; b[1] = u.y; b[2] = u.z; b[3] = u.w; b[4] = v.x; b[5] = v.y; b[6] = v.z; b[7] = v.w; b[8] = z.x; b[9] = z.y;
}
__device__ __forceinline__ float fold(float a, float b, bool sel, int m) { return (sel ? b : a) + shx(sel ? a : b, m); }

__device__ __forceinline__ void chain_role(const Params& p, int w, int lane) {
    const int cta = blockIdx.x, h = cta >> 2, s = cta & 3;
    const int g = lane >> 2, t4 = lane & 3;
    const bool e1 = t4 & 1, e2 = t4 & 2;
    uint32_t wq[5][3][4], wo[3][5][4], wg[5][4], wh[5][2], wd[4][4];
    const int col0 = 80 * w + (e2 ? 48 : 0) + g + (e1 ? 8 : 0);
    const uint32_t xw = opaque(SM_X + w * 384 + 48 * (g >> 1) + (e2 ? 24 : 0) + (e1 ? 4 : 0) + 2 * (g & 1));
    const uint32_t xr = opaque(g == 1 ? SM_ONES : SM_X + w * 384 + (g == 3 ? 192 : 0) + 48 * t4);
    TRACES(75);
    sts32_if(lane < 12, SM_ONES + lane * 4, 0x3f803f80u);
    uint32_t zero = lane >> 5;
    const int mi = lane >> 3, mr = lane & 7;
    mbar_wait(bar_at(B_W), 0);
    TRACES(74);
    sts16(xw + 192, lds16(ST_X + 5120 + col0 * 2)); sts16(xw + 200, lds16(ST_X + 5120 + col0 * 2 + 32));
    sts16_if(!e2, xw + 208, lds16(ST_X + 5120 + col0 * 2 + 64));
#pragma unroll
    for (int i = 0; i < 5; i++)
#pragma unroll
        for (int mt = 0; mt < 3; mt++) ldsm4t(wq[i][mt], ST_WQ + (80 * w + 16 * i + mr + 8 * (mi >> 1)) * 96 + 32 * mt + 16 * (mi & 1), zero);
    const bool odd = cta & 1;
    const uint32_t lo = ST_WD + (mr + (odd ? 4 : 0)) * 1280 + 160 * w + 16 * (mi & 1);
    const uint32_t hi = ST_WD + ((mr & 3) + (odd ? 0 : 8)) * 1280 + 160 * w + 16 * (mi & 1);
    ldsm4t(wd[0], lo + 96 * (mi >> 1), zero);
    ldsm4t(wd[1], lo + 96 * (mi >> 1) + 32, zero);
    ldsm4t(wd[2], (mi < 2 ? lo : hi) + 64, zero);
    ldsm4t(wd[3], hi + 32 * (mi >> 1) + 96 * (mr >> 2), zero);
    fence_async();
    __syncwarp();
    mbar_arrive_if(lane == 0, bar_at(B_WC));
    mbar_wait(bar_at(B_EP), 0);
    const uint32_t near = __shfl_sync(0xffffffffu, near_half(), 0);
    uint32_t x01 = 0, x2 = 0, nx01 = 0, nx2 = 0;
#pragma unroll 1
    for (int n = -5; n < NROUND; n++) {
        const bool last = (ORD_LAST >> (n & 15)) & 1, head = !((ORD_NO_HEAD >> (n & 15)) & 1);
        const int k = (ORD_BATCH >> (2 * (n & 15))) & 3;
        if (n > -5 && n <= 0) bar_sync<7, 288>();
        else if (!last) bar_sync<2, 256>();
        TRACES(n <= 0 ? 83 + n : 95);
        const char* const slice = p.scr + acc_off(k, last, w);
        const char* const cell = opaque(slice + g * 256 + t4 * 16);
        if (n < -1) {
            const uint32_t xa = ST_X + (n + 5) * 1280, ln = opaque(lane);
            const int col0 = 80 * w + (ln & 2 ? 48 : 0) + (ln >> 2) + (ln & 1 ? 8 : 0);
            float sm = 0.f, sq = 0.f;
#pragma unroll
            for (int i = 0; i < 5; i++) {
                const uint2 c = lds64(xa + i * 256 + ln * 8);
                sm += (bf_lo(c.x) + bf_hi(c.x)) + (bf_lo(c.y) + bf_hi(c.y));
                sq = fmaf(bf_lo(c.x), bf_lo(c.x), fmaf(bf_hi(c.x), bf_hi(c.x), fmaf(bf_lo(c.y), bf_lo(c.y), fmaf(bf_hi(c.y), bf_hi(c.y), sq))));
            }
            x01 = lds16(xa + col0 * 2) | lds16(xa + col0 * 2 + 32) << 16;
            x2 = lds16(xa + col0 * 2 + 64);
#pragma unroll
            for (int o = 16; o; o >>= 1) { sm += shx(sm, o); sq += shx(sq, o); }
            float mean_b, rden;
            ln_finish(sm, sq, mean_b, rden);
            x01 = ln_apply(x01, mean_b, rden);
            x2 = ln_apply(x2, mean_b, rden);
            put_x(x01, x2, xw, e2);
        } else {
            if (n >= 0 && head) {
                if (!last || n == NROUND - 1) mbar_wait(bar_at(B_Z), (k + last) & 1);
                const char* src = p.scr + SCR_O + head_off(h) + head_near(h, near) + last * 2048 + (w & 6) * 256 + (lane & 15) * 16;
                const uint32_t tag = (lds32(SM_EPOCH) * NB + k) | 0x80u;
                mbar_wait(bar_at(last ? B_RV : B_PS), k & 1);
                uint4 v, z;
                {
                    SPIN_DECL;
                    do {
                        v = ld_pkt(src); z = ld_pkt(src + 256);
                        SPIN_CHECK(n);
                    } while (__any_sync(0xffffffffu, (((v.w ^ tag) | (z.w ^ tag)) & 0xffu) != 0));
                }
                TRACES(tr + 0);
                float a[3][4] = {};
                const uint32_t bb[3][2] = {{v.x, v.y}, {z.x, z.y}, {v.z, z.z}};
                float sa, sb, rl;
#pragma unroll
                for (int i = 0; i < 3; i++) {
                    const uint32_t l0 = g < 4 ? bb[i][0] : 0, l1 = g < 4 ? bb[i][1] : 0, h0 = g < 4 ? 0 : bb[i][0], h1 = g < 4 ? 0 : bb[i][1];
#pragma unroll
                    for (int mt = 0; mt < 5; mt++)
                        mma16816(a[mt % 3], wo[i][mt][0], wo[i][mt][1], wo[i][mt][2], wo[i][mt][3], mt < 3 ? l0 : h0, mt < 3 ? l1 : h1);
                    if (i == 0) {
                        int key = v.w & 0xffffff00u;
                        key ^= (key >> 31) & 0x7fffffff;
                        key = __reduce_max_sync(0xffffffffu, key);
                        key ^= (key >> 31) & 0x7fffffff;
                        const float ws = fast_ex2((F(v.w & 0xffffff00u) - __int_as_float(key)) * LOG2E);
                        sa = shi(ws, e1 ? 8 : 0); sb = shi(ws, e1 ? 12 : 4);
                        rl = ws * F(z.w & 0xffffff00u);
                        rl += shx(rl, 4);
                    }
                    if (i == 1) rl += shx(rl, 8);
                }
                float y[3];
#pragma unroll
                for (int j = 2; j < 5; j++) {
                    const int mt = j % 3;
                    y[mt] = fold(fmaf(a[mt][0], sa, a[mt][1] * sb), fmaf(a[mt][2], sa, a[mt][3] * sb), e1, 1);
                }
                const uint32_t pa = SM_PO + w * 512 + lane * 16;
                if (w < 2) {
                    const char* dst = opaque(cell + s * 16384);
                    rl = fast_rcp(rl);
                    bar_sync<1, 256>();
                    const uint4 c1 = lds128(pa), c2 = lds128(pa + 1024), c3 = lds128(pa + 2048);
                    red_cell2_if(true, dst, ((y[0] + F(c1.x)) + (F(c2.x) + F(c3.x))) * rl, ((y[1] + F(c1.y)) + (F(c2.y) + F(c3.y))) * rl,
                                 ((y[2] + F(c1.z)) + (F(c2.z) + F(c3.z))) * rl);
                } else {
                    stsf4(pa - 1024, y[0], y[1], y[2], 0.f);
                    bar_sync<1, 256>();
                }
                TRACES(tr + 1);
                if ((ORD_NO_TAIL >> n) & 1) continue;
                const uint32_t tsend = clk32();
                if (n == 0) {
                    st_pkt2_if(lane < 4, p.scr + SCR_O + head_off(h) + 2048 + w * 256 + s * 64 + lane * 16, 0, 0, 0, 0);
                    __syncwarp();
                } else if (!last) {
                    const char* nsrc = p.scr + acc_off(k - 1, 1, w) + near + g * 256 + t4 * 16;
                    SPIN_DECL;
                    do {
                        v = ld_pkt(nsrc);
                        SPIN_CHECK(n);
                        nx01 = pack2(F(v.x), F(v.y)); nx2 = pack2(F(v.z), 0.f);
                    } while (__any_sync(0xffffffffu, v.w != FULL_A));
                }
                wait_clk(tsend + (w < 2 ? 0 : 60) + (n < QUIET ? CFG(DLY_AL) : CFG(DLY_A)));
                {
                    SPIN_DECL;
                    do {
                        v = ld_pkt(cell + near);
                        SPIN_CHECK(n);
                        x01 = pack2(F(v.x), F(v.y));
                        x2 = pack2(F(v.z), 0.f);
                        put_x(x01, x2, xw, e2);
                    } while (__any_sync(0xffffffffu, v.w != FULL_A));
                }
                TRACES(tr + 2);
            } else if (n >= 0) {
                x01 = nx01; x2 = nx2;
                put_x(x01, x2, xw, e2);
            } else {
                mbar_wait(bar_at(B_W + 1), 0);
                const uint32_t ln = opaque(lane);
                const int mi = ln >> 3, mr = ln & 7;
                uint32_t zero = ln >> 5;
                TRACES(76);
#pragma unroll
                for (int i = 0; i < 3; i++) {
                    const int d = 16 * (w >> 1) + (mr >> 1) + 8 * (mr & 1) + (i < 2 ? 64 * (mi >> 1) + 4 * i : 128 + 4 * (mi >> 1));
#pragma unroll
                    for (int mt = 0; mt < 5; mt++) ldsm4t(wo[i][mt], ST_WO + d * 320 + 160 * (w & 1) + 32 * mt + 16 * (mi & 1), zero);
                }
                fence_async();
                __syncwarp();
                mbar_arrive_if(lane == 0, bar_at(B_WC + 1));
                mbar_wait(bar_at(B_W + 2), 0);
                TRACES(77);
#pragma unroll
                for (int i = 0; i < 5; i++) {
                    const uint32_t ga = ST_WG + (mi & 1) * 20480 + (80 * w + 16 * i + mr + 8 * (mi >> 1)) * 32;
                    uint32_t r[4];
                    ldsm4t(wg[i], ga + (odd ? 16 : 0), zero);
                    ldsm4t(r, ga + (odd ? 0 : 16), zero);
#pragma unroll
                    for (int kh = 0; kh < 2; kh++) {
                        const uint32_t moved = __shfl_xor_sync(0xffffffffu, odd ? r[2 * kh] : r[2 * kh + 1], 16);
                        wh[i][kh] = (g < 4) == odd ? moved : odd ? r[2 * kh + 1] : r[2 * kh];
                    }
                }
                fence_async();
                __syncwarp();
                mbar_arrive_if(lane == 0, bar_at(B_WC + 2));
                TRACES(72);
                x01 = 0x3f803f80u; x2 = 0x3f80u;
                put_x(x01, x2, xw, e2);
            }
            uint32_t b[10];
            get_x(b, xr);
            float a[2][4] = {};
#pragma unroll
            for (int i = 0; i < 5; i++) {
                mma16816(a[0], wg[i][0], wg[i][1], wg[i][2], wg[i][3], b[2 * i], b[2 * i + 1]);
                mma16816(a[1], wh[i][0], b[2 * i], wh[i][1], b[2 * i + 1], b[2 * i], b[2 * i + 1]);
            }
            stsf(SM_PG + (w >> 2) * 512 + (g + 8 * t4) * 16 + (w & 3) * 4, e2 ? (e1 ? a[1][2] : a[1][0]) : (e1 ? a[0][2] : a[0][0]));
            const uint2 cs = lds64(SM_CSG + lane * 48);
            const char* dst = opaque(cell + 3 * HALF - near);
            bar_sync<2, 256>();
            const float S = sum8(lds128(SM_PG + lane * 16), lds128(SM_PG + 512 + lane * 16));
            const float sx = shi(S, 25), sq = shi(S, 24), Su = shi(S, lane + (lane < 16 ? 8 : 4));
            if (n < 0) {
                if (w == 0) stsf2(SM_CSG + lane * 48, S, Su);
            } else {
                float mean_b, rden;
                ln_fast(sx, sq, mean_b, rden);
                const float gv = bfr(fmaf(-mean_b, F(cs.x), S) * rden), uv = bfr(fmaf(-mean_b, F(cs.y), Su) * rden);
                const float sg = fast_rcp(1.f + fast_ex2(-LOG2E * gv));
                const uint32_t hb = pack2(bfr(gv * sg) * uv, 0.f);
                const uint32_t b0 = __byte_perm(shi(hb, 2 * t4), shi(hb, 2 * t4 + 1), 0x5410);
                const uint32_t b1 = __byte_perm(shi(hb, e1 ? 18 : 16), shi(hb, e1 ? 19 : 17), 0x5410);
                const bool up = g >= 4;
                const uint32_t l0 = up ? 0 : b0, h0 = up ? b0 : 0;
                const uint32_t m1 = up == e2 ? b1 : 0;
                float d[3][4] = {};
                mma16816(d[0], wd[0][0], wd[0][1], wd[0][2], wd[0][3], l0, h0);
                mma16816(d[1], wd[1][0], wd[1][1], wd[1][2], wd[1][3], l0, h0);
                mma16816(d[2], wd[2][0], wd[2][1], wd[2][2], wd[2][3], l0, up ? 0 : m1);
                mma1688(d[0], wd[3][0], wd[3][1], m1);
                mma1688(d[1], wd[3][2], wd[3][3], m1);
                red_cell(dst, e1 ? d[0][2] : d[0][0], e1 ? d[1][2] : d[1][0], e1 ? d[2][2] : d[2][0]);
                const uint32_t tsend = clk32();
                TRACES(tr + 3);
                if (last && w != cta >> 4) continue;
                const float sgr = shi(sg, 27);
                const uint32_t sg2 = pack2(sgr, sgr);
                const uint32_t n01 = opaque(pack2((bf_lo(x01) - mean_b) * rden, (bf_hi(x01) - mean_b) * rden));
                const uint32_t n2 = opaque(pack2((bf_lo(x2) - mean_b) * rden, 0.f));
                if (last) {
                    sts128_if(lane >> 1 == (cta & 15), SM_FIN + (lane & 1) * 16, x01, n01, __byte_perm(x2, n2, 0x5410), sg2);
                    mbar_arrive_if(lane >> 1 == (cta & 15), bar_at(B_FIN));
                    __syncwarp();
                    continue;
                }
                wait_clk(tsend + (n < QUIET ? CFG(DLY_BL) : CFG(DLY_B)));
                const uint32_t r01 = x01, r2 = x2;
                float cnt;
                SPIN_DECL;
                do {
                    const uint4 v = ld_pkt(cell + 2 * HALF), z = ld_pkt(cell + 3 * HALF);
                    SPIN_CHECK(n);
                    cnt = F(v.w) + F(z.w);
                    x01 = badd2(r01, badd2(n01, bmul2(pack2(F(v.x) + F(z.x), F(v.y) + F(z.y)), sg2)));
                    x2 = badd2(r2, badd2(n2, bmul2(pack2(F(v.z) + F(z.z), 0.f), sg2)));
                    put_x(x01, x2, xw, e2);
                } while (__any_sync(0xffffffffu, cnt != NCTA));
                TRACES(tr + 4);
            }
        }
        {
            uint32_t b[10];
            get_x(b, xr);
            float a[3][4] = {};
            const float f0 = bf_lo(x01), f1 = bf_hi(x01), f2 = e2 ? 0.f : bf_lo(x2);
            float st;
#pragma unroll
            for (int i = 0; i < 5; i++) {
#pragma unroll
                for (int mt = 0; mt < 3; mt++) {
                    mma16816(a[mt], wq[i][mt][0], wq[i][mt][1], wq[i][mt][2], wq[i][mt][3], b[2 * i], b[2 * i + 1]);
                    if (i == 0 && mt == 0) st = fold(fmaf(f0, f0, fmaf(f1, f1, f2 * f2)), (f0 + f1) + f2, g & 1, 4);
                }
                if (i < 4) st += shx(st, i < 2 ? 1 << i : 2 << i);
            }
            const uint32_t pa = SM_PQ + (w >> 2) * 1024 + (g & 1) * 512 + ((e2 ? 16 : 0) + (e1 ? 4 : 0) + (g >> 1)) * 16 + (w & 3) * 4;
            stsf(pa + 128, e2 ? st : e1 ? a[1][2] : a[1][0]);
            stsf(pa, e2 ? (e1 ? a[2][2] : a[2][0]) : (e1 ? a[0][2] : a[0][0]));
            bar_sync<3, 288>();
            if (n >= 0 && w == cta >> 4) {
                red_cell2_if(lane >> 1 == (cta & 15), cell + (acc_off(k, 1, 0) - acc_off(k, 0, 0)), f0, f1, f2);
                __syncwarp();
            }
        }
    }
}

__host__ __device__ constexpr int bar_count(int i) {
    return i < 16 ? 1 : i < B_RR ? 0 : i < B_RK ? 2 : i <= B_RV ? 4 : i == B_Z ? 1 : i == B_EP ? 9 : i < B_WC ? 0 : i < B_FIN ? 8 :
           i == B_FIN ? 2 : i == B_PS || i == B_RP ? 4 : i == B_QR ? 32 : 1;
}
template <int I, int END> __device__ __forceinline__ void init_bars() {
    if constexpr (I < END) {
        if (bar_count(I)) mbar_init(bar_at(I), bar_count(I));
        init_bars<I + 1, END>();
    }
}
template <int ID> __device__ __forceinline__ void role_exit() { asm volatile("exit; // %0" ::"n"(ID)); }
constexpr int NTHREADS = 512;
#define STR2(x) #x
#define STR(x) STR2(x)
__global__ void __launch_bounds__(NTHREADS, 1)
decode_kernel(const Params p, const __grid_constant__ Maps tm) {
    extern __shared__ __align__(1024) unsigned char smem[];
    if (threadIdx.x == 0) l2_prefetch(p.wq + (size_t)blockIdx.x * 12288, 12288);
    const uint32_t t0 = now_ns() - CFG(LEAD);
    const int lane = threadIdx.x & 31;
    const int warp = __reduce_max_sync(0xffffffffu, threadIdx.x >> 5);
    if (warp < 8) {
        asm volatile("setmaxnreg.inc.sync.aligned.u32 " STR(CFG_REG_CHAIN) ";");
        bar_arrive<5, 480>();
        const uint32_t vote = probe_near(p, warp, lane);
        bar_sync<2, 256 + 32>();
        sts32(SM_NEAR + warp * 4, vote);
        mbar_arrive_if(lane == 0, bar_at(B_EP));
        chain_role(p, warp, __shfl_sync(0xffffffffu, lane, lane));
        role_exit<3>();
    } else if (warp < 12) {
        asm volatile("setmaxnreg.dec.sync.aligned.u32 " STR(CFG_REG_ATT) ";");
        if (elect_one()) {
            if (warp == 8) init_bars<0, 12>();
            else if (warp == 9) init_bars<12, 30>();
            else if (warp == 10) init_bars<30, 42>();
            else init_bars<42, NBAR>();
            asm volatile("fence.mbarrier_init.release.cluster;" ::: "memory");
            fence_async();
        }
        if (warp == 8) TRACE(236);
        bar_sync<5, 480>();
        if (warp == 8) TRACE(237);
        attention_role(p, warp - 8, lane);
        role_exit<2>();
    } else {
        asm volatile("setmaxnreg.dec.sync.aligned.u32 " STR(CFG_REG_HELP) ";");
        if (warp == 12) {
            load_role(p, &tm.k, lane, t0);
            role_exit<0>();
        } else {
            if (warp == 14) {
                if (smem_u32(smem) != SB) __trap();
                if (elect_one()) {
                    asm volatile("prefetch.tensormap [%0];" ::"l"(&tm.q) : "memory");
                    mbar_init(bar_at(B_W), 1); mbar_init(bar_at(B_W + 1), 1); mbar_init(bar_at(B_W + 2), 1);
                    asm volatile("fence.mbarrier_init.release.cluster;" ::: "memory");
                    fence_async();
                    mbar_expect_tx(bar_at(B_W), 61440 + 15360 + 6400); mbar_expect_tx(bar_at(B_W + 1), 61440); mbar_expect_tx(bar_at(B_W + 2), 40960);
                    bulk_load(ST_X, p.x, 5120, bar_at(B_W));
                    bulk_load(ST_X + 5120, p.wr, 1280, bar_at(B_W));
                }
                TRACE(238);
                reload_role(p, &tm, t0);
            } else {
                if (warp == 13 && elect_one()) {
                    asm volatile("prefetch.tensormap [%0];" ::"l"(&tm.g) : "memory");
                    asm volatile("prefetch.tensormap [%0];" ::"l"(&tm.u) : "memory");
                    asm volatile("prefetch.tensormap [%0];" ::"l"(&tm.o) : "memory");
                    asm volatile("prefetch.tensormap [%0];" ::"l"(&tm.k) : "memory");
                    asm volatile("prefetch.tensormap [%0];" ::"l"(&tm.v) : "memory");
                }
                TRACE(233 + warp);
                bar_sync<5, 480>();
                if (warp == 13) { bar_arrive<6, 64>(); q_role(p, lane); }
                else { bar_arrive<2, 256 + 32>(); zero_role(p, lane, t0); }
            }
            role_exit<1>();
        }
    }
}

typedef CUresult (*EncodeFn)(CUtensorMap*, CUtensorMapDataType, cuuint32_t, void*, const cuuint64_t*, const cuuint64_t*,
                             const cuuint32_t*, const cuuint32_t*, CUtensorMapInterleave, CUtensorMapSwizzle,
                             CUtensorMapL2promotion, CUtensorMapFloatOOBfill);

bool make_map(EncodeFn fn, CUtensorMap* m, const void* ptr, uint64_t cols, uint64_t rows, uint32_t bc, uint32_t br) {
    cuuint64_t dims[2] = {cols, rows};
    cuuint64_t strides[1] = {cols * 2};
    cuuint32_t box[2] = {bc, br};
    cuuint32_t es[2] = {1, 1};
    return fn(m, CU_TENSOR_MAP_DATA_TYPE_BFLOAT16, 2, const_cast<void*>(ptr), dims, strides, box, es, CU_TENSOR_MAP_INTERLEAVE_NONE,
              CU_TENSOR_MAP_SWIZZLE_NONE, CU_TENSOR_MAP_L2_PROMOTION_L2_128B, CU_TENSOR_MAP_FLOAT_OOB_FILL_NONE) == CUDA_SUCCESS;
}

bool make_kv_map(EncodeFn fn, CUtensorMap* m, const void* ptr) {
    cuuint64_t dims[4] = {64, 8, 3, (cuuint64_t)NB * NHEAD * SK / 8};
    cuuint64_t strides[3] = {DH * 2, 128, 8 * DH * 2};
    cuuint32_t box[4] = {64, 8, 3, 4};
    cuuint32_t es[4] = {1, 1, 1, 1};
    return fn(m, CU_TENSOR_MAP_DATA_TYPE_BFLOAT16, 4, const_cast<void*>(ptr), dims, strides, box, es, CU_TENSOR_MAP_INTERLEAVE_NONE,
              CU_TENSOR_MAP_SWIZZLE_128B, CU_TENSOR_MAP_L2_PROMOTION_L2_128B, CU_TENSOR_MAP_FLOAT_OOB_FILL_NONE) == CUDA_SUCCESS;
}

}

extern "C" void kernel_launch(void* const* d_in, const int* in_sizes, int n_in, void* d_out, int out_size) {
    (void)in_sizes; (void)n_in; (void)out_size;
    static EncodeFn fn = nullptr;
    static const char* scr = nullptr;
    if (!fn) {
        void* f = nullptr;
        cudaDriverEntryPointQueryResult qr;
        if (cudaGetDriverEntryPoint("cuTensorMapEncodeTiled", &f, cudaEnableDefault, &qr) != cudaSuccess || !f) return;
        void* sp = nullptr;
        if (cudaGetSymbolAddress(&sp, g_scratch) != cudaSuccess) return;
        scr = (const char*)(((uintptr_t)sp + (2 << 20) - 1) & ~(uintptr_t)((2 << 20) - 1));
        fn = (EncodeFn)f;
        cudaFuncSetAttribute(decode_kernel, cudaFuncAttributeMaxDynamicSharedMemorySize, SMEM_BYTES);
    }
    Maps tm;
    if (!make_kv_map(fn, &tm.k, d_in[1]) || !make_kv_map(fn, &tm.v, d_in[2])) return;
    if (!make_map(fn, &tm.q, d_in[3], NHEAD * DH, DM, 48, 128) || !make_map(fn, &tm.o, d_in[4], DM, NHEAD * DH, 160, 32)) return;
    if (!make_map(fn, &tm.g, d_in[7], FF, DM, 16, 128) || !make_map(fn, &tm.u, d_in[8], FF, DM, 16, 128)) return;
    Params p;
    p.x = (const unsigned short*)d_in[0];
    p.wq = (const char*)d_in[3];
    p.wo = (const char*)d_in[4];
    p.wr = (const unsigned short*)d_in[6];
    p.wg = (const char*)d_in[7];
    p.wu = (const char*)d_in[8];
    p.wd = (const char*)d_in[9];
    p.out = (unsigned short*)d_out;
    p.scr = scr;
    decode_kernel<<<NCTA, NTHREADS, SMEM_BYTES>>>(p, tm);
}
```

```cpp
#include <cuda_runtime.h>
#include <cuda_bf16.h>
#include <cuda.h>
#include <stdint.h>

namespace {

constexpr int NB = 4, DM = 640, NHEAD = 32, DH = 192, SK = 4096, WIN = 1024, FF = 1536;
constexpr int NCTA = 128;
constexpr int TILE = 12288, PAIR = 2 * TILE;

#define CFG_LIST(X) \
    X(TICK0, 479)        \
    X(TICK, 495)        \
    X(LEAD, 600)        \
    X(STAG, 500)        \
    X(WLAG, 350)        \
    X(GSTEP, 750)        \
    X(WIN, 5)        \
    X(PMAX, 2)        \
    X(PGRACE, 50)        \
    X(LMAX0, 150)        \
    X(LMAX, 160) \
    X(GAIN, 5)        \
    X(VSTEP, 150)        \
    X(RSTEP, 670)        \
    X(RSTEP3, 450) \
    X(ZTILE, 11)        \
    X(DLY_A, 410)        \
    X(DLY_AL, 100) \
    X(DLY_B, 570) \
    X(DLY_BL, 950) \
    X(DLY_F, 290) \
    X(ILV, 1) \
    X(FLIP, 0) \

#define X(n, v) constexpr int CFG_##n = v;
CFG_LIST(X)
#undef X
#define CFG(n) CFG_##n
constexpr int QUIET = 8;
#define CFG_REG_CHAIN 216
#define CFG_REG_ATT 48
#define CFG_REG_HELP 32
constexpr int KB_KV0 = 165;
__device__ __forceinline__ int kb_ns(int kb) { return kb * CFG(TICK0) / 12; }
__device__ __forceinline__ int tick_ns(int j) { return j <= 16 ? CFG(TICK0) : CFG(TICK); }
__device__ __forceinline__ int batch_ns(int k) { return kb_ns(KB_KV0) + (k ? 16 * (CFG(TICK0) + (k - 1) * CFG(TICK)) : 0); }

__device__ __forceinline__ uint32_t slots(int k) { return k & 2 ? (k & 1 ? 0x21304768u : 0x76835214u) : (k & 1 ? 0x21480765u : 0x76543210u); }
__device__ __forceinline__ int pass_nibble(int k, int u) { return k > 0 ? 4 + (u & 1) : u; }
__device__ __forceinline__ uint32_t slot_at(uint32_t tab, int u) { return (tab >> (4 * u)) & 15; }

constexpr int NROUND = 11;
constexpr uint32_t ORD_BATCH = 0x3b9910, ORD_LAST = 0x6da, ORD_NO_HEAD = 0x248, ORD_NO_TAIL = 0x092;

constexpr uint32_t SB = 1024;
constexpr uint32_t SM_BAR = SB + 9 * PAIR;
constexpr int B_F1 = 0;
constexpr int B_RR = 24;
constexpr int B_RK = 32;
constexpr int B_RV = 36;
constexpr int B_Z = 37;
constexpr int B_EP = 38;
constexpr int B_W = 39;
constexpr int B_WC = 42;
constexpr int B_FIN = 45;
constexpr int B_F3 = 46;
constexpr int B_PS = 48;
constexpr int B_RP = 49;
constexpr int B_FL = 50;
constexpr int B_QR = 51;
constexpr int NBAR = 52;
__host__ __device__ constexpr uint32_t bar_at(int i) { return SM_BAR + 8 * i; }
constexpr uint32_t SM_EPOCH = SM_BAR + 416;
constexpr uint32_t SM_MAX = SM_EPOCH + 16;
constexpr uint32_t SM_SUM = SM_MAX + 16;
constexpr uint32_t SM_NEAR = SM_SUM + 32;
constexpr uint32_t SM_FIN = SM_NEAR + 32;
constexpr uint32_t SM_Q = SM_FIN + 32;
constexpr uint32_t PSTR = 144;
constexpr uint32_t SM_P = SM_Q + 5 * 384;
constexpr uint32_t SM_X = SM_P + 8 * PSTR;
constexpr uint32_t SM_CSG = SM_X + 40;
constexpr uint32_t SM_ONES = SM_X + 8 * 384;
constexpr uint32_t SM_PG = SM_ONES + 48;
constexpr uint32_t SM_PO = SM_PG + 1024;
constexpr uint32_t SM_PQ = SM_PO;
constexpr int SMEM_BYTES = SM_PO + 3072 - SB;
static_assert(SMEM_BYTES <= 232448 && SM_Q % 16 == 0 && SM_P % 16 == 0 && SM_X % 16 == 0 && SM_PO % 16 == 0, "smem");
constexpr uint32_t ST_WQ = SB, ST_WD = SB + 3 * PAIR, ST_WO = SB + 4 * PAIR, ST_WG = SB + 7 * PAIR, ST_X = ST_WG + 40960;

__device__ unsigned g_epoch;
__device__ unsigned char g_scratch[4 << 20];
constexpr uint32_t HALF = 4096, SCR_O = 1 << 16, SCR_Q = 1 << 17, SCR_COUNT = 3 << 16;
__device__ __forceinline__ uint32_t acc_off(int k, int layer, int w) {
    return (k & 1) << 6 | layer << 7 | (w & 1) << 11 | (w >> 1) << 14 | (k + layer == NB) << 18;
}
__device__ __forceinline__ uint32_t head_off(int h) { return (h & 3) << 14 | (h & 4) << 16 | (h & 8) << 17 | (h & 16) << 9; }
__device__ __forceinline__ uint32_t head_near(int h, uint32_t near) { return near ^ HALF ^ (h & 16) << 8; }
constexpr uint32_t FULL_A = 0x42040000u;

struct Params {
    const char* wq;
    const unsigned short* x;
    const char* wo;
    const unsigned short* wr;
    const char* wg;
    const char* wu;
    const char* wd;
    unsigned short* out;
    const char* scr;
};

__device__ __forceinline__ uint32_t smem_u32(const void* p) { return (uint32_t)__cvta_generic_to_shared(p); }
__device__ __forceinline__ void mbar_init(uint32_t a, uint32_t c) { asm volatile("mbarrier.init.shared::cta.b64 [%0], %1;" ::"r"(a), "r"(c) : "memory"); }
__device__ __forceinline__ void mbar_expect_tx(uint32_t a, uint32_t b) {
    asm volatile("mbarrier.arrive.expect_tx.shared::cta.b64 _, [%0], %1;" ::"r"(a), "r"(b) : "memory");
}
__device__ __forceinline__ void mbar_arrive(uint32_t a) { asm volatile("mbarrier.arrive.shared::cta.b64 _, [%0];" ::"r"(a) : "memory"); }
constexpr uint32_t SPIN_LIMIT = 1u << 22;
#define SPIN_DECL uint32_t spins = 0
#define SPIN_CHECK(info) { if (++spins > SPIN_LIMIT) __trap(); }
__device__ __forceinline__ void jitter() {}
__device__ __forceinline__ void mbar_wait(uint32_t a, uint32_t parity) {
    jitter();
    uint32_t ok;
    SPIN_DECL;
    while (true) {
        asm volatile("{\n.reg .pred p;\nmbarrier.try_wait.parity.shared::cta.b64 p, [%1], %2;\nselp.u32 %0, 1, 0, p;\n}"
                     : "=r"(ok) : "r"(a), "r"(parity) : "memory");
        if (ok) break;
        SPIN_CHECK((a - SM_BAR) / 8 * 10 + parity);
    }
    jitter();
}
__device__ __forceinline__ bool mbar_test2(uint32_t a, uint32_t pa, uint32_t b, uint32_t pb) {
    uint32_t ok;
    asm volatile("{\n.reg .pred p, q;\nmbarrier.test_wait.parity.shared::cta.b64 p, [%1], %2;\n"
                 "mbarrier.test_wait.parity.shared::cta.b64 q, [%3], %4;\nand.pred p, p, q;\nvote.sync.all.pred p, p, 0xffffffff;\nselp.u32 %0, 1, 0, p;\n}"
                 : "=r"(ok) : "r"(a), "r"(pa), "r"(b), "r"(pb) : "memory");
    return ok;
}
__device__ __forceinline__ uint32_t now_ns() { uint32_t t; asm volatile("mov.u32 %0, %%globaltimer_lo;" : "=r"(t) :: "memory"); return t; }
__device__ __forceinline__ uint32_t clk32() { uint32_t c; asm volatile("mov.u32 %0, %%clock;" : "=r"(c) :: "memory"); return c; }
__device__ __forceinline__ void wait_ns(uint32_t t) { jitter(); while ((int)(now_ns() - t) < 0) {} }
__device__ __forceinline__ void wait_clk(uint32_t t) { jitter(); while ((int)(clk32() - t) < 0) {} }
__device__ __forceinline__ bool elect_one() {
    uint32_t e;
    asm volatile("{\n.reg .pred p;\nelect.sync _|p, 0xffffffff;\nselp.u32 %0, 1, 0, p;\n}" : "=r"(e));
    return e;
}
constexpr uint64_t POL_FIRST = 0x12F0000000000000ull, POL_NORMAL = 0x1000000000000000ull;
__device__ __forceinline__ void tma_tile(uint32_t dst, const CUtensorMap* tm, int group, uint32_t bar, uint64_t pol) {
    asm volatile("cp.async.bulk.tensor.4d.shared::cluster.global.mbarrier::complete_tx::bytes.L2::cache_hint"
                 " [%0], [%1, {%3, %3, %3, %4}], [%2], %5;"
                 ::"r"(dst), "l"(tm), "r"(bar), "r"(0), "r"(group), "l"(pol) : "memory");
}
__device__ __forceinline__ void tma2d(uint32_t dst, const CUtensorMap* tm, int x, int y, uint32_t bar) {
    asm volatile("cp.async.bulk.tensor.2d.shared::cluster.global.mbarrier::complete_tx::bytes [%0], [%1, {%3, %4}], [%2];"
                 ::"r"(dst), "l"(tm), "r"(bar), "r"(x), "r"(y) : "memory");
}
__device__ __forceinline__ void bulk_load(uint32_t dst, const void* src, uint32_t bytes, uint32_t bar) {
    asm volatile("cp.async.bulk.shared::cluster.global.mbarrier::complete_tx::bytes [%0], [%1], %2, [%3];"
                 ::"r"(dst), "l"(src), "r"(bytes), "r"(bar) : "memory");
}
__device__ __forceinline__ void l2_prefetch(const void* p, uint32_t bytes) {
    asm volatile("cp.async.bulk.prefetch.L2.global [%0], %1;" ::"l"(p), "r"(bytes) : "memory");
}
__device__ __forceinline__ void mma16816(float (&c)[4], uint32_t a0, uint32_t a1, uint32_t a2, uint32_t a3, uint32_t b0, uint32_t b1) {
    asm volatile("mma.sync.aligned.m16n8k16.row.col.f32.bf16.bf16.f32 {%0,%1,%2,%3}, {%4,%5,%6,%7}, {%8,%9}, {%0,%1,%2,%3};"
                 : "+f"(c[0]), "+f"(c[1]), "+f"(c[2]), "+f"(c[3]) : "r"(a0), "r"(a1), "r"(a2), "r"(a3), "r"(b0), "r"(b1));
}
__device__ __forceinline__ void mma1688(float (&c)[4], uint32_t a0, uint32_t a1, uint32_t b0) {
    asm volatile("mma.sync.aligned.m16n8k8.row.col.f32.bf16.bf16.f32 {%0,%1,%2,%3}, {%4,%5}, {%6}, {%0,%1,%2,%3};"
                 : "+f"(c[0]), "+f"(c[1]), "+f"(c[2]), "+f"(c[3]) : "r"(a0), "r"(a1), "r"(b0));
}
__device__ __forceinline__ void ldsm4(uint32_t (&r)[4], uint32_t a) {
    asm volatile("ldmatrix.sync.aligned.m8n8.x4.shared.b16 {%0,%1,%2,%3}, [%4];"
                 : "=r"(r[0]), "=r"(r[1]), "=r"(r[2]), "=r"(r[3]) : "r"(a) : "memory");
}
__device__ __forceinline__ void ldsm4t(uint32_t (&r)[4], uint32_t a, uint32_t& zero) {
    asm volatile("ldmatrix.sync.aligned.m8n8.x4.trans.shared.b16 {%0,%1,%2,%3}, [%4];"
                 : "=r"(r[0]), "=r"(r[1]), "=r"(r[2]), "=r"(r[3]) : "r"(a + zero) : "memory");
    zero &= r[3];
}
__device__ __forceinline__ uint4 ld_pkt(const void* p) {
    uint4 v;
    asm volatile("{\n.reg .b128 t;\nld.relaxed.gpu.global.b128 t, [%4];\nmov.b128 {%0,%1,%2,%3}, t;\n}"
                 : "=r"(v.x), "=r"(v.y), "=r"(v.z), "=r"(v.w) : "l"(p) : "memory");
    return v;
}
__device__ __forceinline__ void st_pkt(const void* p, uint32_t a, uint32_t b, uint32_t c, uint32_t d) {
    asm volatile("{\n.reg .b128 t;\nmov.b128 t, {%1,%2,%3,%4};\nst.relaxed.gpu.global.b128 [%0], t;\n}"
                 ::"l"(p), "r"(a), "r"(b), "r"(c), "r"(d) : "memory");
}
__device__ __forceinline__ uint2 ld_pkt8(const void* p) {
    uint2 v;
    asm volatile("{\n.reg .b64 t;\nld.relaxed.gpu.global.b64 t, [%2];\nmov.b64 {%0,%1}, t;\n}" : "=r"(v.x), "=r"(v.y) : "l"(p) : "memory");
    return v;
}
__device__ __forceinline__ void red_cell(const char* p, float a, float b, float c) {
    jitter();
    asm volatile("red.relaxed.gpu.global.add.v4.f32 [%0], {%1,%2,%3,%4};" ::"l"(p), "f"(a), "f"(b), "f"(c), "f"(1.0f) : "memory");
}
#define PRED(n) "{\n.reg .pred p;\nsetp.ne.u32 p, %" #n ", 0;\n"
__device__ __forceinline__ void red_cell2_if(bool on, const char* p, float a, float b, float c) {
    jitter();
    asm volatile(PRED(5) "@p red.relaxed.gpu.global.add.v4.f32 [%0], {%1,%2,%3,%4};\n@p red.relaxed.gpu.global.add.v4.f32 [%0+4096], {%1,%2,%3,%4};\n}"
                 ::"l"(p), "f"(a), "f"(b), "f"(c), "f"(1.0f), "r"((uint32_t)on) : "memory");
}
__device__ __forceinline__ void st_pkt8_if(bool on, const void* p, uint32_t a, uint32_t b) {
    jitter();
    asm volatile(PRED(3) ".reg .b64 t;\nmov.b64 t, {%1,%2};\n@p st.relaxed.gpu.global.b64 [%0], t;\n}" ::"l"(p), "r"(a), "r"(b), "r"((uint32_t)on) : "memory");
}
__device__ __forceinline__ void st_pkt82_if(bool on, const void* p, uint32_t a, uint32_t b) {
    asm volatile(PRED(3) ".reg .b64 t;\nmov.b64 t, {%1,%2};\n@p st.relaxed.gpu.global.b64 [%0], t;\n@p st.relaxed.gpu.global.b64 [%0+4096], t;\n}"
                 ::"l"(p), "r"(a), "r"(b), "r"((uint32_t)on) : "memory");
}
__device__ __forceinline__ void st_pkt2_if(bool on, const void* p, uint32_t a, uint32_t b, uint32_t c, uint32_t d) {
    jitter();
    asm volatile(PRED(5) ".reg .b128 t;\nmov.b128 t, {%1,%2,%3,%4};\n@p st.relaxed.gpu.global.b128 [%0], t;\n@p st.relaxed.gpu.global.b128 [%0+4096], t;\n}"
                 ::"l"(p), "r"(a), "r"(b), "r"(c), "r"(d), "r"((uint32_t)on) : "memory");
}
__device__ __forceinline__ void mbar_arrive_if(bool on, uint32_t a) {
    jitter();
    asm volatile(PRED(1) "@p mbarrier.arrive.shared::cta.b64 _, [%0];\n}" ::"r"(a), "r"((uint32_t)on) : "memory");
}
__device__ __forceinline__ void sts16_if(bool on, uint32_t a, uint32_t v) {
    asm volatile(PRED(2) "@p st.shared.u16 [%0], %1;\n}" ::"r"(a), "h"((unsigned short)v), "r"((uint32_t)on) : "memory");
}
__device__ __forceinline__ void sts32_if(bool on, uint32_t a, uint32_t v) {
    asm volatile(PRED(2) "@p st.shared.u32 [%0], %1;\n}" ::"r"(a), "r"(v), "r"((uint32_t)on) : "memory");
}
__device__ __forceinline__ void sts128_if(bool on, uint32_t a, uint32_t x, uint32_t y, uint32_t z, uint32_t w) {
    jitter();
    asm volatile(PRED(5) "@p st.shared.v4.u32 [%0], {%1,%2,%3,%4};\n}" ::"r"(a), "r"(x), "r"(y), "r"(z), "r"(w), "r"((uint32_t)on) : "memory");
}
__device__ __forceinline__ float fast_rcp(float x) { float r; asm("rcp.approx.ftz.f32 %0, %1;" : "=f"(r) : "f"(x)); return r; }
__device__ __forceinline__ float fast_sqrt(float x) { float r; asm("sqrt.approx.ftz.f32 %0, %1;" : "=f"(r) : "f"(x)); return r; }
__device__ __forceinline__ float fast_ex2(float x) { float r; asm("ex2.approx.ftz.f32 %0, %1;" : "=f"(r) : "f"(x)); return r; }
__device__ __forceinline__ uint32_t pack2(float lo, float hi) {
    uint32_t r;
    asm("cvt.rn.bf16x2.f32 %0, %1, %2;" : "=r"(r) : "f"(hi), "f"(lo));
    return r;
}
__device__ __forceinline__ float bfr(float x) { return __uint_as_float(pack2(0.f, x)); }
__device__ __forceinline__ uint32_t badd2(uint32_t a, uint32_t b) { uint32_t r; asm("add.rn.bf16x2 %0, %1, %2;" : "=r"(r) : "r"(a), "r"(b)); return r; }
__device__ __forceinline__ uint32_t bsub2(uint32_t a, uint32_t b) { uint32_t r; asm("sub.rn.bf16x2 %0, %1, %2;" : "=r"(r) : "r"(a), "r"(b)); return r; }
__device__ __forceinline__ uint32_t bmul2(uint32_t a, uint32_t b) { uint32_t r; asm("mul.rn.bf16x2 %0, %1, %2;" : "=r"(r) : "r"(a), "r"(b)); return r; }
__device__ __forceinline__ float bf_lo(uint32_t w) { return __uint_as_float(w << 16); }
__device__ __forceinline__ float bf_hi(uint32_t w) { return __uint_as_float(w & 0xffff0000u); }
__device__ __forceinline__ float F(uint32_t t) { return __uint_as_float(t); }
__device__ __forceinline__ uint32_t lds16(uint32_t a) { unsigned short h; asm volatile("ld.shared.u16 %0, [%1];" : "=h"(h) : "r"(a) : "memory"); return h; }
__device__ __forceinline__ uint32_t lds32(uint32_t a) { uint32_t v; asm volatile("ld.shared.u32 %0, [%1];" : "=r"(v) : "r"(a) : "memory"); return v; }
__device__ __forceinline__ uint2 lds64(uint32_t a) {
    uint2 v; asm volatile("ld.shared.v2.u32 {%0,%1}, [%2];" : "=r"(v.x), "=r"(v.y) : "r"(a) : "memory"); return v;
}
__device__ __forceinline__ uint4 lds128(uint32_t a) {
    uint4 v; asm volatile("ld.shared.v4.u32 {%0,%1,%2,%3}, [%4];" : "=r"(v.x), "=r"(v.y), "=r"(v.z), "=r"(v.w) : "r"(a) : "memory"); return v;
}
__device__ __forceinline__ float sum8(const uint4& u, const uint4& v) {
    return ((F(u.x) + F(u.y)) + (F(u.z) + F(u.w))) + ((F(v.x) + F(v.y)) + (F(v.z) + F(v.w)));
}
__device__ __forceinline__ void sts16(uint32_t a, uint32_t v) { asm volatile("st.shared.u16 [%0], %1;" ::"r"(a), "h"((unsigned short)v) : "memory"); }
__device__ __forceinline__ void sts32(uint32_t a, uint32_t v) { asm volatile("st.shared.u32 [%0], %1;" ::"r"(a), "r"(v) : "memory"); }
__device__ __forceinline__ void stsf(uint32_t a, float v) { asm volatile("st.shared.f32 [%0], %1;" ::"r"(a), "f"(v) : "memory"); }
__device__ __forceinline__ void stsf2(uint32_t a, float x, float y) { asm volatile("st.shared.v2.f32 [%0], {%1,%2};" ::"r"(a), "f"(x), "f"(y) : "memory"); }
__device__ __forceinline__ void stsf4(uint32_t a, float x, float y, float z, float w) {
    asm volatile("st.shared.v4.f32 [%0], {%1,%2,%3,%4};" ::"r"(a), "f"(x), "f"(y), "f"(z), "f"(w) : "memory");
}
template <int ID, int N> __device__ __forceinline__ void bar_sync() { jitter(); asm volatile("bar.sync %0, %1;" ::"n"(ID), "n"(N) : "memory"); jitter(); }
template <int ID, int N> __device__ __forceinline__ void bar_arrive() { jitter(); asm volatile("bar.arrive %0, %1;" ::"n"(ID), "n"(N) : "memory"); jitter(); }
__device__ __forceinline__ void fence_async() { asm volatile("fence.proxy.async.shared::cta;" ::: "memory"); }
__device__ __forceinline__ float shx(float v, int m) { return __shfl_xor_sync(0xffffffffu, v, m); }
__device__ __forceinline__ float shi(float v, int l) { return __shfl_sync(0xffffffffu, v, l); }
__device__ __forceinline__ uint32_t shi(uint32_t v, int l) { return __shfl_sync(0xffffffffu, v, l); }
__device__ __forceinline__ uint32_t opaque(uint32_t x) { asm volatile("mov.u32 %0, %0;" : "+r"(x)); return x; }
__device__ __forceinline__ const char* opaque(const char* x) { asm volatile("mov.u64 %0, %0;" : "+l"(x)); return x; }
constexpr float LOG2E = 1.4426950408889634f, SCALE = 0.07216878364870322f;

#define TRACE(idx) do {} while (0)
#define TRACES(slot) do {} while (0)

__device__ __forceinline__ uint32_t probe_near(const Params& p, int w, int lane) {
    const int cta = blockIdx.x;
    const char* pr = p.scr + SCR_O + head_off(cta >> 2) + 2048 + w * 256 + (cta & 3) * 64;
    st_pkt2_if(lane < 4, pr + lane * 16, 0, 0, 0, 0);
    uint32_t best0 = ~0u, best1 = ~0u;
#pragma unroll 1
    for (int i = w & 1; i < 6 + (w & 1); i++) {
        uint32_t c = clk32(), v = 0;
        if (lane == 0) asm volatile("atom.relaxed.gpu.global.add.u32 %0, [%1], 1;" : "=r"(v) : "l"(pr + (i & 1) * HALF) : "memory");
        c += __shfl_sync(0xffffffffu, v, 0) >> 16;
        c = clk32() - c;
        if (i & 1) best1 = min(best1, c); else best0 = min(best0, c);
    }
    return min(best0, 0xffffu) | min(best1, 0xffffu) << 16;
}
__device__ __forceinline__ uint32_t near_half() {
    const uint4 a = lds128(SM_NEAR), b = lds128(SM_NEAR + 16);
    const uint32_t m = __vminu2(__vminu2(__vminu2(a.x, a.y), __vminu2(a.z, a.w)), __vminu2(__vminu2(b.x, b.y), __vminu2(b.z, b.w)));
    return head_near(blockIdx.x >> 2, ((m & 0xffffu) > m >> 16) != (CFG(FLIP) != 0) ? HALF : 0);
}

__device__ __forceinline__ int kv_group(int k, int t) {
    const int cta = blockIdx.x;
    return ((k * NHEAD + (cta >> 2)) * SK + (SK - WIN) + (CFG(ILV) ? (cta & 3) * 32 + t * 128 : (cta & 3) * 256 + t * 32)) / 8;
}
__device__ __forceinline__ uint32_t phase_ns() { return (((blockIdx.x >> 2) * 13) & 31) * CFG(STAG) / 32; }

__device__ __forceinline__ void ln_fast(float s, float q, float& mean, float& rstd) {
    mean = s * (1.f / DM);
    asm("rsqrt.approx.ftz.f32 %0, %1;" : "=f"(rstd) : "f"(fmaxf(fmaf(-mean, mean, fmaf(q, 1.f / DM, 1e-5f)), 1e-5f)));
}
__device__ __forceinline__ void q_role(const Params& p, int lane) {
    const int cta = blockIdx.x;
    mbar_wait(bar_at(B_EP), 0);
    const uint32_t epoch = lds32(SM_EPOCH), near = head_near(cta >> 2, near_half());
    auto sums = [&](float& S0, float& S1) {
        bar_sync<3, 288>();
        const uint32_t ra = SM_PQ + lane * 16;
        S0 = sum8(lds128(ra), lds128(ra + 1024)); S1 = sum8(lds128(ra + 512), lds128(ra + 1536));
    };
    float cs0, cs1;
    {
        uint32_t q0 = 0, q1 = 0, q2 = 0, q3 = 0;
#pragma unroll 1
        for (int r = 0; r < NB; r++) {
            sums(cs0, cs1);
            bar_arrive<7, 288>();
            q0 = q1; q1 = q2; q2 = q3; q3 = pack2(cs0, cs1);
        }
        const uint32_t t0 = shi(q3, 3 * lane - 72), t1 = shi(q3, 3 * lane - 71), t2 = shi(q3, 3 * lane - 70), tag = epoch << 8 | 0x40;
        const char* box = p.scr + SCR_O + head_off(cta >> 2) + 2048 + (lane >> 2) * 256 + (lane & 3) * 16;
        st_pkt2_if(true, box + (cta & 3) * 64, lane < 24 ? q0 : t0, lane < 24 ? q1 : t1, lane < 24 ? q2 : t2, tag);
        const uint32_t qd = SM_Q + (lane < 24 ? lane * 4 : 3 * 384 + (lane - 24) * 12), step = lane < 24 ? 384 : 4;
#pragma unroll 1
        for (int j = 0; j < 4; j++) {
            uint4 v;
            SPIN_DECL;
            do {
                __nanosleep(200);
                v = ld_pkt(box + near + j * 64);
                SPIN_CHECK(j);
            } while (__any_sync(0xffffffffu, v.w != tag));
            sts32(qd + j * 96, v.x); sts32(qd + j * 96 + step, v.y); sts32(qd + j * 96 + 2 * step, v.z);
        }
        mbar_arrive(bar_at(B_QR));
    }
    sums(cs0, cs1);
    bar_arrive<7, 288>();
    const char* const src = p.scr + SCR_Q + head_off(cta >> 2) + lane * 8 + near;
    const char* const dst = src + (cta & 3) * 192;
    const uint32_t qd = SM_Q + NB * 384 + lane * 4;
    st_pkt82_if(lane < 24, dst - near, 0, 0);
#pragma unroll 1
    for (int k = 0; k < NB; k++) {
        float S0, S1, mean, rstd;
        sums(S0, S1);
        ln_fast(shi(S1, 24), shi(S0, 24), mean, rstd);
        const uint32_t qq = pack2(fmaf(-mean, cs0, S0) * rstd, fmaf(-mean, cs1, S1) * rstd), tag = epoch * NB + k;
        st_pkt8_if(lane < 24, dst + ((int)HALF - 2 * (int)near), qq, tag);
        st_pkt8_if(lane < 24, dst, qq, tag);
        TRACES(k * 12 + 5);
        uint2 a, b, c;
        SPIN_DECL;
        do {
            a = ld_pkt8(src); b = ld_pkt8(src + 256); c = ld_pkt8(src + 512);
            SPIN_CHECK(k);
            sts32(qd, a.x); sts32(qd + 128, b.x); sts32(qd + 256, c.x);
        } while (__any_sync(0xffffffffu, a.y != tag || b.y != tag || c.y != tag));
        mbar_arrive(bar_at(B_QR));
    }
}

struct Maps { CUtensorMap k, v, q, o, g, u; };
__device__ __forceinline__ void load_role(const Params& p, const CUtensorMap* tmKV, int lane, uint32_t t0) {
    const int cta = blockIdx.x;
    t0 += phase_ns();
#pragma unroll 1
    for (int i = 1; i < 5; i++) {
        wait_ns(t0 + i * CFG(TICK0));
        if (elect_one()) l2_prefetch(p.wq + (size_t)(128 * i + cta) * 12288, 12288);
        TRACE(230 + i);
    }
    uint32_t plan[2];
#pragma unroll
    for (int i = 0; i < 2; i++) {
        const int j = lane + 32 * i, k = j >> 4, t = j & 15, u = t >> 1, jw = j - CFG(WIN);
        const int sb = k == 0 ? B_WC + (t >= 8) + (t >= 14) : t >= 12 ? B_RK + u - 5 : t >= 4 ? B_RR + t - 4 : t >= 2 ? B_RP : k > 1 ? B_RK + 3 : B_RR + t;
        const uint32_t sw = sb * 8 | (j < 18 ? 0 : (t >= 12 || u == 1 ? k - 1 : k) & 1) << 9;
        plan[i] = sw | (jw < 0 ? sw : (B_F1 + (jw & 15)) * 8 | ((jw >> 4) & 1) << 9) << 10 |
                  (slot_at(slots(k), t < 8 ? pass_nibble(k, u) : u) * 2 + (t & 1)) << 20 | (t < 10 && j >= 8 && j < 56) << 25;
    }
    bar_sync<6, 64>();
    wait_ns(t0 + kb_ns(60));
    if (elect_one()) bulk_load(ST_WD, p.wd + cta * 15360, 15360, bar_at(B_W));
    TRACE(235);
#pragma unroll 1
    for (int i = 0; i < 5; i++) {
        wait_ns(t0 + kb_ns(75) + i * kb_ns(6));
        if (elect_one()) { l2_prefetch(p.wg + (128 * i + cta) * 3072, 3072); l2_prefetch(p.wu + (128 * i + cta) * 3072, 3072); }
    }
#pragma unroll 1
    for (int i = 0; i < 6; i++) {
        wait_ns(t0 + kb_ns(105) + min(i, 4) * kb_ns(10));
        if (elect_one()) l2_prefetch(p.wo + (size_t)((cta >> 2) * DH + 32 * i + 8 * (cta & 3)) * 1280, 10240);
    }
    t0 += batch_ns(0);
    int jp = 0, shift = 0;
    uint32_t earliest = t0;
    auto requested = [&](uint32_t now) {
        shift = max(max(shift - CFG(GAIN), 0), (int)(now - t0) - (jp < 12 ? CFG(LMAX0) : CFG(LMAX)));
        TRACE(128 + jp);
        t0 += tick_ns(++jp);
    };
    const int grp0 = kv_group(0, 0);
    auto group = [&](int j) { return grp0 + (j >> 4) * (NHEAD * SK / 8) + (j & 7) * (CFG(ILV) ? 16 : 4); };
#pragma unroll 1
    for (int j = 0; j < 16 * NB; j++) {
        const uint32_t pl = __shfl_sync(0xffffffffu, j & 32 ? plan[1] : plan[0], j);
        const int jmax = min(j + CFG(PMAX), 16 * NB);
        jitter();
        uint32_t now;
        SPIN_DECL;
        while (true) {
            const bool ok = mbar_test2(SM_BAR + (pl & 511), (pl >> 9) & 1, SM_BAR + ((pl >> 10) & 511), (pl >> 19) & 1);
            now = now_ns();
            const int late = now - t0 - shift;
            if (ok && (jp > j ? (int)(now - earliest) : late) >= 0) break;
            if (late >= (jp > j ? 0 : CFG(PGRACE)) && jp < jmax) {
                if (elect_one())
                    asm volatile("cp.async.bulk.prefetch.tensor.4d.L2.global [%0, {%1, %1, %1, %2}];" ::"l"(tmKV + ((jp >> 3) & 1)), "r"(0), "r"(group(jp)) : "memory");
                requested(now);
            }
            SPIN_CHECK(j);
        }
        if (elect_one()) {
            mbar_expect_tx(bar_at(B_F1 + (j & 15)), TILE);
            tma_tile(SB + ((pl >> 20) & 31) * TILE, tmKV + ((j >> 3) & 1), group(j), bar_at(B_F1 + (j & 15)), pl >> 25 ? POL_NORMAL : POL_FIRST);
        }
        TRACE(256 + j);
        if ((j & 15) == 15) TRACES(88 + (j >> 4));
        earliest = now + CFG(VSTEP);
        if (jp == j) requested(now);
    }
}

__device__ __forceinline__ void reload_role(const Params& p, const Maps* tm, uint32_t t0) {
    const CUtensorMap* const tmK = &tm->k;
    const CUtensorMap* const tmV = &tm->v;
    const int cta = blockIdx.x;
    t0 += CFG(TICK0) + CFG(WLAG) + phase_ns();
#pragma unroll 1
    for (int i = 0; i < 5; i++) {
        wait_ns(t0 + i * CFG(TICK0));
        if (elect_one()) tma2d(ST_WQ + i * 12288, &tm->q, 48 * cta, 128 * i, bar_at(B_W));
        TRACE(240 + i);
        if (i == 1) bar_sync<5, 480>();
    }
#pragma unroll 1
    for (int i = 0, o = 0; i < 10;) {
        const uint32_t now = now_ns() - t0;
        if (o < 6 && (int)now >= kb_ns(105) + o * kb_ns(10)) {
            if (elect_one()) tma2d(ST_WO + o * 10240, &tm->o, 160 * (cta & 3), (cta >> 2) * DH + 32 * o, bar_at(B_W + 1));
            o++;
        } else if ((int)now >= kb_ns(77) + i * CFG(GSTEP) && (i < 9 || o == 6)) {
            if (elect_one()) tma2d(ST_WG + (i & 1) * 20480 + (i >> 1) * 4096, i & 1 ? &tm->u : &tm->g, (12 * cta) & ~7, 128 * (i >> 1), bar_at(B_W + 2));
            i++;
        }
    }
#pragma unroll 1
    for (int k = 0; k < NB - 1; k++) {
        mbar_wait(bar_at(B_RK), k & 1);
        if (elect_one()) {
            const uint32_t dst = SB + slot_at(slots(k), 0) * PAIR;
            mbar_expect_tx(bar_at(B_FL), PAIR);
            tma_tile(dst, tmV, kv_group(k, 0), bar_at(B_FL), POL_FIRST);
            tma_tile(dst + TILE, tmV, kv_group(k, 1), bar_at(B_FL), POL_FIRST);
        }
        mbar_wait(bar_at(B_RV), k & 1);
        uint32_t due = now_ns();
        if (elect_one()) mbar_expect_tx(bar_at(B_F3), 4 * PAIR);
#pragma unroll 1
        for (int t = 0; t < 8; t++) {
            wait_ns(due);
            due += k == NB - 2 ? CFG(RSTEP3) : CFG(RSTEP);
            if (elect_one())
                tma_tile(SB + slot_at(slots(k + 1), t >> 1) * PAIR + (t & 1) * TILE, tmK, kv_group(k + 1, t), bar_at(B_F3), POL_FIRST);
        }
        TRACE(121 + k);
    }
}

__device__ __forceinline__ void zero_role(const Params& p, int lane, uint32_t t0) {
    const int cta = blockIdx.x;
    unsigned ticket = 0;
    if (lane == 0) ticket = atomicAdd(&g_epoch, 1u);
    const uint32_t epoch = __shfl_sync(0xffffffffu, ticket, 0) / NCTA + 1;
    if (lane == 0) { sts32(SM_EPOCH, epoch); mbar_arrive(bar_at(B_EP)); }
    mbar_wait(bar_at(B_EP), 0);
#pragma unroll 1
    for (int k = 0; k < NB + 2; k++) {
        lane = opaque(lane);
        const int cl = 2 * (cta & 15) + (lane & 1);
        const int col = 80 * (cta >> 4) + (cl & 2 ? 48 : 0) + (cl >> 2) + (cl & 1 ? 8 : 0);
        const char* own = p.scr + (cl >> 2) * 256 + (cl & 3) * 16;
        uint32_t v0 = 0, v1 = 0, v2 = 0;
        if (lane < 4 && k < NB) {
            const unsigned short* xp = p.x + k * DM + col;
            v0 = __ldg(xp) << 16; v1 = __ldg(xp + 16) << 16; v2 = cl & 2 ? 0 : __ldg(xp + 32) << 16;
        }
        uint4 r;
        if (k == 1) mbar_wait(bar_at(B_RK), 0);
        if (k > 1) {
            mbar_wait(bar_at(B_FIN), k & 1);
            r = lds128(SM_FIN + (lane & 1) * 16);
        }
        if (k < NB) {
            const int lg = lane >> 3, ty = (lane & 7) >> 1;
            const char* dst = own + acc_off((k - (lg >> 1)) & 3, lg != 0, cta >> 4) + ty * HALF;
            wait_ns(t0 + batch_ns(k) + CFG(ZTILE) * CFG(TICK0));
            if (lg == 0 || (lg == 1 && (ty < 2 || k == NB - 1)) || (lg == 2 && k > 0 && ty > 1)) {
                st_pkt(dst, v0, v1, v2, ~0u);
                asm volatile("atom.relaxed.gpu.global.exch.b32 %0, [%1+12], %2;" : "=r"(v0) : "l"(dst), "r"(lane < 4 ? 0x3f800000u : 0u) : "memory");
                v0 = ~v0;
            }
            if (__any_sync(0xffffffffu, v0 != 0)) __trap();
            const char* cnt = p.scr + SCR_COUNT;
            if (lane < 2) asm volatile("red.relaxed.gpu.global.add.u32 [%0], 1;" ::"l"(cnt + lane * HALF) : "memory");
            const uint32_t target = ((epoch - 1) * NB + k + 1) * NCTA;
            cnt += near_half();
            SPIN_DECL;
            uint32_t v;
            do {
                __nanosleep(100);
                asm volatile("ld.relaxed.gpu.global.u32 %0, [%1];" : "=r"(v) : "l"(cnt) : "memory");
                SPIN_CHECK(v);
            } while (__any_sync(0xffffffffu, (int)(v - target) < 0));
        }
        __syncwarp();
        if (lane == 0) mbar_arrive(bar_at(B_Z));
        if (k > 1) {
            const int b = k - 2;
            const char* src = own + acc_off(b, 1, cta >> 4) + (2 + ((lane >> 1) & 1)) * HALF;
            unsigned short* o = p.out + b * DM + col + (lane >> 2) * 16;
            const bool on = !(lane & 2) && lane < (cl & 2 ? 8 : 12);
            wait_clk(clk32() + CFG(DLY_F));
            float cnt;
            SPIN_DECL;
            do {
                const uint4 v = ld_pkt(src);
                SPIN_CHECK(k);
                cnt = F(v.w) + shx(F(v.w), 2);
                const float y0 = F(v.x) + shx(F(v.x), 2), y1 = F(v.y) + shx(F(v.y), 2), y2 = F(v.z) + shx(F(v.z), 2);
                const uint32_t x01 = badd2(r.x, badd2(r.y, bmul2(pack2(y0, y1), r.w)));
                const uint32_t x2 = badd2(r.z, badd2(r.z >> 16, bmul2(pack2(y2, 0.f), r.w)));
                if (cnt == NCTA && on) *o = lane < 4 ? x01 : lane < 8 ? x01 >> 16 : x2;
            } while (__any_sync(0xffffffffu, cnt != NCTA));
            TRACES((2 * b + 1) * 6 + 4);
        }
    }
}

__host__ __device__ constexpr uint32_t desc_lo(uint32_t addr) { return ((addr & 0x3FFFFu) >> 4) | (1u << 16); }
constexpr uint32_t DESC_HI_TILE = (3072u >> 4) | (1u << 30);
constexpr uint32_t DESC_HI_VEC = 1u;
template <int TA, int AOFF, int BOFF>
__device__ __forceinline__ void wgmma_n8(float (&d)[4], uint32_t alo, uint32_t blo, int accumulate) {
    asm volatile("{\n.reg .pred p;\n.reg .b32 a, b;\n.reg .b64 da, db;\nsetp.ne.b32 p, %6, 0;\n"
                 "add.u32 a, %4, %8;\nadd.u32 b, %5, %9;\nmov.b64 da, {a, %10};\nmov.b64 db, {b, %11};\n"
                 "wgmma.mma_async.sync.aligned.m64n8k16.f32.bf16.bf16 {%0,%1,%2,%3}, da, db, p, 1, 1, %7, 0;\n}"
                 : "+f"(d[0]), "+f"(d[1]), "+f"(d[2]), "+f"(d[3])
                 : "r"(alo), "r"(blo), "r"(accumulate), "n"(TA), "n"(AOFF >> 4), "n"(BOFF >> 4), "n"(DESC_HI_TILE), "n"(DESC_HI_VEC));
}
template <int KS, int END>
__device__ __forceinline__ void qk_steps(float (&d)[4], uint32_t alo, uint32_t blo) {
    if constexpr (KS < END) {
        wgmma_n8<0, (KS >> 2) * 1024 + (KS & 3) * 32, KS * 32>(d, alo, blo, KS > 0);
        qk_steps<KS + 1, END>(d, alo, blo);
    }
}
__device__ __forceinline__ void pv_steps(float (&e)[3][4], uint32_t alo, uint32_t blo, int acc) {
    wgmma_n8<1, 0, 0>(e[0], alo, blo, acc); wgmma_n8<1, 1024, 0>(e[1], alo, blo, acc); wgmma_n8<1, 2048, 0>(e[2], alo, blo, acc);
    wgmma_n8<1, 6144, 32>(e[0], alo, blo, 1); wgmma_n8<1, 7168, 32>(e[1], alo, blo, 1); wgmma_n8<1, 8192, 32>(e[2], alo, blo, 1);
}
__device__ __forceinline__ void wg_fence() { asm volatile("wgmma.fence.sync.aligned;" ::: "memory"); }
__device__ __forceinline__ void wg_commit() { asm volatile("wgmma.commit_group.sync.aligned;" ::: "memory"); }
template <int N> __device__ __forceinline__ void wg_wait() { asm volatile("wgmma.wait_group.sync.aligned %0;" ::"n"(N) : "memory"); }
__device__ __forceinline__ void acc_ready(float (&d)[4]) { asm volatile("" : "+f"(d[0]), "+f"(d[1]), "+f"(d[2]), "+f"(d[3]) :: "memory"); }
__device__ __forceinline__ uint32_t score_pair(float (&d)[4]) {
    acc_ready(d);
    const uint32_t r = pack2(d[0], d[2]);
    return pack2(bf_lo(r) * SCALE, bf_hi(r) * SCALE);
}

__device__ __forceinline__ void attention_role(const Params& p, int w, int lane) {
    const int cta = blockIdx.x, t4 = lane & 3, g = lane >> 2;
    mbar_wait(bar_at(B_EP), 0);
    const uint32_t tag0 = lds32(SM_EPOCH) * NB;
    const char* const odst = p.scr + SCR_O + head_off(cta >> 2) + (2 * w + (g >> 2)) * 256 + (cta & 3) * 64 + (g & 3) * 16;
    const uint32_t pdst = SM_P + ((t4 + 3) & 3) * PSTR + (16 * w + g) * 2;
    auto softmax = [&](uint32_t& sc, int ps) -> uint32_t {
        const float s0 = bf_lo(sc), s1 = bf_hi(sc);
        int key = __float_as_int(fmaxf(s0, s1));
        key ^= (key >> 31) & 0x7fffffff;
        key = __reduce_max_sync(0xffffffffu, key);
        sts32(SM_MAX + w * 4, key);
        bar_sync<4, 128>();
        const uint4 mx = lds128(SM_MAX);
        key = max(max((int)mx.x, (int)mx.y), max((int)mx.z, (int)mx.w));
        key ^= (key >> 31) & 0x7fffffff;
        const float mb = __int_as_float(key) * LOG2E;
        const uint32_t pp = pack2(fast_ex2(fmaf(s0, LOG2E, -mb)), fast_ex2(fmaf(s1, LOG2E, -mb)));
        sts16(pdst + ps * 4 * PSTR, pp); sts16(pdst + ps * 4 * PSTR + 16, pp >> 16);
        fence_async();
        bar_sync<4, 128>();
        sc = pp;
        return key;
    };
    auto put_sum = [&](uint32_t pp, int ps) {
        uint32_t fs;
        asm volatile("redux.sync.add.u32 %0, %1, 0xffffffff;" : "=r"(fs) : "r"(__float2uint_rn((bf_lo(pp) + bf_hi(pp)) * 8388608.f)) : "memory");
        sts32(SM_SUM + ps * 16 + w * 4, fs);
    };
    auto aux_word = [&](uint32_t mx, const uint4& u, int k) {
        const float l = __uint2float_rn((u.x + u.y) + (u.z + u.w)) * (1.f / 8388608.f);
        return (g < 4 ? mx : (__float_as_uint(l) + 0x80u) & 0xffffff00u) | ((tag0 + k) & 0x7fu) | 0x80u;
    };
    auto send = [&](float (&e)[3][4], uint32_t aux, int ps) {
        acc_ready(e[0]); acc_ready(e[1]); acc_ready(e[2]);
        const uint32_t o0 = pack2(e[0][0], e[0][2]), o1 = pack2(e[1][0], e[1][2]), o2 = pack2(e[2][0], e[2][2]);
        st_pkt2_if(t4 == 0, odst + ps * 2048, o0, o1, o2, aux);
        mbar_arrive_if(lane == 0, bar_at(ps ? B_RV : B_PS));
    };
    mbar_wait(bar_at(B_QR), 0);
    TRACES(73);
#pragma unroll 1
    for (int it = 0; it <= NB; it++) {
        uint32_t m1 = 0;
        if (it < NB) {
            const uint32_t tab = slots(it);
            const uint32_t ka = SB + (2 * w + ((lane >> 3) & 1)) * 3072 + (lane & 7) * 128 + (((lane >> 4) ^ (lane & 7)) << 4);
            const uint32_t qa = SM_Q + it * 384 + (lane >> 3) * 16;
            uint32_t sc = 0;
#pragma unroll 1
            for (int u = 0; u < 4; u++) {
                const uint32_t base = ka + slot_at(tab, pass_nibble(it, u)) * PAIR;
                mbar_wait(bar_at(B_F1 + 2 * u + (w >> 1)), it & 1);
                float d0[4] = {}, d1[4] = {};
#pragma unroll
                for (int c = 0; c < 6; c++) {
                    uint32_t a0[4], a1[4], b[4];
                    ldsm4(b, qa + c * 64);
                    ldsm4(a0, (base ^ ((c & 1) * 64)) + (c >> 1) * 1024);
                    ldsm4(a1, (base ^ ((c & 1) * 64 + 32)) + (c >> 1) * 1024);
                    mma16816(d0, a0[0], a0[1], a0[2], a0[3], b[0], b[1]);
                    mma16816(d1, a1[0], a1[1], a1[2], a1[3], b[2], b[3]);
                }
                const uint32_t r = pack2(d0[0] + d1[0], d0[2] + d1[2]);
                mbar_arrive_if(lane == 0, bar_at(B_RR + 2 * u + (w >> 1)));
                if (t4 == ((u + 1) & 3)) sc = pack2(bf_lo(r) * SCALE, bf_hi(r) * SCALE);
            }
            m1 = softmax(sc, 0);
            put_sum(sc, 0);
        }
        if (it > 0) {
            const int k = it - 1;
            const uint32_t tab = slots(k);
            const uint32_t v0 = slot_at(tab, k < NB - 1 ? 0 : 4);
            TRACES(48 + k * 6);
            if (k > 0) mbar_wait(bar_at(B_F3), it & 1);
            mbar_wait(bar_at(B_QR), it & 1);
            fence_async();
            TRACES(49 + k * 6);
            float d[4][4] = {};
            const bool busy = k < NB - 1;
#pragma unroll
            for (int u = 0; u < 4; u++) {
                const uint32_t alo = desc_lo(SB) + slot_at(tab, u) * (PAIR >> 4), blo = desc_lo(SM_Q + 4 * 384);
                wg_fence();
                qk_steps<0, 6>(d[u], alo, blo);
                wg_commit();
                if (busy) {
                    wg_wait<1>();
                    if (u > 0) mbar_arrive_if(lane == 0, bar_at(B_RK + u - 1));
                }
                wg_fence();
                qk_steps<6, 12>(d[u], alo, blo);
                wg_commit();
                if (u < 3 && busy) wg_wait<1>();
            }
            wg_wait<2>();
            uint32_t sc = shi(score_pair(d[0]), lane & 28), s = shi(score_pair(d[1]), lane & 28);
            if (t4 == 2) sc = s;
            s = shi(score_pair(d[2]), lane & 28);
            if (t4 == 3) sc = s;
            wg_wait<0>();
            s = score_pair(d[3]);
            if (t4 == 0) sc = s;
            mbar_arrive_if(lane == 0, bar_at(B_RK + 3));
            TRACES(50 + k * 6);
            const uint32_t m2 = softmax(sc, 1);
            TRACES(51 + k * 6);
            float e[3][4] = {};
#pragma unroll
            for (int t = 0; t < 8; t++) {
                const int pr = ((t >> 1) + 1) & 3;
                if (t == 6 && k < NB - 1) mbar_wait(bar_at(B_FL), k & 1);
                wg_fence();
                pv_steps(e, desc_lo(SB + (t & 1) * TILE) + (pr ? slot_at(tab, 4 + pr) : v0) * (PAIR >> 4), desc_lo(SM_P + (4 + pr) * PSTR + (t & 1) * 64), t > 0);
                wg_commit();
                if (t < 7 && busy) wg_wait<1>();
                if (t == 1) put_sum(sc, 1);
            }
            bar_sync<4, 128>();
            const uint32_t aux = opaque(aux_word(m2, lds128(SM_SUM + 16), k));
            wg_wait<0>();
            send(e, aux, 1);
            TRACES(52 + k * 6);
        }
        if (it < NB) {
            const uint32_t tab = slots(it);
            if (it == 0) st_pkt2_if(t4 == 0, odst, 0, 0, 0, 0);
            bar_sync<4, 128>();
            const uint32_t aux = opaque(aux_word(m1, lds128(SM_SUM), it));
            float e[3][4] = {};
#pragma unroll 1
            for (int u = 0; u < 4; u++) {
                const uint32_t alo = desc_lo(SB) + slot_at(tab, 4 + u) * (PAIR >> 4), blo = desc_lo(SM_P) + u * (PSTR >> 4);
                mbar_wait(bar_at(B_F1 + 8 + 2 * u), it & 1);
                wg_fence();
                pv_steps(e, alo, blo, u > 0);
                wg_commit();
                wg_wait<1>();
                if (u == 1) mbar_arrive_if(lane == 0, bar_at(B_RP));
                mbar_wait(bar_at(B_F1 + 9 + 2 * u), it & 1);
                wg_fence();
                pv_steps(e, alo + (TILE >> 4), blo + 4, 1);
                wg_commit();
                wg_wait<1>();
            }
            wg_wait<0>();
            send(e, aux, 0);
            TRACES(53 + it * 6);
        }
    }
}

__device__ __forceinline__ void ln_finish(float s, float q, float& mean_b, float& rden) {
    const float mean = s * (1.f / DM);
    const float var = fmaxf(fmaf(q, 1.f / DM, -mean * mean), 0.f);
    mean_b = bfr(mean);
    rden = fast_rcp(bfr(fast_sqrt(bfr(bfr(var) + 1e-5f))));
}
__device__ __forceinline__ uint32_t ln_apply(uint32_t w, float mean_b, float rden) {
    const uint32_t d = bsub2(w, __byte_perm(__float_as_uint(mean_b), 0, 0x3232));
    return pack2(bf_lo(d) * rden, bf_hi(d) * rden);
}
__device__ __forceinline__ void put_x(uint32_t x01, uint32_t x2, uint32_t wa, bool e2) {
    jitter();
    sts16(wa, x01); sts16(wa + 8, x01 >> 16);
    sts16_if(!e2, wa + 16, x2);
}
__device__ __forceinline__ void get_x(uint32_t (&b)[10], uint32_t ra) {
    __syncwarp();
    const uint4 u = lds128(ra), v = lds128(ra + 16);
    const uint2 z = lds64(ra + 32);
    b[0] = u.x; b[1] = u.y; b[2] = u.z; b[3] = u.w; b[4] = v.x; b[5] = v.y; b[6] = v.z; b[7] = v.w; b[8] = z.x; b[9] = z.y;
}
__device__ __forceinline__ float fold(float a, float b, bool sel, int m) { return (sel ? b : a) + shx(sel ? a : b, m); }

__device__ __forceinline__ void chain_role(const Params& p, int w, int lane) {
    const int cta = blockIdx.x, h = cta >> 2, s = cta & 3;
    const int g = lane >> 2, t4 = lane & 3;
    const bool e1 = t4 & 1, e2 = t4 & 2;
    uint32_t wq[5][3][4], wo[3][5][4], wg[5][4], wh[5][2], wd[4][4];
    const int col0 = 80 * w + (e2 ? 48 : 0) + g + (e1 ? 8 : 0);
    const uint32_t xw = opaque(SM_X + w * 384 + 48 * (g >> 1) + (e2 ? 24 : 0) + (e1 ? 4 : 0) + 2 * (g & 1));
    const uint32_t xr = opaque(g == 1 ? SM_ONES : SM_X + w * 384 + (g == 3 ? 192 : 0) + 48 * t4);
    TRACES(75);
    sts32_if(lane < 12, SM_ONES + lane * 4, 0x3f803f80u);
    uint32_t zero = lane >> 5;
    const int mi = lane >> 3, mr = lane & 7;
    mbar_wait(bar_at(B_W), 0);
    TRACES(74);
    sts16(xw + 192, lds16(ST_X + 5120 + col0 * 2)); sts16(xw + 200, lds16(ST_X + 5120 + col0 * 2 + 32));
    sts16_if(!e2, xw + 208, lds16(ST_X + 5120 + col0 * 2 + 64));
#pragma unroll
    for (int i = 0; i < 5; i++)
#pragma unroll
        for (int mt = 0; mt < 3; mt++) ldsm4t(wq[i][mt], ST_WQ + (80 * w + 16 * i + mr + 8 * (mi >> 1)) * 96 + 32 * mt + 16 * (mi & 1), zero);
    const bool odd = cta & 1;
    const uint32_t lo = ST_WD + (mr + (odd ? 4 : 0)) * 1280 + 160 * w + 16 * (mi & 1);
    const uint32_t hi = ST_WD + ((mr & 3) + (odd ? 0 : 8)) * 1280 + 160 * w + 16 * (mi & 1);
    ldsm4t(wd[0], lo + 96 * (mi >> 1), zero);
    ldsm4t(wd[1], lo + 96 * (mi >> 1) + 32, zero);
    ldsm4t(wd[2], (mi < 2 ? lo : hi) + 64, zero);
    ldsm4t(wd[3], hi + 32 * (mi >> 1) + 96 * (mr >> 2), zero);
    fence_async();
    __syncwarp();
    mbar_arrive_if(lane == 0, bar_at(B_WC));
    mbar_wait(bar_at(B_EP), 0);
    const uint32_t near = __shfl_sync(0xffffffffu, near_half(), 0);
    uint32_t x01 = 0, x2 = 0, nx01 = 0, nx2 = 0;
#pragma unroll 1
    for (int n = -5; n < NROUND; n++) {
        const bool last = (ORD_LAST >> (n & 15)) & 1, head = !((ORD_NO_HEAD >> (n & 15)) & 1);
        const int k = (ORD_BATCH >> (2 * (n & 15))) & 3;
        if (n > -5 && n <= 0) bar_sync<7, 288>();
        else if (!last) bar_sync<2, 256>();
        TRACES(n <= 0 ? 83 + n : 95);
        const char* const slice = p.scr + acc_off(k, last, w);
        const char* const cell = opaque(slice + g * 256 + t4 * 16);
        if (n < -1) {
            const uint32_t xa = ST_X + (n + 5) * 1280, ln = opaque(lane);
            const int col0 = 80 * w + (ln & 2 ? 48 : 0) + (ln >> 2) + (ln & 1 ? 8 : 0);
            float sm = 0.f, sq = 0.f;
#pragma unroll
            for (int i = 0; i < 5; i++) {
                const uint2 c = lds64(xa + i * 256 + ln * 8);
                sm += (bf_lo(c.x) + bf_hi(c.x)) + (bf_lo(c.y) + bf_hi(c.y));
                sq = fmaf(bf_lo(c.x), bf_lo(c.x), fmaf(bf_hi(c.x), bf_hi(c.x), fmaf(bf_lo(c.y), bf_lo(c.y), fmaf(bf_hi(c.y), bf_hi(c.y), sq))));
            }
            x01 = lds16(xa + col0 * 2) | lds16(xa + col0 * 2 + 32) << 16;
            x2 = lds16(xa + col0 * 2 + 64);
#pragma unroll
            for (int o = 16; o; o >>= 1) { sm += shx(sm, o); sq += shx(sq, o); }
            float mean_b, rden;
            ln_finish(sm, sq, mean_b, rden);
            x01 = ln_apply(x01, mean_b, rden);
            x2 = ln_apply(x2, mean_b, rden);
            put_x(x01, x2, xw, e2);
        } else {
            if (n >= 0 && head) {
                if (!last || n == NROUND - 1) mbar_wait(bar_at(B_Z), (k + last) & 1);
                const char* src = p.scr + SCR_O + head_off(h) + head_near(h, near) + last * 2048 + (w & 6) * 256 + (lane & 15) * 16;
                const uint32_t tag = (lds32(SM_EPOCH) * NB + k) | 0x80u;
                mbar_wait(bar_at(last ? B_RV : B_PS), k & 1);
                uint4 v, z;
                {
                    SPIN_DECL;
                    do {
                        v = ld_pkt(src); z = ld_pkt(src + 256);
                        SPIN_CHECK(n);
                    } while (__any_sync(0xffffffffu, (((v.w ^ tag) | (z.w ^ tag)) & 0xffu) != 0));
                }
                TRACES(tr + 0);
                float a[3][4] = {};
                const uint32_t bb[3][2] = {{v.x, v.y}, {z.x, z.y}, {v.z, z.z}};
                float sa, sb, rl;
#pragma unroll
                for (int i = 0; i < 3; i++) {
                    const uint32_t l0 = g < 4 ? bb[i][0] : 0, l1 = g < 4 ? bb[i][1] : 0, h0 = g < 4 ? 0 : bb[i][0], h1 = g < 4 ? 0 : bb[i][1];
#pragma unroll
                    for (int mt = 0; mt < 5; mt++)
                        mma16816(a[mt % 3], wo[i][mt][0], wo[i][mt][1], wo[i][mt][2], wo[i][mt][3], mt < 3 ? l0 : h0, mt < 3 ? l1 : h1);
                    if (i == 0) {
                        int key = v.w & 0xffffff00u;
                        key ^= (key >> 31) & 0x7fffffff;
                        key = __reduce_max_sync(0xffffffffu, key);
                        key ^= (key >> 31) & 0x7fffffff;
                        const float ws = fast_ex2((F(v.w & 0xffffff00u) - __int_as_float(key)) * LOG2E);
                        sa = shi(ws, e1 ? 8 : 0); sb = shi(ws, e1 ? 12 : 4);
                        rl = ws * F(z.w & 0xffffff00u);
                        rl += shx(rl, 4);
                    }
                    if (i == 1) rl += shx(rl, 8);
                }
                float y[3];
#pragma unroll
                for (int j = 2; j < 5; j++) {
                    const int mt = j % 3;
                    y[mt] = fold(fmaf(a[mt][0], sa, a[mt][1] * sb), fmaf(a[mt][2], sa, a[mt][3] * sb), e1, 1);
                }
                const uint32_t pa = SM_PO + w * 512 + lane * 16;
                if (w < 2) {
                    const char* dst = opaque(cell + s * 16384);
                    rl = fast_rcp(rl);
                    bar_sync<1, 256>();
                    const uint4 c1 = lds128(pa), c2 = lds128(pa + 1024), c3 = lds128(pa + 2048);
                    red_cell2_if(true, dst, ((y[0] + F(c1.x)) + (F(c2.x) + F(c3.x))) * rl, ((y[1] + F(c1.y)) + (F(c2.y) + F(c3.y))) * rl,
                                 ((y[2] + F(c1.z)) + (F(c2.z) + F(c3.z))) * rl);
                } else {
                    stsf4(pa - 1024, y[0], y[1], y[2], 0.f);
                    bar_sync<1, 256>();
                }
                TRACES(tr + 1);
                if ((ORD_NO_TAIL >> n) & 1) continue;
                const uint32_t tsend = clk32();
                if (n == 0) {
                    st_pkt2_if(lane < 4, p.scr + SCR_O + head_off(h) + 2048 + w * 256 + s * 64 + lane * 16, 0, 0, 0, 0);
                    __syncwarp();
                } else if (!last) {
                    const char* nsrc = p.scr + acc_off(k - 1, 1, w) + near + g * 256 + t4 * 16;
                    SPIN_DECL;
                    do {
                        v = ld_pkt(nsrc);
                        SPIN_CHECK(n);
                        nx01 = pack2(F(v.x), F(v.y)); nx2 = pack2(F(v.z), 0.f);
                    } while (__any_sync(0xffffffffu, v.w != FULL_A));
                }
                wait_clk(tsend + (w < 2 ? 0 : 60) + (n < QUIET ? CFG(DLY_AL) : CFG(DLY_A)));
                {
                    SPIN_DECL;
                    do {
                        v = ld_pkt(cell + near);
                        SPIN_CHECK(n);
                        x01 = pack2(F(v.x), F(v.y));
                        x2 = pack2(F(v.z), 0.f);
                        put_x(x01, x2, xw, e2);
                    } while (__any_sync(0xffffffffu, v.w != FULL_A));
                }
                TRACES(tr + 2);
            } else if (n >= 0) {
                x01 = nx01; x2 = nx2;
                put_x(x01, x2, xw, e2);
            } else {
                mbar_wait(bar_at(B_W + 1), 0);
                const uint32_t ln = opaque(lane);
                const int mi = ln >> 3, mr = ln & 7;
                uint32_t zero = ln >> 5;
                TRACES(76);
#pragma unroll
                for (int i = 0; i < 3; i++) {
                    const int d = 16 * (w >> 1) + (mr >> 1) + 8 * (mr & 1) + (i < 2 ? 64 * (mi >> 1) + 4 * i : 128 + 4 * (mi >> 1));
#pragma unroll
                    for (int mt = 0; mt < 5; mt++) ldsm4t(wo[i][mt], ST_WO + d * 320 + 160 * (w & 1) + 32 * mt + 16 * (mi & 1), zero);
                }
                fence_async();
                __syncwarp();
                mbar_arrive_if(lane == 0, bar_at(B_WC + 1));
                mbar_wait(bar_at(B_W + 2), 0);
                TRACES(77);
#pragma unroll
                for (int i = 0; i < 5; i++) {
                    const uint32_t ga = ST_WG + (mi & 1) * 20480 + (80 * w + 16 * i + mr + 8 * (mi >> 1)) * 32;
                    uint32_t r[4];
                    ldsm4t(wg[i], ga + (odd ? 16 : 0), zero);
                    ldsm4t(r, ga + (odd ? 0 : 16), zero);
#pragma unroll
                    for (int kh = 0; kh < 2; kh++) {
                        const uint32_t moved = __shfl_xor_sync(0xffffffffu, odd ? r[2 * kh] : r[2 * kh + 1], 16);
                        wh[i][kh] = (g < 4) == odd ? moved : odd ? r[2 * kh + 1] : r[2 * kh];
                    }
                }
                fence_async();
                __syncwarp();
                mbar_arrive_if(lane == 0, bar_at(B_WC + 2));
                TRACES(72);
                x01 = 0x3f803f80u; x2 = 0x3f80u;
                put_x(x01, x2, xw, e2);
            }
            uint32_t b[10];
            get_x(b, xr);
            float a[2][4] = {};
#pragma unroll
            for (int i = 0; i < 5; i++) {
                mma16816(a[0], wg[i][0], wg[i][1], wg[i][2], wg[i][3], b[2 * i], b[2 * i + 1]);
                mma16816(a[1], wh[i][0], b[2 * i], wh[i][1], b[2 * i + 1], b[2 * i], b[2 * i + 1]);
            }
            stsf(SM_PG + (w >> 2) * 512 + (g + 8 * t4) * 16 + (w & 3) * 4, e2 ? (e1 ? a[1][2] : a[1][0]) : (e1 ? a[0][2] : a[0][0]));
            const uint2 cs = lds64(SM_CSG + lane * 48);
            const char* dst = opaque(cell + 3 * HALF - near);
            bar_sync<2, 256>();
            const float S = sum8(lds128(SM_PG + lane * 16), lds128(SM_PG + 512 + lane * 16));
            const float sx = shi(S, 25), sq = shi(S, 24), Su = shi(S, lane + (lane < 16 ? 8 : 4));
            if (n < 0) {
                if (w == 0) stsf2(SM_CSG + lane * 48, S, Su);
            } else {
                float mean_b, rden;
                ln_fast(sx, sq, mean_b, rden);
                const float gv = bfr(fmaf(-mean_b, F(cs.x), S) * rden), uv = bfr(fmaf(-mean_b, F(cs.y), Su) * rden);
                const float sg = fast_rcp(1.f + fast_ex2(-LOG2E * gv));
                const uint32_t hb = pack2(bfr(gv * sg) * uv, 0.f);
                const uint32_t b0 = __byte_perm(shi(hb, 2 * t4), shi(hb, 2 * t4 + 1), 0x5410);
                const uint32_t b1 = __byte_perm(shi(hb, e1 ? 18 : 16), shi(hb, e1 ? 19 : 17), 0x5410);
                const bool up = g >= 4;
                const uint32_t l0 = up ? 0 : b0, h0 = up ? b0 : 0;
                const uint32_t m1 = up == e2 ? b1 : 0;
                float d[3][4] = {};
                mma16816(d[0], wd[0][0], wd[0][1], wd[0][2], wd[0][3], l0, h0);
                mma16816(d[1], wd[1][0], wd[1][1], wd[1][2], wd[1][3], l0, h0);
                mma16816(d[2], wd[2][0], wd[2][1], wd[2][2], wd[2][3], l0, up ? 0 : m1);
                mma1688(d[0], wd[3][0], wd[3][1], m1);
                mma1688(d[1], wd[3][2], wd[3][3], m1);
                red_cell(dst, e1 ? d[0][2] : d[0][0], e1 ? d[1][2] : d[1][0], e1 ? d[2][2] : d[2][0]);
                const uint32_t tsend = clk32();
                TRACES(tr + 3);
                if (last && w != cta >> 4) continue;
                const float sgr = shi(sg, 27);
                const uint32_t sg2 = pack2(sgr, sgr);
                const uint32_t n01 = opaque(pack2((bf_lo(x01) - mean_b) * rden, (bf_hi(x01) - mean_b) * rden));
                const uint32_t n2 = opaque(pack2((bf_lo(x2) - mean_b) * rden, 0.f));
                if (last) {
                    sts128_if(lane >> 1 == (cta & 15), SM_FIN + (lane & 1) * 16, x01, n01, __byte_perm(x2, n2, 0x5410), sg2);
                    mbar_arrive_if(lane >> 1 == (cta & 15), bar_at(B_FIN));
                    __syncwarp();
                    continue;
                }
                wait_clk(tsend + (n < QUIET ? CFG(DLY_BL) : CFG(DLY_B)));
                const uint32_t r01 = x01, r2 = x2;
                float cnt;
                SPIN_DECL;
                do {
                    const uint4 v = ld_pkt(cell + 2 * HALF), z = ld_pkt(cell + 3 * HALF);
                    SPIN_CHECK(n);
                    cnt = F(v.w) + F(z.w);
                    x01 = badd2(r01, badd2(n01, bmul2(pack2(F(v.x) + F(z.x), F(v.y) + F(z.y)), sg2)));
                    x2 = badd2(r2, badd2(n2, bmul2(pack2(F(v.z) + F(z.z), 0.f), sg2)));
                    put_x(x01, x2, xw, e2);
                } while (__any_sync(0xffffffffu, cnt != NCTA));
                TRACES(tr + 4);
            }
        }
        {
            uint32_t b[10];
            get_x(b, xr);
            float a[3][4] = {};
            const float f0 = bf_lo(x01), f1 = bf_hi(x01), f2 = e2 ? 0.f : bf_lo(x2);
            float st;
#pragma unroll
            for (int i = 0; i < 5; i++) {
#pragma unroll
                for (int mt = 0; mt < 3; mt++) {
                    mma16816(a[mt], wq[i][mt][0], wq[i][mt][1], wq[i][mt][2], wq[i][mt][3], b[2 * i], b[2 * i + 1]);
                    if (i == 0 && mt == 0) st = fold(fmaf(f0, f0, fmaf(f1, f1, f2 * f2)), (f0 + f1) + f2, g & 1, 4);
                }
                if (i < 4) st += shx(st, i < 2 ? 1 << i : 2 << i);
            }
            const uint32_t pa = SM_PQ + (w >> 2) * 1024 + (g & 1) * 512 + ((e2 ? 16 : 0) + (e1 ? 4 : 0) + (g >> 1)) * 16 + (w & 3) * 4;
            stsf(pa + 128, e2 ? st : e1 ? a[1][2] : a[1][0]);
            stsf(pa, e2 ? (e1 ? a[2][2] : a[2][0]) : (e1 ? a[0][2] : a[0][0]));
            bar_sync<3, 288>();
            if (n >= 0 && w == cta >> 4) {
                red_cell2_if(lane >> 1 == (cta & 15), cell + (acc_off(k, 1, 0) - acc_off(k, 0, 0)), f0, f1, f2);
                __syncwarp();
            }
        }
    }
}

__host__ __device__ constexpr int bar_count(int i) {
    return i < 16 ? 1 : i < B_RR ? 0 : i < B_RK ? 2 : i <= B_RV ? 4 : i == B_Z ? 1 : i == B_EP ? 9 : i < B_WC ? 0 : i < B_FIN ? 8 :
           i == B_FIN ? 2 : i == B_PS || i == B_RP ? 4 : i == B_QR ? 32 : 1;
}
template <int I, int END> __device__ __forceinline__ void init_bars() {
    if constexpr (I < END) {
        if (bar_count(I)) mbar_init(bar_at(I), bar_count(I));
        init_bars<I + 1, END>();
    }
}
template <int ID> __device__ __forceinline__ void role_exit() { asm volatile("exit; // %0" ::"n"(ID)); }
constexpr int NTHREADS = 512;
#define STR2(x) #x
#define STR(x) STR2(x)
__global__ void __launch_bounds__(NTHREADS, 1)
decode_kernel(const Params p, const __grid_constant__ Maps tm) {
    extern __shared__ __align__(1024) unsigned char smem[];
    if (threadIdx.x == 0) l2_prefetch(p.wq + (size_t)blockIdx.x * 12288, 12288);
    const uint32_t t0 = now_ns() - CFG(LEAD);
    const int lane = threadIdx.x & 31;
    const int warp = __reduce_max_sync(0xffffffffu, threadIdx.x >> 5);
    if (warp < 8) {
        asm volatile("setmaxnreg.inc.sync.aligned.u32 " STR(CFG_REG_CHAIN) ";");
        bar_arrive<5, 480>();
        const uint32_t vote = probe_near(p, warp, lane);
        bar_sync<2, 256 + 32>();
        sts32(SM_NEAR + warp * 4, vote);
        mbar_arrive_if(lane == 0, bar_at(B_EP));
        chain_role(p, warp, __shfl_sync(0xffffffffu, lane, lane));
        role_exit<3>();
    } else if (warp < 12) {
        asm volatile("setmaxnreg.dec.sync.aligned.u32 " STR(CFG_REG_ATT) ";");
        if (elect_one()) {
            if (warp == 8) init_bars<0, 12>();
            else if (warp == 9) init_bars<12, 30>();
            else if (warp == 10) init_bars<30, 42>();
            else init_bars<42, NBAR>();
            asm volatile("fence.mbarrier_init.release.cluster;" ::: "memory");
            fence_async();
        }
        if (warp == 8) TRACE(236);
        bar_sync<5, 480>();
        if (warp == 8) TRACE(237);
        attention_role(p, warp - 8, lane);
        role_exit<2>();
    } else {
        asm volatile("setmaxnreg.dec.sync.aligned.u32 " STR(CFG_REG_HELP) ";");
        if (warp == 12) {
            load_role(p, &tm.k, lane, t0);
            role_exit<0>();
        } else {
            if (warp == 14) {
                if (smem_u32(smem) != SB) __trap();
                if (elect_one()) {
                    asm volatile("prefetch.tensormap [%0];" ::"l"(&tm.q) : "memory");
                    mbar_init(bar_at(B_W), 1); mbar_init(bar_at(B_W + 1), 1); mbar_init(bar_at(B_W + 2), 1);
                    asm volatile("fence.mbarrier_init.release.cluster;" ::: "memory");
                    fence_async();
                    mbar_expect_tx(bar_at(B_W), 61440 + 15360 + 6400); mbar_expect_tx(bar_at(B_W + 1), 61440); mbar_expect_tx(bar_at(B_W + 2), 40960);
                    bulk_load(ST_X, p.x, 5120, bar_at(B_W));
                    bulk_load(ST_X + 5120, p.wr, 1280, bar_at(B_W));
                }
                TRACE(238);
                reload_role(p, &tm, t0);
            } else {
                if (warp == 13 && elect_one()) {
                    asm volatile("prefetch.tensormap [%0];" ::"l"(&tm.g) : "memory");
                    asm volatile("prefetch.tensormap [%0];" ::"l"(&tm.u) : "memory");
                    asm volatile("prefetch.tensormap [%0];" ::"l"(&tm.o) : "memory");
                    asm volatile("prefetch.tensormap [%0];" ::"l"(&tm.k) : "memory");
                    asm volatile("prefetch.tensormap [%0];" ::"l"(&tm.v) : "memory");
                }
                TRACE(233 + warp);
                bar_sync<5, 480>();
                if (warp == 13) { bar_arrive<6, 64>(); q_role(p, lane); }
                else { bar_arrive<2, 256 + 32>(); zero_role(p, lane, t0); }
            }
            role_exit<1>();
        }
    }
}

typedef CUresult (*EncodeFn)(CUtensorMap*, CUtensorMapDataType, cuuint32_t, void*, const cuuint64_t*, const cuuint64_t*,
                             const cuuint32_t*, const cuuint32_t*, CUtensorMapInterleave, CUtensorMapSwizzle,
                             CUtensorMapL2promotion, CUtensorMapFloatOOBfill);

bool make_map(EncodeFn fn, CUtensorMap* m, const void* ptr, uint64_t cols, uint64_t rows, uint32_t bc, uint32_t br) {
    cuuint64_t dims[2] = {cols, rows};
    cuuint64_t strides[1] = {cols * 2};
    cuuint32_t box[2] = {bc, br};
    cuuint32_t es[2] = {1, 1};
    return fn(m, CU_TENSOR_MAP_DATA_TYPE_BFLOAT16, 2, const_cast<void*>(ptr), dims, strides, box, es, CU_TENSOR_MAP_INTERLEAVE_NONE,
              CU_TENSOR_MAP_SWIZZLE_NONE, CU_TENSOR_MAP_L2_PROMOTION_L2_128B, CU_TENSOR_MAP_FLOAT_OOB_FILL_NONE) == CUDA_SUCCESS;
}

bool make_kv_map(EncodeFn fn, CUtensorMap* m, const void* ptr) {
    cuuint64_t dims[4] = {64, 8, 3, (cuuint64_t)NB * NHEAD * SK / 8};
    cuuint64_t strides[3] = {DH * 2, 128, 8 * DH * 2};
    cuuint32_t box[4] = {64, 8, 3, 4};
    cuuint32_t es[4] = {1, 1, 1, 1};
    return fn(m, CU_TENSOR_MAP_DATA_TYPE_BFLOAT16, 4, const_cast<void*>(ptr), dims, strides, box, es, CU_TENSOR_MAP_INTERLEAVE_NONE,
              CU_TENSOR_MAP_SWIZZLE_128B, CU_TENSOR_MAP_L2_PROMOTION_L2_128B, CU_TENSOR_MAP_FLOAT_OOB_FILL_NONE) == CUDA_SUCCESS;
}

}

extern "C" void kernel_launch(void* const* d_in, const int* in_sizes, int n_in, void* d_out, int out_size) {
    (void)in_sizes; (void)n_in; (void)out_size;
    static EncodeFn fn = nullptr;
    static const char* scr = nullptr;
    if (!fn) {
        void* f = nullptr;
        cudaDriverEntryPointQueryResult qr;
        if (cudaGetDriverEntryPoint("cuTensorMapEncodeTiled", &f, cudaEnableDefault, &qr) != cudaSuccess || !f) return;
        void* sp = nullptr;
        if (cudaGetSymbolAddress(&sp, g_scratch) != cudaSuccess) return;
        scr = (const char*)(((uintptr_t)sp + (2 << 20) - 1) & ~(uintptr_t)((2 << 20) - 1));
        fn = (EncodeFn)f;
        cudaFuncSetAttribute(decode_kernel, cudaFuncAttributeMaxDynamicSharedMemorySize, SMEM_BYTES);
    }
    Maps tm;
    if (!make_kv_map(fn, &tm.k, d_in[1]) || !make_kv_map(fn, &tm.v, d_in[2])) return;
    if (!make_map(fn, &tm.q, d_in[3], NHEAD * DH, DM, 48, 128) || !make_map(fn, &tm.o, d_in[4], DM, NHEAD * DH, 160, 32)) return;
    if (!make_map(fn, &tm.g, d_in[7], FF, DM, 16, 128) || !make_map(fn, &tm.u, d_in[8], FF, DM, 16, 128)) return;
    Params p;
    p.x = (const unsigned short*)d_in[0];
    p.wq = (const char*)d_in[3];
    p.wo = (const char*)d_in[4];
    p.wr = (const unsigned short*)d_in[6];
    p.wg = (const char*)d_in[7];
    p.wu = (const char*)d_in[8];
    p.wd = (const char*)d_in[9];
    p.out = (unsigned short*)d_out;
    p.scr = scr;
    decode_kernel<<<NCTA, NTHREADS, SMEM_BYTES>>>(p, tm);
}
```

```cpp
#include <cuda_runtime.h>
#include <cuda_bf16.h>
#include <cuda.h>
#include <stdint.h>

namespace {

constexpr int NB = 4, DM = 640, NHEAD = 32, DH = 192, SK = 4096, WIN = 1024, FF = 1536;
constexpr int NCTA = 128;
constexpr int TILE = 12288, PAIR = 2 * TILE;

#define CFG_LIST(X) \
    X(TICK0, 479)        \
    X(TICK, 495)        \
    X(LEAD, 600)        \
    X(STAG, 500)        \
    X(WLAG, 350)        \
    X(GSTEP, 750)        \
    X(WIN, 5)        \
    X(PMAX, 2)        \
    X(PGRACE, 50)        \
    X(LMAX0, 150)        \
    X(LMAX, 160) \
    X(GAIN, 5)        \
    X(VSTEP, 150)        \
    X(RSTEP, 670)        \
    X(RSTEP3, 450) \
    X(ZTILE, 11)        \
    X(DLY_A, 410)        \
    X(DLY_AL, 100) \
    X(DLY_B, 570) \
    X(DLY_BL, 950) \
    X(DLY_F, 290) \
    X(ILV, 1) \
    X(ODD, 0) \
    X(FLIP, 0) \

#define X(n, v) constexpr int CFG_##n = v;
CFG_LIST(X)
#undef X
#define CFG(n) CFG_##n
constexpr int QUIET = 8;
#define CFG_REG_CHAIN 216
#define CFG_REG_ATT 48
#define CFG_REG_HELP 32
constexpr int KB_KV0 = 165;
__device__ __forceinline__ int kb_ns(int kb) { return kb * CFG(TICK0) / 12; }
__device__ __forceinline__ int tick_ns(int j) { return (j <= 16 ? CFG(TICK0) : CFG(TICK)) + (j & 1 ? -CFG(ODD) : CFG(ODD)); }
__device__ __forceinline__ int batch_ns(int k) { return kb_ns(KB_KV0) + (k ? 16 * (CFG(TICK0) + (k - 1) * CFG(TICK)) : 0); }

__device__ __forceinline__ uint32_t slots(int k) { return k & 2 ? (k & 1 ? 0x21304768u : 0x76835214u) : (k & 1 ? 0x21480765u : 0x76543210u); }
__device__ __forceinline__ int pass_nibble(int k, int u) { return k > 0 ? 4 + (u & 1) : u; }
__device__ __forceinline__ uint32_t slot_at(uint32_t tab, int u) { return (tab >> (4 * u)) & 15; }

constexpr int NROUND = 11;
constexpr uint32_t ORD_BATCH = 0x3b9910, ORD_LAST = 0x6da, ORD_NO_HEAD = 0x248, ORD_NO_TAIL = 0x092;

constexpr uint32_t SB = 1024;
constexpr uint32_t SM_BAR = SB + 9 * PAIR;
constexpr int B_F1 = 0;
constexpr int B_RR = 24;
constexpr int B_RK = 32;
constexpr int B_RV = 36;
constexpr int B_Z = 37;
constexpr int B_EP = 38;
constexpr int B_W = 39;
constexpr int B_WC = 42;
constexpr int B_FIN = 45;
constexpr int B_F3 = 46;
constexpr int B_PS = 48;
constexpr int B_RP = 49;
constexpr int B_FL = 50;
constexpr int B_QR = 51;
constexpr int NBAR = 52;
__host__ __device__ constexpr uint32_t bar_at(int i) { return SM_BAR + 8 * i; }
constexpr uint32_t SM_EPOCH = SM_BAR + 416;
constexpr uint32_t SM_MAX = SM_EPOCH + 16;
constexpr uint32_t SM_SUM = SM_MAX + 16;
constexpr uint32_t SM_NEAR = SM_SUM + 32;
constexpr uint32_t SM_FIN = SM_NEAR + 32;
constexpr uint32_t SM_Q = SM_FIN + 32;
constexpr uint32_t PSTR = 144;
constexpr uint32_t SM_P = SM_Q + 5 * 384;
constexpr uint32_t SM_X = SM_P + 8 * PSTR;
constexpr uint32_t SM_CSG = SM_X + 40;
constexpr uint32_t SM_ONES = SM_X + 8 * 384;
constexpr uint32_t SM_PG = SM_ONES + 48;
constexpr uint32_t SM_PO = SM_PG + 1024;
constexpr uint32_t SM_PQ = SM_PO;
constexpr int SMEM_BYTES = SM_PO + 3072 - SB;
static_assert(SMEM_BYTES <= 232448 && SM_Q % 16 == 0 && SM_P % 16 == 0 && SM_X % 16 == 0 && SM_PO % 16 == 0, "smem");
constexpr uint32_t ST_WQ = SB, ST_WD = SB + 3 * PAIR, ST_WO = SB + 4 * PAIR, ST_WG = SB + 7 * PAIR, ST_X = ST_WG + 40960;

__device__ unsigned g_epoch;
__device__ unsigned char g_scratch[4 << 20];
constexpr uint32_t HALF = 4096, SCR_O = 1 << 16, SCR_Q = 1 << 17, SCR_COUNT = 3 << 16;
__device__ __forceinline__ uint32_t acc_off(int k, int layer, int w) {
    return (k & 1) << 6 | layer << 7 | (w & 1) << 11 | (w >> 1) << 14 | (k + layer == NB) << 18;
}
__device__ __forceinline__ uint32_t head_off(int h) { return (h & 3) << 14 | (h & 4) << 16 | (h & 8) << 17 | (h & 16) << 9; }
__device__ __forceinline__ uint32_t head_near(int h, uint32_t near) { return near ^ HALF ^ (h & 16) << 8; }
constexpr uint32_t FULL_A = 0x42040000u;

struct Params {
    const char* wq;
    const unsigned short* x;
    const char* wo;
    const unsigned short* wr;
    const char* wg;
    const char* wu;
    const char* wd;
    unsigned short* out;
    const char* scr;
};

__device__ __forceinline__ uint32_t smem_u32(const void* p) { return (uint32_t)__cvta_generic_to_shared(p); }
__device__ __forceinline__ void mbar_init(uint32_t a, uint32_t c) { asm volatile("mbarrier.init.shared::cta.b64 [%0], %1;" ::"r"(a), "r"(c) : "memory"); }
__device__ __forceinline__ void mbar_expect_tx(uint32_t a, uint32_t b) {
    asm volatile("mbarrier.arrive.expect_tx.shared::cta.b64 _, [%0], %1;" ::"r"(a), "r"(b) : "memory");
}
__device__ __forceinline__ void mbar_arrive(uint32_t a) { asm volatile("mbarrier.arrive.shared::cta.b64 _, [%0];" ::"r"(a) : "memory"); }
constexpr uint32_t SPIN_LIMIT = 1u << 22;
#define SPIN_DECL uint32_t spins = 0
#define SPIN_CHECK(info) { if (++spins > SPIN_LIMIT) __trap(); }
__device__ __forceinline__ void jitter() {}
__device__ __forceinline__ void mbar_wait(uint32_t a, uint32_t parity) {
    jitter();
    uint32_t ok;
    SPIN_DECL;
    while (true) {
        asm volatile("{\n.reg .pred p;\nmbarrier.try_wait.parity.shared::cta.b64 p, [%1], %2;\nselp.u32 %0, 1, 0, p;\n}"
                     : "=r"(ok) : "r"(a), "r"(parity) : "memory");
        if (ok) break;
        SPIN_CHECK((a - SM_BAR) / 8 * 10 + parity);
    }
    jitter();
}
__device__ __forceinline__ bool mbar_test2(uint32_t a, uint32_t pa, uint32_t b, uint32_t pb) {
    uint32_t ok;
    asm volatile("{\n.reg .pred p, q;\nmbarrier.test_wait.parity.shared::cta.b64 p, [%1], %2;\n"
                 "mbarrier.test_wait.parity.shared::cta.b64 q, [%3], %4;\nand.pred p, p, q;\nvote.sync.all.pred p, p, 0xffffffff;\nselp.u32 %0, 1, 0, p;\n}"
                 : "=r"(ok) : "r"(a), "r"(pa), "r"(b), "r"(pb) : "memory");
    return ok;
}
__device__ __forceinline__ uint32_t now_ns() { uint32_t t; asm volatile("mov.u32 %0, %%globaltimer_lo;" : "=r"(t) :: "memory"); return t; }
__device__ __forceinline__ uint32_t clk32() { uint32_t c; asm volatile("mov.u32 %0, %%clock;" : "=r"(c) :: "memory"); return c; }
__device__ __forceinline__ void wait_ns(uint32_t t) { jitter(); while ((int)(now_ns() - t) < 0) {} }
__device__ __forceinline__ void wait_clk(uint32_t t) { jitter(); while ((int)(clk32() - t) < 0) {} }
__device__ __forceinline__ bool elect_one() {
    uint32_t e;
    asm volatile("{\n.reg .pred p;\nelect.sync _|p, 0xffffffff;\nselp.u32 %0, 1, 0, p;\n}" : "=r"(e));
    return e;
}
constexpr uint64_t POL_FIRST = 0x12F0000000000000ull, POL_NORMAL = 0x1000000000000000ull;
__device__ __forceinline__ void tma_tile(uint32_t dst, const CUtensorMap* tm, int group, uint32_t bar, uint64_t pol) {
    asm volatile("cp.async.bulk.tensor.4d.shared::cluster.global.mbarrier::complete_tx::bytes.L2::cache_hint"
                 " [%0], [%1, {%3, %3, %3, %4}], [%2], %5;"
                 ::"r"(dst), "l"(tm), "r"(bar), "r"(0), "r"(group), "l"(pol) : "memory");
}
__device__ __forceinline__ void tma2d(uint32_t dst, const CUtensorMap* tm, int x, int y, uint32_t bar) {
    asm volatile("cp.async.bulk.tensor.2d.shared::cluster.global.mbarrier::complete_tx::bytes [%0], [%1, {%3, %4}], [%2];"
                 ::"r"(dst), "l"(tm), "r"(bar), "r"(x), "r"(y) : "memory");
}
__device__ __forceinline__ void bulk_load(uint32_t dst, const void* src, uint32_t bytes, uint32_t bar) {
    asm volatile("cp.async.bulk.shared::cluster.global.mbarrier::complete_tx::bytes [%0], [%1], %2, [%3];"
                 ::"r"(dst), "l"(src), "r"(bytes), "r"(bar) : "memory");
}
__device__ __forceinline__ void l2_prefetch(const void* p, uint32_t bytes) {
    asm volatile("cp.async.bulk.prefetch.L2.global [%0], %1;" ::"l"(p), "r"(bytes) : "memory");
}
__device__ __forceinline__ void mma16816(float (&c)[4], uint32_t a0, uint32_t a1, uint32_t a2, uint32_t a3, uint32_t b0, uint32_t b1) {
    asm volatile("mma.sync.aligned.m16n8k16.row.col.f32.bf16.bf16.f32 {%0,%1,%2,%3}, {%4,%5,%6,%7}, {%8,%9}, {%0,%1,%2,%3};"
                 : "+f"(c[0]), "+f"(c[1]), "+f"(c[2]), "+f"(c[3]) : "r"(a0), "r"(a1), "r"(a2), "r"(a3), "r"(b0), "r"(b1));
}
__device__ __forceinline__ void mma1688(float (&c)[4], uint32_t a0, uint32_t a1, uint32_t b0) {
    asm volatile("mma.sync.aligned.m16n8k8.row.col.f32.bf16.bf16.f32 {%0,%1,%2,%3}, {%4,%5}, {%6}, {%0,%1,%2,%3};"
                 : "+f"(c[0]), "+f"(c[1]), "+f"(c[2]), "+f"(c[3]) : "r"(a0), "r"(a1), "r"(b0));
}
__device__ __forceinline__ void ldsm4(uint32_t (&r)[4], uint32_t a) {
    asm volatile("ldmatrix.sync.aligned.m8n8.x4.shared.b16 {%0,%1,%2,%3}, [%4];"
                 : "=r"(r[0]), "=r"(r[1]), "=r"(r[2]), "=r"(r[3]) : "r"(a) : "memory");
}
__device__ __forceinline__ void ldsm4t(uint32_t (&r)[4], uint32_t a, uint32_t& zero) {
    asm volatile("ldmatrix.sync.aligned.m8n8.x4.trans.shared.b16 {%0,%1,%2,%3}, [%4];"
                 : "=r"(r[0]), "=r"(r[1]), "=r"(r[2]), "=r"(r[3]) : "r"(a + zero) : "memory");
    zero &= r[3];
}
__device__ __forceinline__ uint4 ld_pkt(const void* p) {
    uint4 v;
    asm volatile("{\n.reg .b128 t;\nld.relaxed.gpu.global.b128 t, [%4];\nmov.b128 {%0,%1,%2,%3}, t;\n}"
                 : "=r"(v.x), "=r"(v.y), "=r"(v.z), "=r"(v.w) : "l"(p) : "memory");
    return v;
}
__device__ __forceinline__ void st_pkt(const void* p, uint32_t a, uint32_t b, uint32_t c, uint32_t d) {
    asm volatile("{\n.reg .b128 t;\nmov.b128 t, {%1,%2,%3,%4};\nst.relaxed.gpu.global.b128 [%0], t;\n}"
                 ::"l"(p), "r"(a), "r"(b), "r"(c), "r"(d) : "memory");
}
__device__ __forceinline__ uint2 ld_pkt8(const void* p) {
    uint2 v;
    asm volatile("{\n.reg .b64 t;\nld.relaxed.gpu.global.b64 t, [%2];\nmov.b64 {%0,%1}, t;\n}" : "=r"(v.x), "=r"(v.y) : "l"(p) : "memory");
    return v;
}
__device__ __forceinline__ void red_cell(const char* p, float a, float b, float c) {
    jitter();
    asm volatile("red.relaxed.gpu.global.add.v4.f32 [%0], {%1,%2,%3,%4};" ::"l"(p), "f"(a), "f"(b), "f"(c), "f"(1.0f) : "memory");
}
#define PRED(n) "{\n.reg .pred p;\nsetp.ne.u32 p, %" #n ", 0;\n"
__device__ __forceinline__ void red_cell2_if(bool on, const char* p, float a, float b, float c) {
    jitter();
    asm volatile(PRED(5) "@p red.relaxed.gpu.global.add.v4.f32 [%0], {%1,%2,%3,%4};\n@p red.relaxed.gpu.global.add.v4.f32 [%0+4096], {%1,%2,%3,%4};\n}"
                 ::"l"(p), "f"(a), "f"(b), "f"(c), "f"(1.0f), "r"((uint32_t)on) : "memory");
}
__device__ __forceinline__ void st_pkt8_if(bool on, const void* p, uint32_t a, uint32_t b) {
    jitter();
    asm volatile(PRED(3) ".reg .b64 t;\nmov.b64 t, {%1,%2};\n@p st.relaxed.gpu.global.b64 [%0], t;\n}" ::"l"(p), "r"(a), "r"(b), "r"((uint32_t)on) : "memory");
}
__device__ __forceinline__ void st_pkt82_if(bool on, const void* p, uint32_t a, uint32_t b) {
    asm volatile(PRED(3) ".reg .b64 t;\nmov.b64 t, {%1,%2};\n@p st.relaxed.gpu.global.b64 [%0], t;\n@p st.relaxed.gpu.global.b64 [%0+4096], t;\n}"
                 ::"l"(p), "r"(a), "r"(b), "r"((uint32_t)on) : "memory");
}
__device__ __forceinline__ void st_pkt2_if(bool on, const void* p, uint32_t a, uint32_t b, uint32_t c, uint32_t d) {
    jitter();
    asm volatile(PRED(5) ".reg .b128 t;\nmov.b128 t, {%1,%2,%3,%4};\n@p st.relaxed.gpu.global.b128 [%0], t;\n@p st.relaxed.gpu.global.b128 [%0+4096], t;\n}"
                 ::"l"(p), "r"(a), "r"(b), "r"(c), "r"(d), "r"((uint32_t)on) : "memory");
}
__device__ __forceinline__ void mbar_arrive_if(bool on, uint32_t a) {
    jitter();
    asm volatile(PRED(1) "@p mbarrier.arrive.shared::cta.b64 _, [%0];\n}" ::"r"(a), "r"((uint32_t)on) : "memory");
}
__device__ __forceinline__ void sts16_if(bool on, uint32_t a, uint32_t v) {
    asm volatile(PRED(2) "@p st.shared.u16 [%0], %1;\n}" ::"r"(a), "h"((unsigned short)v), "r"((uint32_t)on) : "memory");
}
__device__ __forceinline__ void sts32_if(bool on, uint32_t a, uint32_t v) {
    asm volatile(PRED(2) "@p st.shared.u32 [%0], %1;\n}" ::"r"(a), "r"(v), "r"((uint32_t)on) : "memory");
}
__device__ __forceinline__ void sts128_if(bool on, uint32_t a, uint32_t x, uint32_t y, uint32_t z, uint32_t w) {
    jitter();
    asm volatile(PRED(5) "@p st.shared.v4.u32 [%0], {%1,%2,%3,%4};\n}" ::"r"(a), "r"(x), "r"(y), "r"(z), "r"(w), "r"((uint32_t)on) : "memory");
}
__device__ __forceinline__ float fast_rcp(float x) { float r; asm("rcp.approx.ftz.f32 %0, %1;" : "=f"(r) : "f"(x)); return r; }
__device__ __forceinline__ float fast_sqrt(float x) { float r; asm("sqrt.approx.ftz.f32 %0, %1;" : "=f"(r) : "f"(x)); return r; }
__device__ __forceinline__ float fast_ex2(float x) { float r; asm("ex2.approx.ftz.f32 %0, %1;" : "=f"(r) : "f"(x)); return r; }
__device__ __forceinline__ uint32_t pack2(float lo, float hi) {
    uint32_t r;
    asm("cvt.rn.bf16x2.f32 %0, %1, %2;" : "=r"(r) : "f"(hi), "f"(lo));
    return r;
}
__device__ __forceinline__ float bfr(float x) { return __uint_as_float(pack2(0.f, x)); }
__device__ __forceinline__ uint32_t badd2(uint32_t a, uint32_t b) { uint32_t r; asm("add.rn.bf16x2 %0, %1, %2;" : "=r"(r) : "r"(a), "r"(b)); return r; }
__device__ __forceinline__ uint32_t bsub2(uint32_t a, uint32_t b) { uint32_t r; asm("sub.rn.bf16x2 %0, %1, %2;" : "=r"(r) : "r"(a), "r"(b)); return r; }
__device__ __forceinline__ uint32_t bmul2(uint32_t a, uint32_t b) { uint32_t r; asm("mul.rn.bf16x2 %0, %1, %2;" : "=r"(r) : "r"(a), "r"(b)); return r; }
__device__ __forceinline__ float bf_lo(uint32_t w) { return __uint_as_float(w << 16); }
__device__ __forceinline__ float bf_hi(uint32_t w) { return __uint_as_float(w & 0xffff0000u); }
__device__ __forceinline__ float F(uint32_t t) { return __uint_as_float(t); }
__device__ __forceinline__ uint32_t lds16(uint32_t a) { unsigned short h; asm volatile("ld.shared.u16 %0, [%1];" : "=h"(h) : "r"(a) : "memory"); return h; }
__device__ __forceinline__ uint32_t lds32(uint32_t a) { uint32_t v; asm volatile("ld.shared.u32 %0, [%1];" : "=r"(v) : "r"(a) : "memory"); return v; }
__device__ __forceinline__ uint2 lds64(uint32_t a) {
    uint2 v; asm volatile("ld.shared.v2.u32 {%0,%1}, [%2];" : "=r"(v.x), "=r"(v.y) : "r"(a) : "memory"); return v;
}
__device__ __forceinline__ uint4 lds128(uint32_t a) {
    uint4 v; asm volatile("ld.shared.v4.u32 {%0,%1,%2,%3}, [%4];" : "=r"(v.x), "=r"(v.y), "=r"(v.z), "=r"(v.w) : "r"(a) : "memory"); return v;
}
__device__ __forceinline__ float sum8(const uint4& u, const uint4& v) {
    return ((F(u.x) + F(u.y)) + (F(u.z) + F(u.w))) + ((F(v.x) + F(v.y)) + (F(v.z) + F(v.w)));
}
__device__ __forceinline__ void sts16(uint32_t a, uint32_t v) { asm volatile("st.shared.u16 [%0], %1;" ::"r"(a), "h"((unsigned short)v) : "memory"); }
__device__ __forceinline__ void sts32(uint32_t a, uint32_t v) { asm volatile("st.shared.u32 [%0], %1;" ::"r"(a), "r"(v) : "memory"); }
__device__ __forceinline__ void stsf(uint32_t a, float v) { asm volatile("st.shared.f32 [%0], %1;" ::"r"(a), "f"(v) : "memory"); }
__device__ __forceinline__ void stsf2(uint32_t a, float x, float y) { asm volatile("st.shared.v2.f32 [%0], {%1,%2};" ::"r"(a), "f"(x), "f"(y) : "memory"); }
__device__ __forceinline__ void stsf4(uint32_t a, float x, float y, float z, float w) {
    asm volatile("st.shared.v4.f32 [%0], {%1,%2,%3,%4};" ::"r"(a), "f"(x), "f"(y), "f"(z), "f"(w) : "memory");
}
template <int ID, int N> __device__ __forceinline__ void bar_sync() { jitter(); asm volatile("bar.sync %0, %1;" ::"n"(ID), "n"(N) : "memory"); jitter(); }
template <int ID, int N> __device__ __forceinline__ void bar_arrive() { jitter(); asm volatile("bar.arrive %0, %1;" ::"n"(ID), "n"(N) : "memory"); jitter(); }
__device__ __forceinline__ void fence_async() { asm volatile("fence.proxy.async.shared::cta;" ::: "memory"); }
__device__ __forceinline__ float shx(float v, int m) { return __shfl_xor_sync(0xffffffffu, v, m); }
__device__ __forceinline__ float shi(float v, int l) { return __shfl_sync(0xffffffffu, v, l); }
__device__ __forceinline__ uint32_t shi(uint32_t v, int l) { return __shfl_sync(0xffffffffu, v, l); }
__device__ __forceinline__ uint32_t opaque(uint32_t x) { asm volatile("mov.u32 %0, %0;" : "+r"(x)); return x; }
__device__ __forceinline__ const char* opaque(const char* x) { asm volatile("mov.u64 %0, %0;" : "+l"(x)); return x; }
constexpr float LOG2E = 1.4426950408889634f, SCALE = 0.07216878364870322f;

#define TRACE(idx) do {} while (0)
#define TRACES(slot) do {} while (0)

__device__ __forceinline__ uint32_t probe_near(const Params& p, int w, int lane) {
    const int cta = blockIdx.x;
    const char* pr = p.scr + SCR_O + head_off(cta >> 2) + 2048 + w * 256 + (cta & 3) * 64;
    st_pkt2_if(lane < 4, pr + lane * 16, 0, 0, 0, 0);
    uint32_t best0 = ~0u, best1 = ~0u;
#pragma unroll 1
    for (int i = w & 1; i < 6 + (w & 1); i++) {
        uint32_t c = clk32(), v = 0;
        if (lane == 0) asm volatile("atom.relaxed.gpu.global.add.u32 %0, [%1], 1;" : "=r"(v) : "l"(pr + (i & 1) * HALF) : "memory");
        c += __shfl_sync(0xffffffffu, v, 0) >> 16;
        c = clk32() - c;
        if (i & 1) best1 = min(best1, c); else best0 = min(best0, c);
    }
    return min(best0, 0xffffu) | min(best1, 0xffffu) << 16;
}
__device__ __forceinline__ uint32_t near_half() {
    const uint4 a = lds128(SM_NEAR), b = lds128(SM_NEAR + 16);
    const uint32_t m = __vminu2(__vminu2(__vminu2(a.x, a.y), __vminu2(a.z, a.w)), __vminu2(__vminu2(b.x, b.y), __vminu2(b.z, b.w)));
    return head_near(blockIdx.x >> 2, ((m & 0xffffu) > m >> 16) != (CFG(FLIP) != 0) ? HALF : 0);
}

__device__ __forceinline__ int kv_group(int k, int t) {
    const int cta = blockIdx.x;
    return ((k * NHEAD + (cta >> 2)) * SK + (SK - WIN) + (CFG(ILV) == 1 ? (cta & 3) * 32 + t * 128 : (cta & 3) * 64 + (t >> 1) * 256 + (t & 1) * 32)) / 8;
}
__device__ __forceinline__ uint32_t phase_ns() { return (((blockIdx.x >> 2) * 13) & 31) * CFG(STAG) / 32; }

__device__ __forceinline__ void ln_fast(float s, float q, float& mean, float& rstd) {
    mean = s * (1.f / DM);
    asm("rsqrt.approx.ftz.f32 %0, %1;" : "=f"(rstd) : "f"(fmaxf(fmaf(-mean, mean, fmaf(q, 1.f / DM, 1e-5f)), 1e-5f)));
}
__device__ __forceinline__ void q_role(const Params& p, int lane) {
    const int cta = blockIdx.x;
    mbar_wait(bar_at(B_EP), 0);
    const uint32_t epoch = lds32(SM_EPOCH), near = head_near(cta >> 2, near_half());
    auto sums = [&](float& S0, float& S1) {
        bar_sync<3, 288>();
        const uint32_t ra = SM_PQ + lane * 16;
        S0 = sum8(lds128(ra), lds128(ra + 1024)); S1 = sum8(lds128(ra + 512), lds128(ra + 1536));
    };
    float cs0, cs1;
    {
        uint32_t q0 = 0, q1 = 0, q2 = 0, q3 = 0;
#pragma unroll 1
        for (int r = 0; r < NB; r++) {
            sums(cs0, cs1);
            bar_arrive<7, 288>();
            q0 = q1; q1 = q2; q2 = q3; q3 = pack2(cs0, cs1);
        }
        const uint32_t t0 = shi(q3, 3 * lane - 72), t1 = shi(q3, 3 * lane - 71), t2 = shi(q3, 3 * lane - 70), tag = epoch << 8 | 0x40;
        const char* box = p.scr + SCR_O + head_off(cta >> 2) + 2048 + (lane >> 2) * 256 + (lane & 3) * 16;
        st_pkt2_if(true, box + (cta & 3) * 64, lane < 24 ? q0 : t0, lane < 24 ? q1 : t1, lane < 24 ? q2 : t2, tag);
        const uint32_t qd = SM_Q + (lane < 24 ? lane * 4 : 3 * 384 + (lane - 24) * 12), step = lane < 24 ? 384 : 4;
#pragma unroll 1
        for (int j = 0; j < 4; j++) {
            uint4 v;
            SPIN_DECL;
            do {
                __nanosleep(200);
                v = ld_pkt(box + near + j * 64);
                SPIN_CHECK(j);
            } while (__any_sync(0xffffffffu, v.w != tag));
            sts32(qd + j * 96, v.x); sts32(qd + j * 96 + step, v.y); sts32(qd + j * 96 + 2 * step, v.z);
        }
        mbar_arrive(bar_at(B_QR));
    }
    sums(cs0, cs1);
    bar_arrive<7, 288>();
    const char* const src = p.scr + SCR_Q + head_off(cta >> 2) + lane * 8 + near;
    const char* const dst = src + (cta & 3) * 192;
    const uint32_t qd = SM_Q + NB * 384 + lane * 4;
    st_pkt82_if(lane < 24, dst - near, 0, 0);
#pragma unroll 1
    for (int k = 0; k < NB; k++) {
        float S0, S1, mean, rstd;
        sums(S0, S1);
        ln_fast(shi(S1, 24), shi(S0, 24), mean, rstd);
        const uint32_t qq = pack2(fmaf(-mean, cs0, S0) * rstd, fmaf(-mean, cs1, S1) * rstd), tag = epoch * NB + k;
        st_pkt8_if(lane < 24, dst + ((int)HALF - 2 * (int)near), qq, tag);
        st_pkt8_if(lane < 24, dst, qq, tag);
        TRACES(k * 12 + 5);
        uint2 a, b, c;
        SPIN_DECL;
        do {
            a = ld_pkt8(src); b = ld_pkt8(src + 256); c = ld_pkt8(src + 512);
            SPIN_CHECK(k);
            sts32(qd, a.x); sts32(qd + 128, b.x); sts32(qd + 256, c.x);
        } while (__any_sync(0xffffffffu, a.y != tag || b.y != tag || c.y != tag));
        mbar_arrive(bar_at(B_QR));
    }
}

struct Maps { CUtensorMap k, v, q, o, g, u; };
__device__ __forceinline__ void load_role(const Params& p, const CUtensorMap* tmKV, int lane, uint32_t t0) {
    const int cta = blockIdx.x;
    t0 += phase_ns();
#pragma unroll 1
    for (int i = 1; i < 5; i++) {
        wait_ns(t0 + i * CFG(TICK0));
        if (elect_one()) l2_prefetch(p.wq + (size_t)(128 * i + cta) * 12288, 12288);
        TRACE(230 + i);
    }
    uint32_t plan[2];
#pragma unroll
    for (int i = 0; i < 2; i++) {
        const int j = lane + 32 * i, k = j >> 4, t = j & 15, u = t >> 1, jw = j - CFG(WIN);
        const int sb = k == 0 ? B_WC + (t >= 8) + (t >= 14) : t >= 12 ? B_RK + u - 5 : t >= 4 ? B_RR + t - 4 : t >= 2 ? B_RP : k > 1 ? B_RK + 3 : B_RR + t;
        const uint32_t sw = sb * 8 | (j < 18 ? 0 : (t >= 12 || u == 1 ? k - 1 : k) & 1) << 9;
        plan[i] = sw | (jw < 0 ? sw : (B_F1 + (jw & 15)) * 8 | ((jw >> 4) & 1) << 9) << 10 |
                  (slot_at(slots(k), t < 8 ? pass_nibble(k, u) : u) * 2 + (t & 1)) << 20 | (t < 10 && j >= 8 && j < 56) << 25;
    }
    bar_sync<6, 64>();
    wait_ns(t0 + kb_ns(60));
    if (elect_one()) bulk_load(ST_WD, p.wd + cta * 15360, 15360, bar_at(B_W));
    TRACE(235);
#pragma unroll 1
    for (int i = 0; i < 5; i++) {
        wait_ns(t0 + kb_ns(75) + i * kb_ns(6));
        if (elect_one()) { l2_prefetch(p.wg + (128 * i + cta) * 3072, 3072); l2_prefetch(p.wu + (128 * i + cta) * 3072, 3072); }
    }
#pragma unroll 1
    for (int i = 0; i < 6; i++) {
        wait_ns(t0 + kb_ns(105) + min(i, 4) * kb_ns(10));
        if (elect_one()) l2_prefetch(p.wo + (size_t)((cta >> 2) * DH + 32 * i + 8 * (cta & 3)) * 1280, 10240);
    }
    t0 += batch_ns(0);
    int jp = 0, shift = 0;
    uint32_t earliest = t0;
    auto requested = [&](uint32_t now) {
        shift = max(max(shift - CFG(GAIN), 0), (int)(now - t0) - (jp < 12 ? CFG(LMAX0) : CFG(LMAX)));
        TRACE(128 + jp);
        t0 += tick_ns(++jp);
    };
    const int grp0 = kv_group(0, 0);
    auto group = [&](int j) { return grp0 + (j >> 4) * (NHEAD * SK / 8) + (CFG(ILV) == 1 ? (j & 7) * 16 : (j & 6) * 16 + (j & 1) * 4); };
#pragma unroll 1
    for (int j = 0; j < 16 * NB; j++) {
        const uint32_t pl = __shfl_sync(0xffffffffu, j & 32 ? plan[1] : plan[0], j);
        const int jmax = min(j + CFG(PMAX), 16 * NB);
        jitter();
        uint32_t now;
        SPIN_DECL;
        while (true) {
            const bool ok = mbar_test2(SM_BAR + (pl & 511), (pl >> 9) & 1, SM_BAR + ((pl >> 10) & 511), (pl >> 19) & 1);
            now = now_ns();
            const int late = now - t0 - shift;
            if (ok && (jp > j ? (int)(now - earliest) : late) >= 0) break;
            if (late >= (jp > j ? 0 : CFG(PGRACE)) && jp < jmax) {
                if (elect_one())
                    asm volatile("cp.async.bulk.prefetch.tensor.4d.L2.global [%0, {%1, %1, %1, %2}];" ::"l"(tmKV + ((jp >> 3) & 1)), "r"(0), "r"(group(jp)) : "memory");
                requested(now);
            }
            SPIN_CHECK(j);
        }
        if (elect_one()) {
            mbar_expect_tx(bar_at(B_F1 + (j & 15)), TILE);
            tma_tile(SB + ((pl >> 20) & 31) * TILE, tmKV + ((j >> 3) & 1), group(j), bar_at(B_F1 + (j & 15)), pl >> 25 ? POL_NORMAL : POL_FIRST);
        }
        TRACE(256 + j);
        if ((j & 15) == 15) TRACES(88 + (j >> 4));
        earliest = now + CFG(VSTEP);
        if (jp == j) requested(now);
    }
}

__device__ __forceinline__ void reload_role(const Params& p, const Maps* tm, uint32_t t0) {
    const CUtensorMap* const tmK = &tm->k;
    const CUtensorMap* const tmV = &tm->v;
    const int cta = blockIdx.x;
    t0 += CFG(TICK0) + CFG(WLAG) + phase_ns();
#pragma unroll 1
    for (int i = 0; i < 5; i++) {
        wait_ns(t0 + i * CFG(TICK0));
        if (elect_one()) tma2d(ST_WQ + i * 12288, &tm->q, 48 * cta, 128 * i, bar_at(B_W));
        TRACE(240 + i);
        if (i == 1) bar_sync<5, 480>();
    }
#pragma unroll 1
    for (int i = 0, o = 0; i < 10;) {
        const uint32_t now = now_ns() - t0;
        if (o < 6 && (int)now >= kb_ns(105) + o * kb_ns(10)) {
            if (elect_one()) tma2d(ST_WO + o * 10240, &tm->o, 160 * (cta & 3), (cta >> 2) * DH + 32 * o, bar_at(B_W + 1));
            o++;
        } else if ((int)now >= kb_ns(77) + i * CFG(GSTEP) && (i < 9 || o == 6)) {
            if (elect_one()) tma2d(ST_WG + (i & 1) * 20480 + (i >> 1) * 4096, i & 1 ? &tm->u : &tm->g, (12 * cta) & ~7, 128 * (i >> 1), bar_at(B_W + 2));
            i++;
        }
    }
#pragma unroll 1
    for (int k = 0; k < NB - 1; k++) {
        mbar_wait(bar_at(B_RK), k & 1);
        if (elect_one()) {
            const uint32_t dst = SB + slot_at(slots(k), 0) * PAIR;
            mbar_expect_tx(bar_at(B_FL), PAIR);
            tma_tile(dst, tmV, kv_group(k, 0), bar_at(B_FL), POL_FIRST);
            tma_tile(dst + TILE, tmV, kv_group(k, 1), bar_at(B_FL), POL_FIRST);
        }
        mbar_wait(bar_at(B_RV), k & 1);
        uint32_t due = now_ns();
        if (elect_one()) mbar_expect_tx(bar_at(B_F3), 4 * PAIR);
#pragma unroll 1
        for (int t = 0; t < 8; t++) {
            wait_ns(due);
            due += k == NB - 2 ? CFG(RSTEP3) : CFG(RSTEP);
            if (elect_one())
                tma_tile(SB + slot_at(slots(k + 1), t >> 1) * PAIR + (t & 1) * TILE, tmK, kv_group(k + 1, t), bar_at(B_F3), POL_FIRST);
        }
        TRACE(121 + k);
    }
}

__device__ __forceinline__ void zero_role(const Params& p, int lane, uint32_t t0) {
    const int cta = blockIdx.x;
    unsigned ticket = 0;
    if (lane == 0) ticket = atomicAdd(&g_epoch, 1u);
    const uint32_t epoch = __shfl_sync(0xffffffffu, ticket, 0) / NCTA + 1;
    if (lane == 0) { sts32(SM_EPOCH, epoch); mbar_arrive(bar_at(B_EP)); }
    mbar_wait(bar_at(B_EP), 0);
#pragma unroll 1
    for (int k = 0; k < NB + 2; k++) {
        lane = opaque(lane);
        const int cl = 2 * (cta & 15) + (lane & 1);
        const int col = 80 * (cta >> 4) + (cl & 2 ? 48 : 0) + (cl >> 2) + (cl & 1 ? 8 : 0);
        const char* own = p.scr + (cl >> 2) * 256 + (cl & 3) * 16;
        uint32_t v0 = 0, v1 = 0, v2 = 0;
        if (lane < 4 && k < NB) {
            const unsigned short* xp = p.x + k * DM + col;
            v0 = __ldg(xp) << 16; v1 = __ldg(xp + 16) << 16; v2 = cl & 2 ? 0 : __ldg(xp + 32) << 16;
        }
        uint4 r;
        if (k == 1) mbar_wait(bar_at(B_RK), 0);
        if (k > 1) {
            mbar_wait(bar_at(B_FIN), k & 1);
            r = lds128(SM_FIN + (lane & 1) * 16);
        }
        if (k < NB) {
            const int lg = lane >> 3, ty = (lane & 7) >> 1;
            const char* dst = own + acc_off((k - (lg >> 1)) & 3, lg != 0, cta >> 4) + ty * HALF;
            wait_ns(t0 + batch_ns(k) + CFG(ZTILE) * CFG(TICK0));
            if (lg == 0 || (lg == 1 && (ty < 2 || k == NB - 1)) || (lg == 2 && k > 0 && ty > 1)) {
                st_pkt(dst, v0, v1, v2, ~0u);
                asm volatile("atom.relaxed.gpu.global.exch.b32 %0, [%1+12], %2;" : "=r"(v0) : "l"(dst), "r"(lane < 4 ? 0x3f800000u : 0u) : "memory");
                v0 = ~v0;
            }
            if (__any_sync(0xffffffffu, v0 != 0)) __trap();
            const char* cnt = p.scr + SCR_COUNT;
            if (lane < 2) asm volatile("red.relaxed.gpu.global.add.u32 [%0], 1;" ::"l"(cnt + lane * HALF) : "memory");
            const uint32_t target = ((epoch - 1) * NB + k + 1) * NCTA;
            cnt += near_half();
            SPIN_DECL;
            uint32_t v;
            do {
                __nanosleep(100);
                asm volatile("ld.relaxed.gpu.global.u32 %0, [%1];" : "=r"(v) : "l"(cnt) : "memory");
                SPIN_CHECK(v);
            } while (__any_sync(0xffffffffu, (int)(v - target) < 0));
        }
        __syncwarp();
        if (lane == 0) mbar_arrive(bar_at(B_Z));
        if (k > 1) {
            const int b = k - 2;
            const char* src = own + acc_off(b, 1, cta >> 4) + (2 + ((lane >> 1) & 1)) * HALF;
            unsigned short* o = p.out + b * DM + col + (lane >> 2) * 16;
            const bool on = !(lane & 2) && lane < (cl & 2 ? 8 : 12);
            wait_clk(clk32() + CFG(DLY_F));
            float cnt;
            SPIN_DECL;
            do {
                const uint4 v = ld_pkt(src);
                SPIN_CHECK(k);
                cnt = F(v.w) + shx(F(v.w), 2);
                const float y0 = F(v.x) + shx(F(v.x), 2), y1 = F(v.y) + shx(F(v.y), 2), y2 = F(v.z) + shx(F(v.z), 2);
                const uint32_t x01 = badd2(r.x, badd2(r.y, bmul2(pack2(y0, y1), r.w)));
                const uint32_t x2 = badd2(r.z, badd2(r.z >> 16, bmul2(pack2(y2, 0.f), r.w)));
                if (cnt == NCTA && on) *o = lane < 4 ? x01 : lane < 8 ? x01 >> 16 : x2;
            } while (__any_sync(0xffffffffu, cnt != NCTA));
            TRACES((2 * b + 1) * 6 + 4);
        }
    }
}

__host__ __device__ constexpr uint32_t desc_lo(uint32_t addr) { return ((addr & 0x3FFFFu) >> 4) | (1u << 16); }
constexpr uint32_t DESC_HI_TILE = (3072u >> 4) | (1u << 30);
constexpr uint32_t DESC_HI_VEC = 1u;
template <int TA, int AOFF, int BOFF>
__device__ __forceinline__ void wgmma_n8(float (&d)[4], uint32_t alo, uint32_t blo, int accumulate) {
    asm volatile("{\n.reg .pred p;\n.reg .b32 a, b;\n.reg .b64 da, db;\nsetp.ne.b32 p, %6, 0;\n"
                 "add.u32 a, %4, %8;\nadd.u32 b, %5, %9;\nmov.b64 da, {a, %10};\nmov.b64 db, {b, %11};\n"
                 "wgmma.mma_async.sync.aligned.m64n8k16.f32.bf16.bf16 {%0,%1,%2,%3}, da, db, p, 1, 1, %7, 0;\n}"
                 : "+f"(d[0]), "+f"(d[1]), "+f"(d[2]), "+f"(d[3])
                 : "r"(alo), "r"(blo), "r"(accumulate), "n"(TA), "n"(AOFF >> 4), "n"(BOFF >> 4), "n"(DESC_HI_TILE), "n"(DESC_HI_VEC));
}
template <int KS, int END>
__device__ __forceinline__ void qk_steps(float (&d)[4], uint32_t alo, uint32_t blo) {
    if constexpr (KS < END) {
        wgmma_n8<0, (KS >> 2) * 1024 + (KS & 3) * 32, KS * 32>(d, alo, blo, KS > 0);
        qk_steps<KS + 1, END>(d, alo, blo);
    }
}
__device__ __forceinline__ void pv_steps(float (&e)[3][4], uint32_t alo, uint32_t blo, int acc) {
    wgmma_n8<1, 0, 0>(e[0], alo, blo, acc); wgmma_n8<1, 1024, 0>(e[1], alo, blo, acc); wgmma_n8<1, 2048, 0>(e[2], alo, blo, acc);
    wgmma_n8<1, 6144, 32>(e[0], alo, blo, 1); wgmma_n8<1, 7168, 32>(e[1], alo, blo, 1); wgmma_n8<1, 8192, 32>(e[2], alo, blo, 1);
}
__device__ __forceinline__ void wg_fence() { asm volatile("wgmma.fence.sync.aligned;" ::: "memory"); }
__device__ __forceinline__ void wg_commit() { asm volatile("wgmma.commit_group.sync.aligned;" ::: "memory"); }
template <int N> __device__ __forceinline__ void wg_wait() { asm volatile("wgmma.wait_group.sync.aligned %0;" ::"n"(N) : "memory"); }
__device__ __forceinline__ void acc_ready(float (&d)[4]) { asm volatile("" : "+f"(d[0]), "+f"(d[1]), "+f"(d[2]), "+f"(d[3]) :: "memory"); }
__device__ __forceinline__ uint32_t score_pair(float (&d)[4]) {
    acc_ready(d);
    const uint32_t r = pack2(d[0], d[2]);
    return pack2(bf_lo(r) * SCALE, bf_hi(r) * SCALE);
}

__device__ __forceinline__ void attention_role(const Params& p, int w, int lane) {
    const int cta = blockIdx.x, t4 = lane & 3, g = lane >> 2;
    mbar_wait(bar_at(B_EP), 0);
    const uint32_t tag0 = lds32(SM_EPOCH) * NB;
    const char* const odst = p.scr + SCR_O + head_off(cta >> 2) + (2 * w + (g >> 2)) * 256 + (cta & 3) * 64 + (g & 3) * 16;
    const uint32_t pdst = SM_P + ((t4 + 3) & 3) * PSTR + (16 * w + g) * 2;
    auto softmax = [&](uint32_t& sc, int ps) -> uint32_t {
        const float s0 = bf_lo(sc), s1 = bf_hi(sc);
        int key = __float_as_int(fmaxf(s0, s1));
        key ^= (key >> 31) & 0x7fffffff;
        key = __reduce_max_sync(0xffffffffu, key);
        sts32(SM_MAX + w * 4, key);
        bar_sync<4, 128>();
        const uint4 mx = lds128(SM_MAX);
        key = max(max((int)mx.x, (int)mx.y), max((int)mx.z, (int)mx.w));
        key ^= (key >> 31) & 0x7fffffff;
        const float mb = __int_as_float(key) * LOG2E;
        const uint32_t pp = pack2(fast_ex2(fmaf(s0, LOG2E, -mb)), fast_ex2(fmaf(s1, LOG2E, -mb)));
        sts16(pdst + ps * 4 * PSTR, pp); sts16(pdst + ps * 4 * PSTR + 16, pp >> 16);
        fence_async();
        bar_sync<4, 128>();
        sc = pp;
        return key;
    };
    auto put_sum = [&](uint32_t pp, int ps) {
        uint32_t fs;
        asm volatile("redux.sync.add.u32 %0, %1, 0xffffffff;" : "=r"(fs) : "r"(__float2uint_rn((bf_lo(pp) + bf_hi(pp)) * 8388608.f)) : "memory");
        sts32(SM_SUM + ps * 16 + w * 4, fs);
    };
    auto aux_word = [&](uint32_t mx, const uint4& u, int k) {
        const float l = __uint2float_rn((u.x + u.y) + (u.z + u.w)) * (1.f / 8388608.f);
        return (g < 4 ? mx : (__float_as_uint(l) + 0x80u) & 0xffffff00u) | ((tag0 + k) & 0x7fu) | 0x80u;
    };
    auto send = [&](float (&e)[3][4], uint32_t aux, int ps) {
        acc_ready(e[0]); acc_ready(e[1]); acc_ready(e[2]);
        const uint32_t o0 = pack2(e[0][0], e[0][2]), o1 = pack2(e[1][0], e[1][2]), o2 = pack2(e[2][0], e[2][2]);
        st_pkt2_if(t4 == 0, odst + ps * 2048, o0, o1, o2, aux);
        mbar_arrive_if(lane == 0, bar_at(ps ? B_RV : B_PS));
    };
    mbar_wait(bar_at(B_QR), 0);
    TRACES(73);
#pragma unroll 1
    for (int it = 0; it <= NB; it++) {
        uint32_t m1 = 0;
        if (it < NB) {
            const uint32_t tab = slots(it);
            const uint32_t ka = SB + (2 * w + ((lane >> 3) & 1)) * 3072 + (lane & 7) * 128 + (((lane >> 4) ^ (lane & 7)) << 4);
            const uint32_t qa = SM_Q + it * 384 + (lane >> 3) * 16;
            uint32_t sc = 0;
#pragma unroll 1
            for (int u = 0; u < 4; u++) {
                const uint32_t base = ka + slot_at(tab, pass_nibble(it, u)) * PAIR;
                mbar_wait(bar_at(B_F1 + 2 * u + (w >> 1)), it & 1);
                float d0[4] = {}, d1[4] = {};
#pragma unroll
                for (int c = 0; c < 6; c++) {
                    uint32_t a0[4], a1[4], b[4];
                    ldsm4(b, qa + c * 64);
                    ldsm4(a0, (base ^ ((c & 1) * 64)) + (c >> 1) * 1024);
                    ldsm4(a1, (base ^ ((c & 1) * 64 + 32)) + (c >> 1) * 1024);
                    mma16816(d0, a0[0], a0[1], a0[2], a0[3], b[0], b[1]);
                    mma16816(d1, a1[0], a1[1], a1[2], a1[3], b[2], b[3]);
                }
                const uint32_t r = pack2(d0[0] + d1[0], d0[2] + d1[2]);
                mbar_arrive_if(lane == 0, bar_at(B_RR + 2 * u + (w >> 1)));
                if (t4 == ((u + 1) & 3)) sc = pack2(bf_lo(r) * SCALE, bf_hi(r) * SCALE);
            }
            m1 = softmax(sc, 0);
            put_sum(sc, 0);
        }
        if (it > 0) {
            const int k = it - 1;
            const uint32_t tab = slots(k);
            const uint32_t v0 = slot_at(tab, k < NB - 1 ? 0 : 4);
            TRACES(48 + k * 6);
            if (k > 0) mbar_wait(bar_at(B_F3), it & 1);
            mbar_wait(bar_at(B_QR), it & 1);
            fence_async();
            TRACES(49 + k * 6);
            float d[4][4] = {};
            const bool busy = k < NB - 1;
#pragma unroll
            for (int u = 0; u < 4; u++) {
                const uint32_t alo = desc_lo(SB) + slot_at(tab, u) * (PAIR >> 4), blo = desc_lo(SM_Q + 4 * 384);
                wg_fence();
                qk_steps<0, 6>(d[u], alo, blo);
                wg_commit();
                if (busy) {
                    wg_wait<1>();
                    if (u > 0) mbar_arrive_if(lane == 0, bar_at(B_RK + u - 1));
                }
                wg_fence();
                qk_steps<6, 12>(d[u], alo, blo);
                wg_commit();
                if (u < 3 && busy) wg_wait<1>();
            }
            wg_wait<2>();
            uint32_t sc = shi(score_pair(d[0]), lane & 28), s = shi(score_pair(d[1]), lane & 28);
            if (t4 == 2) sc = s;
            s = shi(score_pair(d[2]), lane & 28);
            if (t4 == 3) sc = s;
            wg_wait<0>();
            s = score_pair(d[3]);
            if (t4 == 0) sc = s;
            mbar_arrive_if(lane == 0, bar_at(B_RK + 3));
            TRACES(50 + k * 6);
            const uint32_t m2 = softmax(sc, 1);
            TRACES(51 + k * 6);
            float e[3][4] = {};
#pragma unroll
            for (int t = 0; t < 8; t++) {
                const int pr = ((t >> 1) + 1) & 3;
                if (t == 6 && k < NB - 1) mbar_wait(bar_at(B_FL), k & 1);
                wg_fence();
                pv_steps(e, desc_lo(SB + (t & 1) * TILE) + (pr ? slot_at(tab, 4 + pr) : v0) * (PAIR >> 4), desc_lo(SM_P + (4 + pr) * PSTR + (t & 1) * 64), t > 0);
                wg_commit();
                if (t < 7 && busy) wg_wait<1>();
                if (t == 1) put_sum(sc, 1);
            }
            bar_sync<4, 128>();
            const uint32_t aux = opaque(aux_word(m2, lds128(SM_SUM + 16), k));
            wg_wait<0>();
            send(e, aux, 1);
            TRACES(52 + k * 6);
        }
        if (it < NB) {
            const uint32_t tab = slots(it);
            if (it == 0) st_pkt2_if(t4 == 0, odst, 0, 0, 0, 0);
            bar_sync<4, 128>();
            const uint32_t aux = opaque(aux_word(m1, lds128(SM_SUM), it));
            float e[3][4] = {};
#pragma unroll 1
            for (int u = 0; u < 4; u++) {
                const uint32_t alo = desc_lo(SB) + slot_at(tab, 4 + u) * (PAIR >> 4), blo = desc_lo(SM_P) + u * (PSTR >> 4);
                mbar_wait(bar_at(B_F1 + 8 + 2 * u), it & 1);
                wg_fence();
                pv_steps(e, alo, blo, u > 0);
                wg_commit();
                wg_wait<1>();
                if (u == 1) mbar_arrive_if(lane == 0, bar_at(B_RP));
                mbar_wait(bar_at(B_F1 + 9 + 2 * u), it & 1);
                wg_fence();
                pv_steps(e, alo + (TILE >> 4), blo + 4, 1);
                wg_commit();
                wg_wait<1>();
            }
            wg_wait<0>();
            send(e, aux, 0);
            TRACES(53 + it * 6);
        }
    }
}

__device__ __forceinline__ void ln_finish(float s, float q, float& mean_b, float& rden) {
    const float mean = s * (1.f / DM);
    const float var = fmaxf(fmaf(q, 1.f / DM, -mean * mean), 0.f);
    mean_b = bfr(mean);
    rden = fast_rcp(bfr(fast_sqrt(bfr(bfr(var) + 1e-5f))));
}
__device__ __forceinline__ uint32_t ln_apply(uint32_t w, float mean_b, float rden) {
    const uint32_t d = bsub2(w, __byte_perm(__float_as_uint(mean_b), 0, 0x3232));
    return pack2(bf_lo(d) * rden, bf_hi(d) * rden);
}
__device__ __forceinline__ void put_x(uint32_t x01, uint32_t x2, uint32_t wa, bool e2) {
    jitter();
    sts16(wa, x01); sts16(wa + 8, x01 >> 16);
    sts16_if(!e2, wa + 16, x2);
}
__device__ __forceinline__ void get_x(uint32_t (&b)[10], uint32_t ra) {
    __syncwarp();
    const uint4 u = lds128(ra), v = lds128(ra + 16);
    const uint2 z = lds64(ra + 32);
    b[0] = u.x; b[1] = u.y; b[2] = u.z; b[3] = u.w; b[4] = v.x; b[5] = v.y; b[6] = v.z; b[7] = v.w; b[8] = z.x; b[9] = z.y;
}
__device__ __forceinline__ float fold(float a, float b, bool sel, int m) { return (sel ? b : a) + shx(sel ? a : b, m); }

__device__ __forceinline__ void chain_role(const Params& p, int w, int lane) {
    const int cta = blockIdx.x, h = cta >> 2, s = cta & 3;
    const int g = lane >> 2, t4 = lane & 3;
    const bool e1 = t4 & 1, e2 = t4 & 2;
    uint32_t wq[5][3][4], wo[3][5][4], wg[5][4], wh[5][2], wd[4][4];
    const int col0 = 80 * w + (e2 ? 48 : 0) + g + (e1 ? 8 : 0);
    const uint32_t xw = opaque(SM_X + w * 384 + 48 * (g >> 1) + (e2 ? 24 : 0) + (e1 ? 4 : 0) + 2 * (g & 1));
    const uint32_t xr = opaque(g == 1 ? SM_ONES : SM_X + w * 384 + (g == 3 ? 192 : 0) + 48 * t4);
    TRACES(75);
    sts32_if(lane < 12, SM_ONES + lane * 4, 0x3f803f80u);
    uint32_t zero = lane >> 5;
    const int mi = lane >> 3, mr = lane & 7;
    mbar_wait(bar_at(B_W), 0);
    TRACES(74);
    sts16(xw + 192, lds16(ST_X + 5120 + col0 * 2)); sts16(xw + 200, lds16(ST_X + 5120 + col0 * 2 + 32));
    sts16_if(!e2, xw + 208, lds16(ST_X + 5120 + col0 * 2 + 64));
#pragma unroll
    for (int i = 0; i < 5; i++)
#pragma unroll
        for (int mt = 0; mt < 3; mt++) ldsm4t(wq[i][mt], ST_WQ + (80 * w + 16 * i + mr + 8 * (mi >> 1)) * 96 + 32 * mt + 16 * (mi & 1), zero);
    const bool odd = cta & 1;
    const uint32_t lo = ST_WD + (mr + (odd ? 4 : 0)) * 1280 + 160 * w + 16 * (mi & 1);
    const uint32_t hi = ST_WD + ((mr & 3) + (odd ? 0 : 8)) * 1280 + 160 * w + 16 * (mi & 1);
    ldsm4t(wd[0], lo + 96 * (mi >> 1), zero);
    ldsm4t(wd[1], lo + 96 * (mi >> 1) + 32, zero);
    ldsm4t(wd[2], (mi < 2 ? lo : hi) + 64, zero);
    ldsm4t(wd[3], hi + 32 * (mi >> 1) + 96 * (mr >> 2), zero);
    fence_async();
    __syncwarp();
    mbar_arrive_if(lane == 0, bar_at(B_WC));
    mbar_wait(bar_at(B_EP), 0);
    const uint32_t near = __shfl_sync(0xffffffffu, near_half(), 0);
    uint32_t x01 = 0, x2 = 0, nx01 = 0, nx2 = 0;
#pragma unroll 1
    for (int n = -5; n < NROUND; n++) {
        const bool last = (ORD_LAST >> (n & 15)) & 1, head = !((ORD_NO_HEAD >> (n & 15)) & 1);
        const int k = (ORD_BATCH >> (2 * (n & 15))) & 3;
        if (n > -5 && n <= 0) bar_sync<7, 288>();
        else if (!last) bar_sync<2, 256>();
        TRACES(n <= 0 ? 83 + n : 95);
        const char* const slice = p.scr + acc_off(k, last, w);
        const char* const cell = opaque(slice + g * 256 + t4 * 16);
        if (n < -1) {
            const uint32_t xa = ST_X + (n + 5) * 1280, ln = opaque(lane);
            const int col0 = 80 * w + (ln & 2 ? 48 : 0) + (ln >> 2) + (ln & 1 ? 8 : 0);
            float sm = 0.f, sq = 0.f;
#pragma unroll
            for (int i = 0; i < 5; i++) {
                const uint2 c = lds64(xa + i * 256 + ln * 8);
                sm += (bf_lo(c.x) + bf_hi(c.x)) + (bf_lo(c.y) + bf_hi(c.y));
                sq = fmaf(bf_lo(c.x), bf_lo(c.x), fmaf(bf_hi(c.x), bf_hi(c.x), fmaf(bf_lo(c.y), bf_lo(c.y), fmaf(bf_hi(c.y), bf_hi(c.y), sq))));
            }
            x01 = lds16(xa + col0 * 2) | lds16(xa + col0 * 2 + 32) << 16;
            x2 = lds16(xa + col0 * 2 + 64);
#pragma unroll
            for (int o = 16; o; o >>= 1) { sm += shx(sm, o); sq += shx(sq, o); }
            float mean_b, rden;
            ln_finish(sm, sq, mean_b, rden);
            x01 = ln_apply(x01, mean_b, rden);
            x2 = ln_apply(x2, mean_b, rden);
            put_x(x01, x2, xw, e2);
        } else {
            if (n >= 0 && head) {
                if (!last || n == NROUND - 1) mbar_wait(bar_at(B_Z), (k + last) & 1);
                const char* src = p.scr + SCR_O + head_off(h) + head_near(h, near) + last * 2048 + (w & 6) * 256 + (lane & 15) * 16;
                const uint32_t tag = (lds32(SM_EPOCH) * NB + k) | 0x80u;
                mbar_wait(bar_at(last ? B_RV : B_PS), k & 1);
                uint4 v, z;
                {
                    SPIN_DECL;
                    do {
                        v = ld_pkt(src); z = ld_pkt(src + 256);
                        SPIN_CHECK(n);
                    } while (__any_sync(0xffffffffu, (((v.w ^ tag) | (z.w ^ tag)) & 0xffu) != 0));
                }
                TRACES(tr + 0);
                float a[3][4] = {};
                const uint32_t bb[3][2] = {{v.x, v.y}, {z.x, z.y}, {v.z, z.z}};
                float sa, sb, rl;
#pragma unroll
                for (int i = 0; i < 3; i++) {
                    const uint32_t l0 = g < 4 ? bb[i][0] : 0, l1 = g < 4 ? bb[i][1] : 0, h0 = g < 4 ? 0 : bb[i][0], h1 = g < 4 ? 0 : bb[i][1];
#pragma unroll
                    for (int mt = 0; mt < 5; mt++)
                        mma16816(a[mt % 3], wo[i][mt][0], wo[i][mt][1], wo[i][mt][2], wo[i][mt][3], mt < 3 ? l0 : h0, mt < 3 ? l1 : h1);
                    if (i == 0) {
                        int key = v.w & 0xffffff00u;
                        key ^= (key >> 31) & 0x7fffffff;
                        key = __reduce_max_sync(0xffffffffu, key);
                        key ^= (key >> 31) & 0x7fffffff;
                        const float ws = fast_ex2((F(v.w & 0xffffff00u) - __int_as_float(key)) * LOG2E);
                        sa = shi(ws, e1 ? 8 : 0); sb = shi(ws, e1 ? 12 : 4);
                        rl = ws * F(z.w & 0xffffff00u);
                        rl += shx(rl, 4);
                    }
                    if (i == 1) rl += shx(rl, 8);
                }
                float y[3];
#pragma unroll
                for (int j = 2; j < 5; j++) {
                    const int mt = j % 3;
                    y[mt] = fold(fmaf(a[mt][0], sa, a[mt][1] * sb), fmaf(a[mt][2], sa, a[mt][3] * sb), e1, 1);
                }
                const uint32_t pa = SM_PO + w * 512 + lane * 16;
                if (w < 2) {
                    const char* dst = opaque(cell + s * 16384);
                    rl = fast_rcp(rl);
                    bar_sync<1, 256>();
                    const uint4 c1 = lds128(pa), c2 = lds128(pa + 1024), c3 = lds128(pa + 2048);
                    red_cell2_if(true, dst, ((y[0] + F(c1.x)) + (F(c2.x) + F(c3.x))) * rl, ((y[1] + F(c1.y)) + (F(c2.y) + F(c3.y))) * rl,
                                 ((y[2] + F(c1.z)) + (F(c2.z) + F(c3.z))) * rl);
                } else {
                    stsf4(pa - 1024, y[0], y[1], y[2], 0.f);
                    bar_sync<1, 256>();
                }
                TRACES(tr + 1);
                if ((ORD_NO_TAIL >> n) & 1) continue;
                const uint32_t tsend = clk32();
                if (n == 0) {
                    st_pkt2_if(lane < 4, p.scr + SCR_O + head_off(h) + 2048 + w * 256 + s * 64 + lane * 16, 0, 0, 0, 0);
                    __syncwarp();
                } else if (!last) {
                    const char* nsrc = p.scr + acc_off(k - 1, 1, w) + near + g * 256 + t4 * 16;
                    SPIN_DECL;
                    do {
                        v = ld_pkt(nsrc);
                        SPIN_CHECK(n);
                        nx01 = pack2(F(v.x), F(v.y)); nx2 = pack2(F(v.z), 0.f);
                    } while (__any_sync(0xffffffffu, v.w != FULL_A));
                }
                wait_clk(tsend + (w < 2 ? 0 : 60) + (n < QUIET ? CFG(DLY_AL) : CFG(DLY_A)));
                {
                    SPIN_DECL;
                    do {
                        v = ld_pkt(cell + near);
                        SPIN_CHECK(n);
                        x01 = pack2(F(v.x), F(v.y));
                        x2 = pack2(F(v.z), 0.f);
                        put_x(x01, x2, xw, e2);
                    } while (__any_sync(0xffffffffu, v.w != FULL_A));
                }
                TRACES(tr + 2);
            } else if (n >= 0) {
                x01 = nx01; x2 = nx2;
                put_x(x01, x2, xw, e2);
            } else {
                mbar_wait(bar_at(B_W + 1), 0);
                const uint32_t ln = opaque(lane);
                const int mi = ln >> 3, mr = ln & 7;
                uint32_t zero = ln >> 5;
                TRACES(76);
#pragma unroll
                for (int i = 0; i < 3; i++) {
                    const int d = 16 * (w >> 1) + (mr >> 1) + 8 * (mr & 1) + (i < 2 ? 64 * (mi >> 1) + 4 * i : 128 + 4 * (mi >> 1));
#pragma unroll
                    for (int mt = 0; mt < 5; mt++) ldsm4t(wo[i][mt], ST_WO + d * 320 + 160 * (w & 1) + 32 * mt + 16 * (mi & 1), zero);
                }
                fence_async();
                __syncwarp();
                mbar_arrive_if(lane == 0, bar_at(B_WC + 1));
                mbar_wait(bar_at(B_W + 2), 0);
                TRACES(77);
#pragma unroll
                for (int i = 0; i < 5; i++) {
                    const uint32_t ga = ST_WG + (mi & 1) * 20480 + (80 * w + 16 * i + mr + 8 * (mi >> 1)) * 32;
                    uint32_t r[4];
                    ldsm4t(wg[i], ga + (odd ? 16 : 0), zero);
                    ldsm4t(r, ga + (odd ? 0 : 16), zero);
#pragma unroll
                    for (int kh = 0; kh < 2; kh++) {
                        const uint32_t moved = __shfl_xor_sync(0xffffffffu, odd ? r[2 * kh] : r[2 * kh + 1], 16);
                        wh[i][kh] = (g < 4) == odd ? moved : odd ? r[2 * kh + 1] : r[2 * kh];
                    }
                }
                fence_async();
                __syncwarp();
                mbar_arrive_if(lane == 0, bar_at(B_WC + 2));
                TRACES(72);
                x01 = 0x3f803f80u; x2 = 0x3f80u;
                put_x(x01, x2, xw, e2);
            }
            uint32_t b[10];
            get_x(b, xr);
            float a[2][4] = {};
#pragma unroll
            for (int i = 0; i < 5; i++) {
                mma16816(a[0], wg[i][0], wg[i][1], wg[i][2], wg[i][3], b[2 * i], b[2 * i + 1]);
                mma16816(a[1], wh[i][0], b[2 * i], wh[i][1], b[2 * i + 1], b[2 * i], b[2 * i + 1]);
            }
            stsf(SM_PG + (w >> 2) * 512 + (g + 8 * t4) * 16 + (w & 3) * 4, e2 ? (e1 ? a[1][2] : a[1][0]) : (e1 ? a[0][2] : a[0][0]));
            const uint2 cs = lds64(SM_CSG + lane * 48);
            const char* dst = opaque(cell + 3 * HALF - near);
            bar_sync<2, 256>();
            const float S = sum8(lds128(SM_PG + lane * 16), lds128(SM_PG + 512 + lane * 16));
            const float sx = shi(S, 25), sq = shi(S, 24), Su = shi(S, lane + (lane < 16 ? 8 : 4));
            if (n < 0) {
                if (w == 0) stsf2(SM_CSG + lane * 48, S, Su);
            } else {
                float mean_b, rden;
                ln_fast(sx, sq, mean_b, rden);
                const float gv = bfr(fmaf(-mean_b, F(cs.x), S) * rden), uv = bfr(fmaf(-mean_b, F(cs.y), Su) * rden);
                const float sg = fast_rcp(1.f + fast_ex2(-LOG2E * gv));
                const uint32_t hb = pack2(bfr(gv * sg) * uv, 0.f);
                const uint32_t b0 = __byte_perm(shi(hb, 2 * t4), shi(hb, 2 * t4 + 1), 0x5410);
                const uint32_t b1 = __byte_perm(shi(hb, e1 ? 18 : 16), shi(hb, e1 ? 19 : 17), 0x5410);
                const bool up = g >= 4;
                const uint32_t l0 = up ? 0 : b0, h0 = up ? b0 : 0;
                const uint32_t m1 = up == e2 ? b1 : 0;
                float d[3][4] = {};
                mma16816(d[0], wd[0][0], wd[0][1], wd[0][2], wd[0][3], l0, h0);
                mma16816(d[1], wd[1][0], wd[1][1], wd[1][2], wd[1][3], l0, h0);
                mma16816(d[2], wd[2][0], wd[2][1], wd[2][2], wd[2][3], l0, up ? 0 : m1);
                mma1688(d[0], wd[3][0], wd[3][1], m1);
                mma1688(d[1], wd[3][2], wd[3][3], m1);
                red_cell(dst, e1 ? d[0][2] : d[0][0], e1 ? d[1][2] : d[1][0], e1 ? d[2][2] : d[2][0]);
                const uint32_t tsend = clk32();
                TRACES(tr + 3);
                if (last && w != cta >> 4) continue;
                const float sgr = shi(sg, 27);
                const uint32_t sg2 = pack2(sgr, sgr);
                const uint32_t n01 = opaque(pack2((bf_lo(x01) - mean_b) * rden, (bf_hi(x01) - mean_b) * rden));
                const uint32_t n2 = opaque(pack2((bf_lo(x2) - mean_b) * rden, 0.f));
                if (last) {
                    sts128_if(lane >> 1 == (cta & 15), SM_FIN + (lane & 1) * 16, x01, n01, __byte_perm(x2, n2, 0x5410), sg2);
                    mbar_arrive_if(lane >> 1 == (cta & 15), bar_at(B_FIN));
                    __syncwarp();
                    continue;
                }
                wait_clk(tsend + (n < QUIET ? CFG(DLY_BL) : CFG(DLY_B)));
                const uint32_t r01 = x01, r2 = x2;
                float cnt;
                SPIN_DECL;
                do {
                    const uint4 v = ld_pkt(cell + 2 * HALF), z = ld_pkt(cell + 3 * HALF);
                    SPIN_CHECK(n);
                    cnt = F(v.w) + F(z.w);
                    x01 = badd2(r01, badd2(n01, bmul2(pack2(F(v.x) + F(z.x), F(v.y) + F(z.y)), sg2)));
                    x2 = badd2(r2, badd2(n2, bmul2(pack2(F(v.z) + F(z.z), 0.f), sg2)));
                    put_x(x01, x2, xw, e2);
                } while (__any_sync(0xffffffffu, cnt != NCTA));
                TRACES(tr + 4);
            }
        }
        {
            uint32_t b[10];
            get_x(b, xr);
            float a[3][4] = {};
            const float f0 = bf_lo(x01), f1 = bf_hi(x01), f2 = e2 ? 0.f : bf_lo(x2);
            float st;
#pragma unroll
            for (int i = 0; i < 5; i++) {
#pragma unroll
                for (int mt = 0; mt < 3; mt++) {
                    mma16816(a[mt], wq[i][mt][0], wq[i][mt][1], wq[i][mt][2], wq[i][mt][3], b[2 * i], b[2 * i + 1]);
                    if (i == 0 && mt == 0) st = fold(fmaf(f0, f0, fmaf(f1, f1, f2 * f2)), (f0 + f1) + f2, g & 1, 4);
                }
                if (i < 4) st += shx(st, i < 2 ? 1 << i : 2 << i);
            }
            const uint32_t pa = SM_PQ + (w >> 2) * 1024 + (g & 1) * 512 + ((e2 ? 16 : 0) + (e1 ? 4 : 0) + (g >> 1)) * 16 + (w & 3) * 4;
            stsf(pa + 128, e2 ? st : e1 ? a[1][2] : a[1][0]);
            stsf(pa, e2 ? (e1 ? a[2][2] : a[2][0]) : (e1 ? a[0][2] : a[0][0]));
            bar_sync<3, 288>();
            if (n >= 0 && w == cta >> 4) {
                red_cell2_if(lane >> 1 == (cta & 15), cell + (acc_off(k, 1, 0) - acc_off(k, 0, 0)), f0, f1, f2);
                __syncwarp();
            }
        }
    }
}

__host__ __device__ constexpr int bar_count(int i) {
    return i < 16 ? 1 : i < B_RR ? 0 : i < B_RK ? 2 : i <= B_RV ? 4 : i == B_Z ? 1 : i == B_EP ? 9 : i < B_WC ? 0 : i < B_FIN ? 8 :
           i == B_FIN ? 2 : i == B_PS || i == B_RP ? 4 : i == B_QR ? 32 : 1;
}
template <int I, int END> __device__ __forceinline__ void init_bars() {
    if constexpr (I < END) {
        if (bar_count(I)) mbar_init(bar_at(I), bar_count(I));
        init_bars<I + 1, END>();
    }
}
template <int ID> __device__ __forceinline__ void role_exit() { asm volatile("exit; // %0" ::"n"(ID)); }
constexpr int NTHREADS = 512;
#define STR2(x) #x
#define STR(x) STR2(x)
__global__ void __launch_bounds__(NTHREADS, 1)
decode_kernel(const Params p, const __grid_constant__ Maps tm) {
    extern __shared__ __align__(1024) unsigned char smem[];
    if (threadIdx.x == 0) l2_prefetch(p.wq + (size_t)blockIdx.x * 12288, 12288);
    const uint32_t t0 = now_ns() - CFG(LEAD);
    const int lane = threadIdx.x & 31;
    const int warp = __reduce_max_sync(0xffffffffu, threadIdx.x >> 5);
    if (warp < 8) {
        asm volatile("setmaxnreg.inc.sync.aligned.u32 " STR(CFG_REG_CHAIN) ";");
        bar_arrive<5, 480>();
        const uint32_t vote = probe_near(p, warp, lane);
        bar_sync<2, 256 + 32>();
        sts32(SM_NEAR + warp * 4, vote);
        mbar_arrive_if(lane == 0, bar_at(B_EP));
        chain_role(p, warp, __shfl_sync(0xffffffffu, lane, lane));
        role_exit<3>();
    } else if (warp < 12) {
        asm volatile("setmaxnreg.dec.sync.aligned.u32 " STR(CFG_REG_ATT) ";");
        if (elect_one()) {
            if (warp == 8) init_bars<0, 12>();
            else if (warp == 9) init_bars<12, 30>();
            else if (warp == 10) init_bars<30, 42>();
            else init_bars<42, NBAR>();
            asm volatile("fence.mbarrier_init.release.cluster;" ::: "memory");
            fence_async();
        }
        if (warp == 8) TRACE(236);
        bar_sync<5, 480>();
        if (warp == 8) TRACE(237);
        attention_role(p, warp - 8, lane);
        role_exit<2>();
    } else {
        asm volatile("setmaxnreg.dec.sync.aligned.u32 " STR(CFG_REG_HELP) ";");
        if (warp == 12) {
            load_role(p, &tm.k, lane, t0);
            role_exit<0>();
        } else {
            if (warp == 14) {
                if (smem_u32(smem) != SB) __trap();
                if (elect_one()) {
                    asm volatile("prefetch.tensormap [%0];" ::"l"(&tm.q) : "memory");
                    mbar_init(bar_at(B_W), 1); mbar_init(bar_at(B_W + 1), 1); mbar_init(bar_at(B_W + 2), 1);
                    asm volatile("fence.mbarrier_init.release.cluster;" ::: "memory");
                    fence_async();
                    mbar_expect_tx(bar_at(B_W), 61440 + 15360 + 6400); mbar_expect_tx(bar_at(B_W + 1), 61440); mbar_expect_tx(bar_at(B_W + 2), 40960);
                    bulk_load(ST_X, p.x, 5120, bar_at(B_W));
                    bulk_load(ST_X + 5120, p.wr, 1280, bar_at(B_W));
                }
                TRACE(238);
                reload_role(p, &tm, t0);
            } else {
                if (warp == 13 && elect_one()) {
                    asm volatile("prefetch.tensormap [%0];" ::"l"(&tm.g) : "memory");
                    asm volatile("prefetch.tensormap [%0];" ::"l"(&tm.u) : "memory");
                    asm volatile("prefetch.tensormap [%0];" ::"l"(&tm.o) : "memory");
                    asm volatile("prefetch.tensormap [%0];" ::"l"(&tm.k) : "memory");
                    asm volatile("prefetch.tensormap [%0];" ::"l"(&tm.v) : "memory");
                }
                TRACE(233 + warp);
                bar_sync<5, 480>();
                if (warp == 13) { bar_arrive<6, 64>(); q_role(p, lane); }
                else { bar_arrive<2, 256 + 32>(); zero_role(p, lane, t0); }
            }
            role_exit<1>();
        }
    }
}

typedef CUresult (*EncodeFn)(CUtensorMap*, CUtensorMapDataType, cuuint32_t, void*, const cuuint64_t*, const cuuint64_t*,
                             const cuuint32_t*, const cuuint32_t*, CUtensorMapInterleave, CUtensorMapSwizzle,
                             CUtensorMapL2promotion, CUtensorMapFloatOOBfill);

bool make_map(EncodeFn fn, CUtensorMap* m, const void* ptr, uint64_t cols, uint64_t rows, uint32_t bc, uint32_t br) {
    cuuint64_t dims[2] = {cols, rows};
    cuuint64_t strides[1] = {cols * 2};
    cuuint32_t box[2] = {bc, br};
    cuuint32_t es[2] = {1, 1};
    return fn(m, CU_TENSOR_MAP_DATA_TYPE_BFLOAT16, 2, const_cast<void*>(ptr), dims, strides, box, es, CU_TENSOR_MAP_INTERLEAVE_NONE,
              CU_TENSOR_MAP_SWIZZLE_NONE, CU_TENSOR_MAP_L2_PROMOTION_L2_128B, CU_TENSOR_MAP_FLOAT_OOB_FILL_NONE) == CUDA_SUCCESS;
}

bool make_kv_map(EncodeFn fn, CUtensorMap* m, const void* ptr) {
    cuuint64_t dims[4] = {64, 8, 3, (cuuint64_t)NB * NHEAD * SK / 8};
    cuuint64_t strides[3] = {DH * 2, 128, 8 * DH * 2};
    cuuint32_t box[4] = {64, 8, 3, 4};
    cuuint32_t es[4] = {1, 1, 1, 1};
    return fn(m, CU_TENSOR_MAP_DATA_TYPE_BFLOAT16, 4, const_cast<void*>(ptr), dims, strides, box, es, CU_TENSOR_MAP_INTERLEAVE_NONE,
              CU_TENSOR_MAP_SWIZZLE_128B, CU_TENSOR_MAP_L2_PROMOTION_L2_128B, CU_TENSOR_MAP_FLOAT_OOB_FILL_NONE) == CUDA_SUCCESS;
}

}

extern "C" void kernel_launch(void* const* d_in, const int* in_sizes, int n_in, void* d_out, int out_size) {
    (void)in_sizes; (void)n_in; (void)out_size;
    static EncodeFn fn = nullptr;
    static const char* scr = nullptr;
    if (!fn) {
        void* f = nullptr;
        cudaDriverEntryPointQueryResult qr;
        if (cudaGetDriverEntryPoint("cuTensorMapEncodeTiled", &f, cudaEnableDefault, &qr) != cudaSuccess || !f) return;
        void* sp = nullptr;
        if (cudaGetSymbolAddress(&sp, g_scratch) != cudaSuccess) return;
        scr = (const char*)(((uintptr_t)sp + (2 << 20) - 1) & ~(uintptr_t)((2 << 20) - 1));
        fn = (EncodeFn)f;
        cudaFuncSetAttribute(decode_kernel, cudaFuncAttributeMaxDynamicSharedMemorySize, SMEM_BYTES);
    }
    Maps tm;
    if (!make_kv_map(fn, &tm.k, d_in[1]) || !make_kv_map(fn, &tm.v, d_in[2])) return;
    if (!make_map(fn, &tm.q, d_in[3], NHEAD * DH, DM, 48, 128) || !make_map(fn, &tm.o, d_in[4], DM, NHEAD * DH, 160, 32)) return;
    if (!make_map(fn, &tm.g, d_in[7], FF, DM, 16, 128) || !make_map(fn, &tm.u, d_in[8], FF, DM, 16, 128)) return;
    Params p;
    p.x = (const unsigned short*)d_in[0];
    p.wq = (const char*)d_in[3];
    p.wo = (const char*)d_in[4];
    p.wr = (const unsigned short*)d_in[6];
    p.wg = (const char*)d_in[7];
    p.wu = (const char*)d_in[8];
    p.wd = (const char*)d_in[9];
    p.out = (unsigned short*)d_out;
    p.scr = scr;
    decode_kernel<<<NCTA, NTHREADS, SMEM_BYTES>>>(p, tm);
}
```

```cpp
#include <cuda_runtime.h>
#include <cuda_bf16.h>
#include <cuda.h>
#include <stdint.h>

namespace {

constexpr int NB = 4, DM = 640, NHEAD = 32, DH = 192, SK = 4096, WIN = 1024, FF = 1536;
constexpr int NCTA = 128;
constexpr int TILE = 12288, PAIR = 2 * TILE;

#define CFG_LIST(X) \
    X(TICK0, 479)        \
    X(TICK, 495)        \
    X(LEAD, 600)        \
    X(STAG, 500)        \
    X(WLAG, 350)        \
    X(GSTEP, 750)        \
    X(WIN, 5)        \
    X(PMAX, 2)        \
    X(PGRACE, 50)        \
    X(LMAX0, 150)        \
    X(LMAX, 160) \
    X(GAIN, 5)        \
    X(VSTEP, 150)        \
    X(RSTEP, 670)        \
    X(RSTEP3, 450) \
    X(ZTILE, 11)        \
    X(DLY_A, 410)        \
    X(DLY_AL, 100) \
    X(DLY_B, 570) \
    X(DLY_BL, 950) \
    X(DLY_F, 290) \
    X(ROT, 0) \
    X(PERM, 13) \
    X(FLIP, 0) \

#define X(n, v) constexpr int CFG_##n = v;
CFG_LIST(X)
#undef X
#define CFG(n) CFG_##n
constexpr int QUIET = 8;
#define CFG_REG_CHAIN 216
#define CFG_REG_ATT 48
#define CFG_REG_HELP 32
constexpr int KB_KV0 = 165;
__device__ __forceinline__ int kb_ns(int kb) { return kb * CFG(TICK0) / 12; }
__device__ __forceinline__ int tick_ns(int j) { return j <= 16 ? CFG(TICK0) : CFG(TICK); }
__device__ __forceinline__ int batch_ns(int k) { return kb_ns(KB_KV0) + (k ? 16 * (CFG(TICK0) + (k - 1) * CFG(TICK)) : 0); }

__device__ __forceinline__ uint32_t slots(int k) { return k & 2 ? (k & 1 ? 0x21304768u : 0x76835214u) : (k & 1 ? 0x21480765u : 0x76543210u); }
__device__ __forceinline__ int pass_nibble(int k, int u) { return k > 0 ? 4 + (u & 1) : u; }
__device__ __forceinline__ uint32_t slot_at(uint32_t tab, int u) { return (tab >> (4 * u)) & 15; }

constexpr int NROUND = 11;
constexpr uint32_t ORD_BATCH = 0x3b9910, ORD_LAST = 0x6da, ORD_NO_HEAD = 0x248, ORD_NO_TAIL = 0x092;

constexpr uint32_t SB = 1024;
constexpr uint32_t SM_BAR = SB + 9 * PAIR;
constexpr int B_F1 = 0;
constexpr int B_RR = 24;
constexpr int B_RK = 32;
constexpr int B_RV = 36;
constexpr int B_Z = 37;
constexpr int B_EP = 38;
constexpr int B_W = 39;
constexpr int B_WC = 42;
constexpr int B_FIN = 45;
constexpr int B_F3 = 46;
constexpr int B_PS = 48;
constexpr int B_RP = 49;
constexpr int B_FL = 50;
constexpr int B_QR = 51;
constexpr int NBAR = 52;
__host__ __device__ constexpr uint32_t bar_at(int i) { return SM_BAR + 8 * i; }
constexpr uint32_t SM_EPOCH = SM_BAR + 416;
constexpr uint32_t SM_MAX = SM_EPOCH + 16;
constexpr uint32_t SM_SUM = SM_MAX + 16;
constexpr uint32_t SM_NEAR = SM_SUM + 32;
constexpr uint32_t SM_FIN = SM_NEAR + 32;
constexpr uint32_t SM_Q = SM_FIN + 32;
constexpr uint32_t PSTR = 144;
constexpr uint32_t SM_P = SM_Q + 5 * 384;
constexpr uint32_t SM_X = SM_P + 8 * PSTR;
constexpr uint32_t SM_CSG = SM_X + 40;
constexpr uint32_t SM_ONES = SM_X + 8 * 384;
constexpr uint32_t SM_PG = SM_ONES + 48;
constexpr uint32_t SM_PO = SM_PG + 1024;
constexpr uint32_t SM_PQ = SM_PO;
constexpr int SMEM_BYTES = SM_PO + 3072 - SB;
static_assert(SMEM_BYTES <= 232448 && SM_Q % 16 == 0 && SM_P % 16 == 0 && SM_X % 16 == 0 && SM_PO % 16 == 0, "smem");
constexpr uint32_t ST_WQ = SB, ST_WD = SB + 3 * PAIR, ST_WO = SB + 4 * PAIR, ST_WG = SB + 7 * PAIR, ST_X = ST_WG + 40960;

__device__ unsigned g_epoch;
__device__ unsigned char g_scratch[4 << 20];
constexpr uint32_t HALF = 4096, SCR_O = 1 << 16, SCR_Q = 1 << 17, SCR_COUNT = 3 << 16;
__device__ __forceinline__ uint32_t acc_off(int k, int layer, int w) {
    return (k & 1) << 6 | layer << 7 | (w & 1) << 11 | (w >> 1) << 14 | (k + layer == NB) << 18;
}
__device__ __forceinline__ uint32_t head_off(int h) { return (h & 3) << 14 | (h & 4) << 16 | (h & 8) << 17 | (h & 16) << 9; }
__device__ __forceinline__ uint32_t head_near(int h, uint32_t near) { return near ^ HALF ^ (h & 16) << 8; }
constexpr uint32_t FULL_A = 0x42040000u;

struct Params {
    const char* wq;
    const unsigned short* x;
    const char* wo;
    const unsigned short* wr;
    const char* wg;
    const char* wu;
    const char* wd;
    unsigned short* out;
    const char* scr;
};

__device__ __forceinline__ uint32_t smem_u32(const void* p) { return (uint32_t)__cvta_generic_to_shared(p); }
__device__ __forceinline__ void mbar_init(uint32_t a, uint32_t c) { asm volatile("mbarrier.init.shared::cta.b64 [%0], %1;" ::"r"(a), "r"(c) : "memory"); }
__device__ __forceinline__ void mbar_expect_tx(uint32_t a, uint32_t b) {
    asm volatile("mbarrier.arrive.expect_tx.shared::cta.b64 _, [%0], %1;" ::"r"(a), "r"(b) : "memory");
}
__device__ __forceinline__ void mbar_arrive(uint32_t a) { asm volatile("mbarrier.arrive.shared::cta.b64 _, [%0];" ::"r"(a) : "memory"); }
constexpr uint32_t SPIN_LIMIT = 1u << 22;
#define SPIN_DECL uint32_t spins = 0
#define SPIN_CHECK(info) { if (++spins > SPIN_LIMIT) __trap(); }
__device__ __forceinline__ void jitter() {}
__device__ __forceinline__ void mbar_wait(uint32_t a, uint32_t parity) {
    jitter();
    uint32_t ok;
    SPIN_DECL;
    while (true) {
        asm volatile("{\n.reg .pred p;\nmbarrier.try_wait.parity.shared::cta.b64 p, [%1], %2;\nselp.u32 %0, 1, 0, p;\n}"
                     : "=r"(ok) : "r"(a), "r"(parity) : "memory");
        if (ok) break;
        SPIN_CHECK((a - SM_BAR) / 8 * 10 + parity);
    }
    jitter();
}
__device__ __forceinline__ bool mbar_test2(uint32_t a, uint32_t pa, uint32_t b, uint32_t pb) {
    uint32_t ok;
    asm volatile("{\n.reg .pred p, q;\nmbarrier.test_wait.parity.shared::cta.b64 p, [%1], %2;\n"
                 "mbarrier.test_wait.parity.shared::cta.b64 q, [%3], %4;\nand.pred p, p, q;\nvote.sync.all.pred p, p, 0xffffffff;\nselp.u32 %0, 1, 0, p;\n}"
                 : "=r"(ok) : "r"(a), "r"(pa), "r"(b), "r"(pb) : "memory");
    return ok;
}
__device__ __forceinline__ uint32_t now_ns() { uint32_t t; asm volatile("mov.u32 %0, %%globaltimer_lo;" : "=r"(t) :: "memory"); return t; }
__device__ __forceinline__ uint32_t clk32() { uint32_t c; asm volatile("mov.u32 %0, %%clock;" : "=r"(c) :: "memory"); return c; }
__device__ __forceinline__ void wait_ns(uint32_t t) { jitter(); while ((int)(now_ns() - t) < 0) {} }
__device__ __forceinline__ void wait_clk(uint32_t t) { jitter(); while ((int)(clk32() - t) < 0) {} }
__device__ __forceinline__ bool elect_one() {
    uint32_t e;
    asm volatile("{\n.reg .pred p;\nelect.sync _|p, 0xffffffff;\nselp.u32 %0, 1, 0, p;\n}" : "=r"(e));
    return e;
}
constexpr uint64_t POL_FIRST = 0x12F0000000000000ull, POL_NORMAL = 0x1000000000000000ull;
__device__ __forceinline__ void tma_tile(uint32_t dst, const CUtensorMap* tm, int group, uint32_t bar, uint64_t pol) {
    asm volatile("cp.async.bulk.tensor.4d.shared::cluster.global.mbarrier::complete_tx::bytes.L2::cache_hint"
                 " [%0], [%1, {%3, %3, %3, %4}], [%2], %5;"
                 ::"r"(dst), "l"(tm), "r"(bar), "r"(0), "r"(group), "l"(pol) : "memory");
}
__device__ __forceinline__ void tma2d(uint32_t dst, const CUtensorMap* tm, int x, int y, uint32_t bar) {
    asm volatile("cp.async.bulk.tensor.2d.shared::cluster.global.mbarrier::complete_tx::bytes [%0], [%1, {%3, %4}], [%2];"
                 ::"r"(dst), "l"(tm), "r"(bar), "r"(x), "r"(y) : "memory");
}
__device__ __forceinline__ void bulk_load(uint32_t dst, const void* src, uint32_t bytes, uint32_t bar) {
    asm volatile("cp.async.bulk.shared::cluster.global.mbarrier::complete_tx::bytes [%0], [%1], %2, [%3];"
                 ::"r"(dst), "l"(src), "r"(bytes), "r"(bar) : "memory");
}
__device__ __forceinline__ void l2_prefetch(const void* p, uint32_t bytes) {
    asm volatile("cp.async.bulk.prefetch.L2.global [%0], %1;" ::"l"(p), "r"(bytes) : "memory");
}
__device__ __forceinline__ void mma16816(float (&c)[4], uint32_t a0, uint32_t a1, uint32_t a2, uint32_t a3, uint32_t b0, uint32_t b1) {
    asm volatile("mma.sync.aligned.m16n8k16.row.col.f32.bf16.bf16.f32 {%0,%1,%2,%3}, {%4,%5,%6,%7}, {%8,%9}, {%0,%1,%2,%3};"
                 : "+f"(c[0]), "+f"(c[1]), "+f"(c[2]), "+f"(c[3]) : "r"(a0), "r"(a1), "r"(a2), "r"(a3), "r"(b0), "r"(b1));
}
__device__ __forceinline__ void mma1688(float (&c)[4], uint32_t a0, uint32_t a1, uint32_t b0) {
    asm volatile("mma.sync.aligned.m16n8k8.row.col.f32.bf16.bf16.f32 {%0,%1,%2,%3}, {%4,%5}, {%6}, {%0,%1,%2,%3};"
                 : "+f"(c[0]), "+f"(c[1]), "+f"(c[2]), "+f"(c[3]) : "r"(a0), "r"(a1), "r"(b0));
}
__device__ __forceinline__ void ldsm4(uint32_t (&r)[4], uint32_t a) {
    asm volatile("ldmatrix.sync.aligned.m8n8.x4.shared.b16 {%0,%1,%2,%3}, [%4];"
                 : "=r"(r[0]), "=r"(r[1]), "=r"(r[2]), "=r"(r[3]) : "r"(a) : "memory");
}
__device__ __forceinline__ void ldsm4t(uint32_t (&r)[4], uint32_t a, uint32_t& zero) {
    asm volatile("ldmatrix.sync.aligned.m8n8.x4.trans.shared.b16 {%0,%1,%2,%3}, [%4];"
                 : "=r"(r[0]), "=r"(r[1]), "=r"(r[2]), "=r"(r[3]) : "r"(a + zero) : "memory");
    zero &= r[3];
}
__device__ __forceinline__ uint4 ld_pkt(const void* p) {
    uint4 v;
    asm volatile("{\n.reg .b128 t;\nld.relaxed.gpu.global.b128 t, [%4];\nmov.b128 {%0,%1,%2,%3}, t;\n}"
                 : "=r"(v.x), "=r"(v.y), "=r"(v.z), "=r"(v.w) : "l"(p) : "memory");
    return v;
}
__device__ __forceinline__ void st_pkt(const void* p, uint32_t a, uint32_t b, uint32_t c, uint32_t d) {
    asm volatile("{\n.reg .b128 t;\nmov.b128 t, {%1,%2,%3,%4};\nst.relaxed.gpu.global.b128 [%0], t;\n}"
                 ::"l"(p), "r"(a), "r"(b), "r"(c), "r"(d) : "memory");
}
__device__ __forceinline__ uint2 ld_pkt8(const void* p) {
    uint2 v;
    asm volatile("{\n.reg .b64 t;\nld.relaxed.gpu.global.b64 t, [%2];\nmov.b64 {%0,%1}, t;\n}" : "=r"(v.x), "=r"(v.y) : "l"(p) : "memory");
    return v;
}
__device__ __forceinline__ void red_cell(const char* p, float a, float b, float c) {
    jitter();
    asm volatile("red.relaxed.gpu.global.add.v4.f32 [%0], {%1,%2,%3,%4};" ::"l"(p), "f"(a), "f"(b), "f"(c), "f"(1.0f) : "memory");
}
#define PRED(n) "{\n.reg .pred p;\nsetp.ne.u32 p, %" #n ", 0;\n"
__device__ __forceinline__ void red_cell2_if(bool on, const char* p, float a, float b, float c) {
    jitter();
    asm volatile(PRED(5) "@p red.relaxed.gpu.global.add.v4.f32 [%0], {%1,%2,%3,%4};\n@p red.relaxed.gpu.global.add.v4.f32 [%0+4096], {%1,%2,%3,%4};\n}"
                 ::"l"(p), "f"(a), "f"(b), "f"(c), "f"(1.0f), "r"((uint32_t)on) : "memory");
}
__device__ __forceinline__ void st_pkt8_if(bool on, const void* p, uint32_t a, uint32_t b) {
    jitter();
    asm volatile(PRED(3) ".reg .b64 t;\nmov.b64 t, {%1,%2};\n@p st.relaxed.gpu.global.b64 [%0], t;\n}" ::"l"(p), "r"(a), "r"(b), "r"((uint32_t)on) : "memory");
}
__device__ __forceinline__ void st_pkt82_if(bool on, const void* p, uint32_t a, uint32_t b) {
    asm volatile(PRED(3) ".reg .b64 t;\nmov.b64 t, {%1,%2};\n@p st.relaxed.gpu.global.b64 [%0], t;\n@p st.relaxed.gpu.global.b64 [%0+4096], t;\n}"
                 ::"l"(p), "r"(a), "r"(b), "r"((uint32_t)on) : "memory");
}
__device__ __forceinline__ void st_pkt2_if(bool on, const void* p, uint32_t a, uint32_t b, uint32_t c, uint32_t d) {
    jitter();
    asm volatile(PRED(5) ".reg .b128 t;\nmov.b128 t, {%1,%2,%3,%4};\n@p st.relaxed.gpu.global.b128 [%0], t;\n@p st.relaxed.gpu.global.b128 [%0+4096], t;\n}"
                 ::"l"(p), "r"(a), "r"(b), "r"(c), "r"(d), "r"((uint32_t)on) : "memory");
}
__device__ __forceinline__ void mbar_arrive_if(bool on, uint32_t a) {
    jitter();
    asm volatile(PRED(1) "@p mbarrier.arrive.shared::cta.b64 _, [%0];\n}" ::"r"(a), "r"((uint32_t)on) : "memory");
}
__device__ __forceinline__ void sts16_if(bool on, uint32_t a, uint32_t v) {
    asm volatile(PRED(2) "@p st.shared.u16 [%0], %1;\n}" ::"r"(a), "h"((unsigned short)v), "r"((uint32_t)on) : "memory");
}
__device__ __forceinline__ void sts32_if(bool on, uint32_t a, uint32_t v) {
    asm volatile(PRED(2) "@p st.shared.u32 [%0], %1;\n}" ::"r"(a), "r"(v), "r"((uint32_t)on) : "memory");
}
__device__ __forceinline__ void sts128_if(bool on, uint32_t a, uint32_t x, uint32_t y, uint32_t z, uint32_t w) {
    jitter();
    asm volatile(PRED(5) "@p st.shared.v4.u32 [%0], {%1,%2,%3,%4};\n}" ::"r"(a), "r"(x), "r"(y), "r"(z), "r"(w), "r"((uint32_t)on) : "memory");
}
__device__ __forceinline__ float fast_rcp(float x) { float r; asm("rcp.approx.ftz.f32 %0, %1;" : "=f"(r) : "f"(x)); return r; }
__device__ __forceinline__ float fast_sqrt(float x) { float r; asm("sqrt.approx.ftz.f32 %0, %1;" : "=f"(r) : "f"(x)); return r; }
__device__ __forceinline__ float fast_ex2(float x) { float r; asm("ex2.approx.ftz.f32 %0, %1;" : "=f"(r) : "f"(x)); return r; }
__device__ __forceinline__ uint32_t pack2(float lo, float hi) {
    uint32_t r;
    asm("cvt.rn.bf16x2.f32 %0, %1, %2;" : "=r"(r) : "f"(hi), "f"(lo));
    return r;
}
__device__ __forceinline__ float bfr(float x) { return __uint_as_float(pack2(0.f, x)); }
__device__ __forceinline__ uint32_t badd2(uint32_t a, uint32_t b) { uint32_t r; asm("add.rn.bf16x2 %0, %1, %2;" : "=r"(r) : "r"(a), "r"(b)); return r; }
__device__ __forceinline__ uint32_t bsub2(uint32_t a, uint32_t b) { uint32_t r; asm("sub.rn.bf16x2 %0, %1, %2;" : "=r"(r) : "r"(a), "r"(b)); return r; }
__device__ __forceinline__ uint32_t bmul2(uint32_t a, uint32_t b) { uint32_t r; asm("mul.rn.bf16x2 %0, %1, %2;" : "=r"(r) : "r"(a), "r"(b)); return r; }
__device__ __forceinline__ float bf_lo(uint32_t w) { return __uint_as_float(w << 16); }
__device__ __forceinline__ float bf_hi(uint32_t w) { return __uint_as_float(w & 0xffff0000u); }
__device__ __forceinline__ float F(uint32_t t) { return __uint_as_float(t); }
__device__ __forceinline__ uint32_t lds16(uint32_t a) { unsigned short h; asm volatile("ld.shared.u16 %0, [%1];" : "=h"(h) : "r"(a) : "memory"); return h; }
__device__ __forceinline__ uint32_t lds32(uint32_t a) { uint32_t v; asm volatile("ld.shared.u32 %0, [%1];" : "=r"(v) : "r"(a) : "memory"); return v; }
__device__ __forceinline__ uint2 lds64(uint32_t a) {
    uint2 v; asm volatile("ld.shared.v2.u32 {%0,%1}, [%2];" : "=r"(v.x), "=r"(v.y) : "r"(a) : "memory"); return v;
}
__device__ __forceinline__ uint4 lds128(uint32_t a) {
    uint4 v; asm volatile("ld.shared.v4.u32 {%0,%1,%2,%3}, [%4];" : "=r"(v.x), "=r"(v.y), "=r"(v.z), "=r"(v.w) : "r"(a) : "memory"); return v;
}
__device__ __forceinline__ float sum8(const uint4& u, const uint4& v) {
    return ((F(u.x) + F(u.y)) + (F(u.z) + F(u.w))) + ((F(v.x) + F(v.y)) + (F(v.z) + F(v.w)));
}
__device__ __forceinline__ void sts16(uint32_t a, uint32_t v) { asm volatile("st.shared.u16 [%0], %1;" ::"r"(a), "h"((unsigned short)v) : "memory"); }
__device__ __forceinline__ void sts32(uint32_t a, uint32_t v) { asm volatile("st.shared.u32 [%0], %1;" ::"r"(a), "r"(v) : "memory"); }
__device__ __forceinline__ void stsf(uint32_t a, float v) { asm volatile("st.shared.f32 [%0], %1;" ::"r"(a), "f"(v) : "memory"); }
__device__ __forceinline__ void stsf2(uint32_t a, float x, float y) { asm volatile("st.shared.v2.f32 [%0], {%1,%2};" ::"r"(a), "f"(x), "f"(y) : "memory"); }
__device__ __forceinline__ void stsf4(uint32_t a, float x, float y, float z, float w) {
    asm volatile("st.shared.v4.f32 [%0], {%1,%2,%3,%4};" ::"r"(a), "f"(x), "f"(y), "f"(z), "f"(w) : "memory");
}
template <int ID, int N> __device__ __forceinline__ void bar_sync() { jitter(); asm volatile("bar.sync %0, %1;" ::"n"(ID), "n"(N) : "memory"); jitter(); }
template <int ID, int N> __device__ __forceinline__ void bar_arrive() { jitter(); asm volatile("bar.arrive %0, %1;" ::"n"(ID), "n"(N) : "memory"); jitter(); }
__device__ __forceinline__ void fence_async() { asm volatile("fence.proxy.async.shared::cta;" ::: "memory"); }
__device__ __forceinline__ float shx(float v, int m) { return __shfl_xor_sync(0xffffffffu, v, m); }
__device__ __forceinline__ float shi(float v, int l) { return __shfl_sync(0xffffffffu, v, l); }
__device__ __forceinline__ uint32_t shi(uint32_t v, int l) { return __shfl_sync(0xffffffffu, v, l); }
__device__ __forceinline__ uint32_t opaque(uint32_t x) { asm volatile("mov.u32 %0, %0;" : "+r"(x)); return x; }
__device__ __forceinline__ const char* opaque(const char* x) { asm volatile("mov.u64 %0, %0;" : "+l"(x)); return x; }
constexpr float LOG2E = 1.4426950408889634f, SCALE = 0.07216878364870322f;

#define TRACE(idx) do {} while (0)
#define TRACES(slot) do {} while (0)

__device__ __forceinline__ uint32_t probe_near(const Params& p, int w, int lane) {
    const int cta = blockIdx.x;
    const char* pr = p.scr + SCR_O + head_off(cta >> 2) + 2048 + w * 256 + (cta & 3) * 64;
    st_pkt2_if(lane < 4, pr + lane * 16, 0, 0, 0, 0);
    uint32_t best0 = ~0u, best1 = ~0u;
#pragma unroll 1
    for (int i = w & 1; i < 6 + (w & 1); i++) {
        uint32_t c = clk32(), v = 0;
        if (lane == 0) asm volatile("atom.relaxed.gpu.global.add.u32 %0, [%1], 1;" : "=r"(v) : "l"(pr + (i & 1) * HALF) : "memory");
        c += __shfl_sync(0xffffffffu, v, 0) >> 16;
        c = clk32() - c;
        if (i & 1) best1 = min(best1, c); else best0 = min(best0, c);
    }
    return min(best0, 0xffffu) | min(best1, 0xffffu) << 16;
}
__device__ __forceinline__ uint32_t near_half() {
    const uint4 a = lds128(SM_NEAR), b = lds128(SM_NEAR + 16);
    const uint32_t m = __vminu2(__vminu2(__vminu2(a.x, a.y), __vminu2(a.z, a.w)), __vminu2(__vminu2(b.x, b.y), __vminu2(b.z, b.w)));
    return head_near(blockIdx.x >> 2, ((m & 0xffffu) > m >> 16) != (CFG(FLIP) != 0) ? HALF : 0);
}

__device__ __forceinline__ int kv_group(int k, int t) {
    const int cta = blockIdx.x;
    return ((k * NHEAD + (cta >> 2)) * SK + (SK - WIN) + (cta & 3) * 32 + ((t + (cta >> 2) * CFG(ROT) / 4) & 7) * 128) / 8;
}
__device__ __forceinline__ uint32_t phase_ns() { return (((blockIdx.x >> 2) * CFG(PERM)) & 31) * CFG(STAG) / 32; }

__device__ __forceinline__ void ln_fast(float s, float q, float& mean, float& rstd) {
    mean = s * (1.f / DM);
    asm("rsqrt.approx.ftz.f32 %0, %1;" : "=f"(rstd) : "f"(fmaxf(fmaf(-mean, mean, fmaf(q, 1.f / DM, 1e-5f)), 1e-5f)));
}
__device__ __forceinline__ void q_role(const Params& p, int lane) {
    const int cta = blockIdx.x;
    mbar_wait(bar_at(B_EP), 0);
    const uint32_t epoch = lds32(SM_EPOCH), near = head_near(cta >> 2, near_half());
    auto sums = [&](float& S0, float& S1) {
        bar_sync<3, 288>();
        const uint32_t ra = SM_PQ + lane * 16;
        S0 = sum8(lds128(ra), lds128(ra + 1024)); S1 = sum8(lds128(ra + 512), lds128(ra + 1536));
    };
    float cs0, cs1;
    {
        uint32_t q0 = 0, q1 = 0, q2 = 0, q3 = 0;
#pragma unroll 1
        for (int r = 0; r < NB; r++) {
            sums(cs0, cs1);
            bar_arrive<7, 288>();
            q0 = q1; q1 = q2; q2 = q3; q3 = pack2(cs0, cs1);
        }
        const uint32_t t0 = shi(q3, 3 * lane - 72), t1 = shi(q3, 3 * lane - 71), t2 = shi(q3, 3 * lane - 70), tag = epoch << 8 | 0x40;
        const char* box = p.scr + SCR_O + head_off(cta >> 2) + 2048 + (lane >> 2) * 256 + (lane & 3) * 16;
        st_pkt2_if(true, box + (cta & 3) * 64, lane < 24 ? q0 : t0, lane < 24 ? q1 : t1, lane < 24 ? q2 : t2, tag);
        const uint32_t qd = SM_Q + (lane < 24 ? lane * 4 : 3 * 384 + (lane - 24) * 12), step = lane < 24 ? 384 : 4;
#pragma unroll 1
        for (int j = 0; j < 4; j++) {
            uint4 v;
            SPIN_DECL;
            do {
                __nanosleep(200);
                v = ld_pkt(box + near + j * 64);
                SPIN_CHECK(j);
            } while (__any_sync(0xffffffffu, v.w != tag));
            sts32(qd + j * 96, v.x); sts32(qd + j * 96 + step, v.y); sts32(qd + j * 96 + 2 * step, v.z);
        }
        mbar_arrive(bar_at(B_QR));
    }
    sums(cs0, cs1);
    bar_arrive<7, 288>();
    const char* const src = p.scr + SCR_Q + head_off(cta >> 2) + lane * 8 + near;
    const char* const dst = src + (cta & 3) * 192;
    const uint32_t qd = SM_Q + NB * 384 + lane * 4;
    st_pkt82_if(lane < 24, dst - near, 0, 0);
#pragma unroll 1
    for (int k = 0; k < NB; k++) {
        float S0, S1, mean, rstd;
        sums(S0, S1);
        ln_fast(shi(S1, 24), shi(S0, 24), mean, rstd);
        const uint32_t qq = pack2(fmaf(-mean, cs0, S0) * rstd, fmaf(-mean, cs1, S1) * rstd), tag = epoch * NB + k;
        st_pkt8_if(lane < 24, dst + ((int)HALF - 2 * (int)near), qq, tag);
        st_pkt8_if(lane < 24, dst, qq, tag);
        TRACES(k * 12 + 5);
        uint2 a, b, c;
        SPIN_DECL;
        do {
            a = ld_pkt8(src); b = ld_pkt8(src + 256); c = ld_pkt8(src + 512);
            SPIN_CHECK(k);
            sts32(qd, a.x); sts32(qd + 128, b.x); sts32(qd + 256, c.x);
        } while (__any_sync(0xffffffffu, a.y != tag || b.y != tag || c.y != tag));
        mbar_arrive(bar_at(B_QR));
    }
}

struct Maps { CUtensorMap k, v, q, o, g, u; };
__device__ __forceinline__ void load_role(const Params& p, const CUtensorMap* tmKV, int lane, uint32_t t0) {
    const int cta = blockIdx.x;
    t0 += phase_ns();
#pragma unroll 1
    for (int i = 1; i < 5; i++) {
        wait_ns(t0 + i * CFG(TICK0));
        if (elect_one()) l2_prefetch(p.wq + (size_t)(128 * i + cta) * 12288, 12288);
        TRACE(230 + i);
    }
    uint32_t plan[2];
#pragma unroll
    for (int i = 0; i < 2; i++) {
        const int j = lane + 32 * i, k = j >> 4, t = j & 15, u = t >> 1, jw = j - CFG(WIN);
        const int sb = k == 0 ? B_WC + (t >= 8) + (t >= 14) : t >= 12 ? B_RK + u - 5 : t >= 4 ? B_RR + t - 4 : t >= 2 ? B_RP : k > 1 ? B_RK + 3 : B_RR + t;
        const uint32_t sw = sb * 8 | (j < 18 ? 0 : (t >= 12 || u == 1 ? k - 1 : k) & 1) << 9;
        plan[i] = sw | (jw < 0 ? sw : (B_F1 + (jw & 15)) * 8 | ((jw >> 4) & 1) << 9) << 10 |
                  (slot_at(slots(k), t < 8 ? pass_nibble(k, u) : u) * 2 + (t & 1)) << 20 | (t < 10 && j >= 8 && j < 56) << 25;
    }
    bar_sync<6, 64>();
    wait_ns(t0 + kb_ns(60));
    if (elect_one()) bulk_load(ST_WD, p.wd + cta * 15360, 15360, bar_at(B_W));
    TRACE(235);
#pragma unroll 1
    for (int i = 0; i < 5; i++) {
        wait_ns(t0 + kb_ns(75) + i * kb_ns(6));
        if (elect_one()) { l2_prefetch(p.wg + (128 * i + cta) * 3072, 3072); l2_prefetch(p.wu + (128 * i + cta) * 3072, 3072); }
    }
#pragma unroll 1
    for (int i = 0; i < 6; i++) {
        wait_ns(t0 + kb_ns(105) + min(i, 4) * kb_ns(10));
        if (elect_one()) l2_prefetch(p.wo + (size_t)((cta >> 2) * DH + 32 * i + 8 * (cta & 3)) * 1280, 10240);
    }
    t0 += batch_ns(0);
    int jp = 0, shift = 0;
    uint32_t earliest = t0;
    auto requested = [&](uint32_t now) {
        shift = max(max(shift - CFG(GAIN), 0), (int)(now - t0) - (jp < 12 ? CFG(LMAX0) : CFG(LMAX)));
        TRACE(128 + jp);
        t0 += tick_ns(++jp);
    };
    const int rot = (cta >> 2) * CFG(ROT) / 4, grp0 = kv_group(0, -rot);
    auto group = [&](int j) { return grp0 + (j >> 4) * (NHEAD * SK / 8) + ((j + rot) & 7) * 16; };
#pragma unroll 1
    for (int j = 0; j < 16 * NB; j++) {
        const uint32_t pl = __shfl_sync(0xffffffffu, j & 32 ? plan[1] : plan[0], j);
        const int jmax = min(j + CFG(PMAX), 16 * NB);
        jitter();
        uint32_t now;
        SPIN_DECL;
        while (true) {
            const bool ok = mbar_test2(SM_BAR + (pl & 511), (pl >> 9) & 1, SM_BAR + ((pl >> 10) & 511), (pl >> 19) & 1);
            now = now_ns();
            const int late = now - t0 - shift;
            if (ok && (jp > j ? (int)(now - earliest) : late) >= 0) break;
            if (late >= (jp > j ? 0 : CFG(PGRACE)) && jp < jmax) {
                if (elect_one())
                    asm volatile("cp.async.bulk.prefetch.tensor.4d.L2.global [%0, {%1, %1, %1, %2}];" ::"l"(tmKV + ((jp >> 3) & 1)), "r"(0), "r"(group(jp)) : "memory");
                requested(now);
            }
            SPIN_CHECK(j);
        }
        if (elect_one()) {
            mbar_expect_tx(bar_at(B_F1 + (j & 15)), TILE);
            tma_tile(SB + ((pl >> 20) & 31) * TILE, tmKV + ((j >> 3) & 1), group(j), bar_at(B_F1 + (j & 15)), pl >> 25 ? POL_NORMAL : POL_FIRST);
        }
        TRACE(256 + j);
        if ((j & 15) == 15) TRACES(88 + (j >> 4));
        earliest = now + CFG(VSTEP);
        if (jp == j) requested(now);
    }
}

__device__ __forceinline__ void reload_role(const Params& p, const Maps* tm, uint32_t t0) {
    const CUtensorMap* const tmK = &tm->k;
    const CUtensorMap* const tmV = &tm->v;
    const int cta = blockIdx.x;
    t0 += CFG(TICK0) + CFG(WLAG) + phase_ns();
#pragma unroll 1
    for (int i = 0; i < 5; i++) {
        wait_ns(t0 + i * CFG(TICK0));
        if (elect_one()) tma2d(ST_WQ + i * 12288, &tm->q, 48 * cta, 128 * i, bar_at(B_W));
        TRACE(240 + i);
        if (i == 1) bar_sync<5, 480>();
    }
#pragma unroll 1
    for (int i = 0, o = 0; i < 10;) {
        const uint32_t now = now_ns() - t0;
        if (o < 6 && (int)now >= kb_ns(105) + o * kb_ns(10)) {
            if (elect_one()) tma2d(ST_WO + o * 10240, &tm->o, 160 * (cta & 3), (cta >> 2) * DH + 32 * o, bar_at(B_W + 1));
            o++;
        } else if ((int)now >= kb_ns(77) + i * CFG(GSTEP) && (i < 9 || o == 6)) {
            if (elect_one()) tma2d(ST_WG + (i & 1) * 20480 + (i >> 1) * 4096, i & 1 ? &tm->u : &tm->g, (12 * cta) & ~7, 128 * (i >> 1), bar_at(B_W + 2));
            i++;
        }
    }
#pragma unroll 1
    for (int k = 0; k < NB - 1; k++) {
        mbar_wait(bar_at(B_RK), k & 1);
        if (elect_one()) {
            const uint32_t dst = SB + slot_at(slots(k), 0) * PAIR;
            mbar_expect_tx(bar_at(B_FL), PAIR);
            tma_tile(dst, tmV, kv_group(k, 0), bar_at(B_FL), POL_FIRST);
            tma_tile(dst + TILE, tmV, kv_group(k, 1), bar_at(B_FL), POL_FIRST);
        }
        mbar_wait(bar_at(B_RV), k & 1);
        uint32_t due = now_ns();
        if (elect_one()) mbar_expect_tx(bar_at(B_F3), 4 * PAIR);
#pragma unroll 1
        for (int t = 0; t < 8; t++) {
            wait_ns(due);
            due += k == NB - 2 ? CFG(RSTEP3) : CFG(RSTEP);
            if (elect_one())
                tma_tile(SB + slot_at(slots(k + 1), t >> 1) * PAIR + (t & 1) * TILE, tmK, kv_group(k + 1, t), bar_at(B_F3), POL_FIRST);
        }
        TRACE(121 + k);
    }
}

__device__ __forceinline__ void zero_role(const Params& p, int lane, uint32_t t0) {
    const int cta = blockIdx.x;
    unsigned ticket = 0;
    if (lane == 0) ticket = atomicAdd(&g_epoch, 1u);
    const uint32_t epoch = __shfl_sync(0xffffffffu, ticket, 0) / NCTA + 1;
    if (lane == 0) { sts32(SM_EPOCH, epoch); mbar_arrive(bar_at(B_EP)); }
    mbar_wait(bar_at(B_EP), 0);
#pragma unroll 1
    for (int k = 0; k < NB + 2; k++) {
        lane = opaque(lane);
        const int cl = 2 * (cta & 15) + (lane & 1);
        const int col = 80 * (cta >> 4) + (cl & 2 ? 48 : 0) + (cl >> 2) + (cl & 1 ? 8 : 0);
        const char* own = p.scr + (cl >> 2) * 256 + (cl & 3) * 16;
        uint32_t v0 = 0, v1 = 0, v2 = 0;
        if (lane < 4 && k < NB) {
            const unsigned short* xp = p.x + k * DM + col;
            v0 = __ldg(xp) << 16; v1 = __ldg(xp + 16) << 16; v2 = cl & 2 ? 0 : __ldg(xp + 32) << 16;
        }
        uint4 r;
        if (k == 1) mbar_wait(bar_at(B_RK), 0);
        if (k > 1) {
            mbar_wait(bar_at(B_FIN), k & 1);
            r = lds128(SM_FIN + (lane & 1) * 16);
        }
        if (k < NB) {
            const int lg = lane >> 3, ty = (lane & 7) >> 1;
            const char* dst = own + acc_off((k - (lg >> 1)) & 3, lg != 0, cta >> 4) + ty * HALF;
            wait_ns(t0 + batch_ns(k) + CFG(ZTILE) * CFG(TICK0));
            if (lg == 0 || (lg == 1 && (ty < 2 || k == NB - 1)) || (lg == 2 && k > 0 && ty > 1)) {
                st_pkt(dst, v0, v1, v2, ~0u);
                asm volatile("atom.relaxed.gpu.global.exch.b32 %0, [%1+12], %2;" : "=r"(v0) : "l"(dst), "r"(lane < 4 ? 0x3f800000u : 0u) : "memory");
                v0 = ~v0;
            }
            if (__any_sync(0xffffffffu, v0 != 0)) __trap();
            const char* cnt = p.scr + SCR_COUNT;
            if (lane < 2) asm volatile("red.relaxed.gpu.global.add.u32 [%0], 1;" ::"l"(cnt + lane * HALF) : "memory");
            const uint32_t target = ((epoch - 1) * NB + k + 1) * NCTA;
            cnt += near_half();
            SPIN_DECL;
            uint32_t v;
            do {
                __nanosleep(100);
                asm volatile("ld.relaxed.gpu.global.u32 %0, [%1];" : "=r"(v) : "l"(cnt) : "memory");
                SPIN_CHECK(v);
            } while (__any_sync(0xffffffffu, (int)(v - target) < 0));
        }
        __syncwarp();
        if (lane == 0) mbar_arrive(bar_at(B_Z));
        if (k > 1) {
            const int b = k - 2;
            const char* src = own + acc_off(b, 1, cta >> 4) + (2 + ((lane >> 1) & 1)) * HALF;
            unsigned short* o = p.out + b * DM + col + (lane >> 2) * 16;
            const bool on = !(lane & 2) && lane < (cl & 2 ? 8 : 12);
            wait_clk(clk32() + CFG(DLY_F));
            float cnt;
            SPIN_DECL;
            do {
                const uint4 v = ld_pkt(src);
                SPIN_CHECK(k);
                cnt = F(v.w) + shx(F(v.w), 2);
                const float y0 = F(v.x) + shx(F(v.x), 2), y1 = F(v.y) + shx(F(v.y), 2), y2 = F(v.z) + shx(F(v.z), 2);
                const uint32_t x01 = badd2(r.x, badd2(r.y, bmul2(pack2(y0, y1), r.w)));
                const uint32_t x2 = badd2(r.z, badd2(r.z >> 16, bmul2(pack2(y2, 0.f), r.w)));
                if (cnt == NCTA && on) *o = lane < 4 ? x01 : lane < 8 ? x01 >> 16 : x2;
            } while (__any_sync(0xffffffffu, cnt != NCTA));
            TRACES((2 * b + 1) * 6 + 4);
        }
    }
}

__host__ __device__ constexpr uint32_t desc_lo(uint32_t addr) { return ((addr & 0x3FFFFu) >> 4) | (1u << 16); }
constexpr uint32_t DESC_HI_TILE = (3072u >> 4) | (1u << 30);
constexpr uint32_t DESC_HI_VEC = 1u;
template <int TA, int AOFF, int BOFF>
__device__ __forceinline__ void wgmma_n8(float (&d)[4], uint32_t alo, uint32_t blo, int accumulate) {
    asm volatile("{\n.reg .pred p;\n.reg .b32 a, b;\n.reg .b64 da, db;\nsetp.ne.b32 p, %6, 0;\n"
                 "add.u32 a, %4, %8;\nadd.u32 b, %5, %9;\nmov.b64 da, {a, %10};\nmov.b64 db, {b, %11};\n"
                 "wgmma.mma_async.sync.aligned.m64n8k16.f32.bf16.bf16 {%0,%1,%2,%3}, da, db, p, 1, 1, %7, 0;\n}"
                 : "+f"(d[0]), "+f"(d[1]), "+f"(d[2]), "+f"(d[3])
                 : "r"(alo), "r"(blo), "r"(accumulate), "n"(TA), "n"(AOFF >> 4), "n"(BOFF >> 4), "n"(DESC_HI_TILE), "n"(DESC_HI_VEC));
}
template <int KS, int END>
__device__ __forceinline__ void qk_steps(float (&d)[4], uint32_t alo, uint32_t blo) {
    if constexpr (KS < END) {
        wgmma_n8<0, (KS >> 2) * 1024 + (KS & 3) * 32, KS * 32>(d, alo, blo, KS > 0);
        qk_steps<KS + 1, END>(d, alo, blo);
    }
}
__device__ __forceinline__ void pv_steps(float (&e)[3][4], uint32_t alo, uint32_t blo, int acc) {
    wgmma_n8<1, 0, 0>(e[0], alo, blo, acc); wgmma_n8<1, 1024, 0>(e[1], alo, blo, acc); wgmma_n8<1, 2048, 0>(e[2], alo, blo, acc);
    wgmma_n8<1, 6144, 32>(e[0], alo, blo, 1); wgmma_n8<1, 7168, 32>(e[1], alo, blo, 1); wgmma_n8<1, 8192, 32>(e[2], alo, blo, 1);
}
__device__ __forceinline__ void wg_fence() { asm volatile("wgmma.fence.sync.aligned;" ::: "memory"); }
__device__ __forceinline__ void wg_commit() { asm volatile("wgmma.commit_group.sync.aligned;" ::: "memory"); }
template <int N> __device__ __forceinline__ void wg_wait() { asm volatile("wgmma.wait_group.sync.aligned %0;" ::"n"(N) : "memory"); }
__device__ __forceinline__ void acc_ready(float (&d)[4]) { asm volatile("" : "+f"(d[0]), "+f"(d[1]), "+f"(d[2]), "+f"(d[3]) :: "memory"); }
__device__ __forceinline__ uint32_t score_pair(float (&d)[4]) {
    acc_ready(d);
    const uint32_t r = pack2(d[0], d[2]);
    return pack2(bf_lo(r) * SCALE, bf_hi(r) * SCALE);
}

__device__ __forceinline__ void attention_role(const Params& p, int w, int lane) {
    const int cta = blockIdx.x, t4 = lane & 3, g = lane >> 2;
    mbar_wait(bar_at(B_EP), 0);
    const uint32_t tag0 = lds32(SM_EPOCH) * NB;
    const char* const odst = p.scr + SCR_O + head_off(cta >> 2) + (2 * w + (g >> 2)) * 256 + (cta & 3) * 64 + (g & 3) * 16;
    const uint32_t pdst = SM_P + ((t4 + 3) & 3) * PSTR + (16 * w + g) * 2;
    auto softmax = [&](uint32_t& sc, int ps) -> uint32_t {
        const float s0 = bf_lo(sc), s1 = bf_hi(sc);
        int key = __float_as_int(fmaxf(s0, s1));
        key ^= (key >> 31) & 0x7fffffff;
        key = __reduce_max_sync(0xffffffffu, key);
        sts32(SM_MAX + w * 4, key);
        bar_sync<4, 128>();
        const uint4 mx = lds128(SM_MAX);
        key = max(max((int)mx.x, (int)mx.y), max((int)mx.z, (int)mx.w));
        key ^= (key >> 31) & 0x7fffffff;
        const float mb = __int_as_float(key) * LOG2E;
        const uint32_t pp = pack2(fast_ex2(fmaf(s0, LOG2E, -mb)), fast_ex2(fmaf(s1, LOG2E, -mb)));
        sts16(pdst + ps * 4 * PSTR, pp); sts16(pdst + ps * 4 * PSTR + 16, pp >> 16);
        fence_async();
        bar_sync<4, 128>();
        sc = pp;
        return key;
    };
    auto put_sum = [&](uint32_t pp, int ps) {
        uint32_t fs;
        asm volatile("redux.sync.add.u32 %0, %1, 0xffffffff;" : "=r"(fs) : "r"(__float2uint_rn((bf_lo(pp) + bf_hi(pp)) * 8388608.f)) : "memory");
        sts32(SM_SUM + ps * 16 + w * 4, fs);
    };
    auto aux_word = [&](uint32_t mx, const uint4& u, int k) {
        const float l = __uint2float_rn((u.x + u.y) + (u.z + u.w)) * (1.f / 8388608.f);
        return (g < 4 ? mx : (__float_as_uint(l) + 0x80u) & 0xffffff00u) | ((tag0 + k) & 0x7fu) | 0x80u;
    };
    auto send = [&](float (&e)[3][4], uint32_t aux, int ps) {
        acc_ready(e[0]); acc_ready(e[1]); acc_ready(e[2]);
        const uint32_t o0 = pack2(e[0][0], e[0][2]), o1 = pack2(e[1][0], e[1][2]), o2 = pack2(e[2][0], e[2][2]);
        st_pkt2_if(t4 == 0, odst + ps * 2048, o0, o1, o2, aux);
        mbar_arrive_if(lane == 0, bar_at(ps ? B_RV : B_PS));
    };
    mbar_wait(bar_at(B_QR), 0);
    TRACES(73);
#pragma unroll 1
    for (int it = 0; it <= NB; it++) {
        uint32_t m1 = 0;
        if (it < NB) {
            const uint32_t tab = slots(it);
            const uint32_t ka = SB + (2 * w + ((lane >> 3) & 1)) * 3072 + (lane & 7) * 128 + (((lane >> 4) ^ (lane & 7)) << 4);
            const uint32_t qa = SM_Q + it * 384 + (lane >> 3) * 16;
            uint32_t sc = 0;
#pragma unroll 1
            for (int u = 0; u < 4; u++) {
                const uint32_t base = ka + slot_at(tab, pass_nibble(it, u)) * PAIR;
                mbar_wait(bar_at(B_F1 + 2 * u + (w >> 1)), it & 1);
                float d0[4] = {}, d1[4] = {};
#pragma unroll
                for (int c = 0; c < 6; c++) {
                    uint32_t a0[4], a1[4], b[4];
                    ldsm4(b, qa + c * 64);
                    ldsm4(a0, (base ^ ((c & 1) * 64)) + (c >> 1) * 1024);
                    ldsm4(a1, (base ^ ((c & 1) * 64 + 32)) + (c >> 1) * 1024);
                    mma16816(d0, a0[0], a0[1], a0[2], a0[3], b[0], b[1]);
                    mma16816(d1, a1[0], a1[1], a1[2], a1[3], b[2], b[3]);
                }
                const uint32_t r = pack2(d0[0] + d1[0], d0[2] + d1[2]);
                mbar_arrive_if(lane == 0, bar_at(B_RR + 2 * u + (w >> 1)));
                if (t4 == ((u + 1) & 3)) sc = pack2(bf_lo(r) * SCALE, bf_hi(r) * SCALE);
            }
            m1 = softmax(sc, 0);
            put_sum(sc, 0);
        }
        if (it > 0) {
            const int k = it - 1;
            const uint32_t tab = slots(k);
            const uint32_t v0 = slot_at(tab, k < NB - 1 ? 0 : 4);
            TRACES(48 + k * 6);
            if (k > 0) mbar_wait(bar_at(B_F3), it & 1);
            mbar_wait(bar_at(B_QR), it & 1);
            fence_async();
            TRACES(49 + k * 6);
            float d[4][4] = {};
            const bool busy = k < NB - 1;
#pragma unroll
            for (int u = 0; u < 4; u++) {
                const uint32_t alo = desc_lo(SB) + slot_at(tab, u) * (PAIR >> 4), blo = desc_lo(SM_Q + 4 * 384);
                wg_fence();
                qk_steps<0, 6>(d[u], alo, blo);
                wg_commit();
                if (busy) {
                    wg_wait<1>();
                    if (u > 0) mbar_arrive_if(lane == 0, bar_at(B_RK + u - 1));
                }
                wg_fence();
                qk_steps<6, 12>(d[u], alo, blo);
                wg_commit();
                if (u < 3 && busy) wg_wait<1>();
            }
            wg_wait<2>();
            uint32_t sc = shi(score_pair(d[0]), lane & 28), s = shi(score_pair(d[1]), lane & 28);
            if (t4 == 2) sc = s;
            s = shi(score_pair(d[2]), lane & 28);
            if (t4 == 3) sc = s;
            wg_wait<0>();
            s = score_pair(d[3]);
            if (t4 == 0) sc = s;
            mbar_arrive_if(lane == 0, bar_at(B_RK + 3));
            TRACES(50 + k * 6);
            const uint32_t m2 = softmax(sc, 1);
            TRACES(51 + k * 6);
            float e[3][4] = {};
#pragma unroll
            for (int t = 0; t < 8; t++) {
                const int pr = ((t >> 1) + 1) & 3;
                if (t == 6 && k < NB - 1) mbar_wait(bar_at(B_FL), k & 1);
                wg_fence();
                pv_steps(e, desc_lo(SB + (t & 1) * TILE) + (pr ? slot_at(tab, 4 + pr) : v0) * (PAIR >> 4), desc_lo(SM_P + (4 + pr) * PSTR + (t & 1) * 64), t > 0);
                wg_commit();
                if (t < 7 && busy) wg_wait<1>();
                if (t == 1) put_sum(sc, 1);
            }
            bar_sync<4, 128>();
            const uint32_t aux = opaque(aux_word(m2, lds128(SM_SUM + 16), k));
            wg_wait<0>();
            send(e, aux, 1);
            TRACES(52 + k * 6);
        }
        if (it < NB) {
            const uint32_t tab = slots(it);
            if (it == 0) st_pkt2_if(t4 == 0, odst, 0, 0, 0, 0);
            bar_sync<4, 128>();
            const uint32_t aux = opaque(aux_word(m1, lds128(SM_SUM), it));
            float e[3][4] = {};
#pragma unroll 1
            for (int u = 0; u < 4; u++) {
                const uint32_t alo = desc_lo(SB) + slot_at(tab, 4 + u) * (PAIR >> 4), blo = desc_lo(SM_P) + u * (PSTR >> 4);
                mbar_wait(bar_at(B_F1 + 8 + 2 * u), it & 1);
                wg_fence();
                pv_steps(e, alo, blo, u > 0);
                wg_commit();
                wg_wait<1>();
                if (u == 1) mbar_arrive_if(lane == 0, bar_at(B_RP));
                mbar_wait(bar_at(B_F1 + 9 + 2 * u), it & 1);
                wg_fence();
                pv_steps(e, alo + (TILE >> 4), blo + 4, 1);
                wg_commit();
                wg_wait<1>();
            }
            wg_wait<0>();
            send(e, aux, 0);
            TRACES(53 + it * 6);
        }
    }
}

__device__ __forceinline__ void ln_finish(float s, float q, float& mean_b, float& rden) {
    const float mean = s * (1.f / DM);
    const float var = fmaxf(fmaf(q, 1.f / DM, -mean * mean), 0.f);
    mean_b = bfr(mean);
    rden = fast_rcp(bfr(fast_sqrt(bfr(bfr(var) + 1e-5f))));
}
__device__ __forceinline__ uint32_t ln_apply(uint32_t w, float mean_b, float rden) {
    const uint32_t d = bsub2(w, __byte_perm(__float_as_uint(mean_b), 0, 0x3232));
    return pack2(bf_lo(d) * rden, bf_hi(d) * rden);
}
__device__ __forceinline__ void put_x(uint32_t x01, uint32_t x2, uint32_t wa, bool e2) {
    jitter();
    sts16(wa, x01); sts16(wa + 8, x01 >> 16);
    sts16_if(!e2, wa + 16, x2);
}
__device__ __forceinline__ void get_x(uint32_t (&b)[10], uint32_t ra) {
    __syncwarp();
    const uint4 u = lds128(ra), v = lds128(ra + 16);
    const uint2 z = lds64(ra + 32);
    b[0] = u.x; b[1] = u.y; b[2] = u.z; b[3] = u.w; b[4] = v.x; b[5] = v.y; b[6] = v.z; b[7] = v.w; b[8] = z.x; b[9] = z.y;
}
__device__ __forceinline__ float fold(float a, float b, bool sel, int m) { return (sel ? b : a) + shx(sel ? a : b, m); }

__device__ __forceinline__ void chain_role(const Params& p, int w, int lane) {
    const int cta = blockIdx.x, h = cta >> 2, s = cta & 3;
    const int g = lane >> 2, t4 = lane & 3;
    const bool e1 = t4 & 1, e2 = t4 & 2;
    uint32_t wq[5][3][4], wo[3][5][4], wg[5][4], wh[5][2], wd[4][4];
    const int col0 = 80 * w + (e2 ? 48 : 0) + g + (e1 ? 8 : 0);
    const uint32_t xw = opaque(SM_X + w * 384 + 48 * (g >> 1) + (e2 ? 24 : 0) + (e1 ? 4 : 0) + 2 * (g & 1));
    const uint32_t xr = opaque(g == 1 ? SM_ONES : SM_X + w * 384 + (g == 3 ? 192 : 0) + 48 * t4);
    TRACES(75);
    sts32_if(lane < 12, SM_ONES + lane * 4, 0x3f803f80u);
    uint32_t zero = lane >> 5;
    const int mi = lane >> 3, mr = lane & 7;
    mbar_wait(bar_at(B_W), 0);
    TRACES(74);
    sts16(xw + 192, lds16(ST_X + 5120 + col0 * 2)); sts16(xw + 200, lds16(ST_X + 5120 + col0 * 2 + 32));
    sts16_if(!e2, xw + 208, lds16(ST_X + 5120 + col0 * 2 + 64));
#pragma unroll
    for (int i = 0; i < 5; i++)
#pragma unroll
        for (int mt = 0; mt < 3; mt++) ldsm4t(wq[i][mt], ST_WQ + (80 * w + 16 * i + mr + 8 * (mi >> 1)) * 96 + 32 * mt + 16 * (mi & 1), zero);
    const bool odd = cta & 1;
    const uint32_t lo = ST_WD + (mr + (odd ? 4 : 0)) * 1280 + 160 * w + 16 * (mi & 1);
    const uint32_t hi = ST_WD + ((mr & 3) + (odd ? 0 : 8)) * 1280 + 160 * w + 16 * (mi & 1);
    ldsm4t(wd[0], lo + 96 * (mi >> 1), zero);
    ldsm4t(wd[1], lo + 96 * (mi >> 1) + 32, zero);
    ldsm4t(wd[2], (mi < 2 ? lo : hi) + 64, zero);
    ldsm4t(wd[3], hi + 32 * (mi >> 1) + 96 * (mr >> 2), zero);
    fence_async();
    __syncwarp();
    mbar_arrive_if(lane == 0, bar_at(B_WC));
    mbar_wait(bar_at(B_EP), 0);
    const uint32_t near = __shfl_sync(0xffffffffu, near_half(), 0);
    uint32_t x01 = 0, x2 = 0, nx01 = 0, nx2 = 0;
#pragma unroll 1
    for (int n = -5; n < NROUND; n++) {
        const bool last = (ORD_LAST >> (n & 15)) & 1, head = !((ORD_NO_HEAD >> (n & 15)) & 1);
        const int k = (ORD_BATCH >> (2 * (n & 15))) & 3;
        if (n > -5 && n <= 0) bar_sync<7, 288>();
        else if (!last) bar_sync<2, 256>();
        TRACES(n <= 0 ? 83 + n : 95);
        const char* const slice = p.scr + acc_off(k, last, w);
        const char* const cell = opaque(slice + g * 256 + t4 * 16);
        if (n < -1) {
            const uint32_t xa = ST_X + (n + 5) * 1280, ln = opaque(lane);
            const int col0 = 80 * w + (ln & 2 ? 48 : 0) + (ln >> 2) + (ln & 1 ? 8 : 0);
            float sm = 0.f, sq = 0.f;
#pragma unroll
            for (int i = 0; i < 5; i++) {
                const uint2 c = lds64(xa + i * 256 + ln * 8);
                sm += (bf_lo(c.x) + bf_hi(c.x)) + (bf_lo(c.y) + bf_hi(c.y));
                sq = fmaf(bf_lo(c.x), bf_lo(c.x), fmaf(bf_hi(c.x), bf_hi(c.x), fmaf(bf_lo(c.y), bf_lo(c.y), fmaf(bf_hi(c.y), bf_hi(c.y), sq))));
            }
            x01 = lds16(xa + col0 * 2) | lds16(xa + col0 * 2 + 32) << 16;
            x2 = lds16(xa + col0 * 2 + 64);
#pragma unroll
            for (int o = 16; o; o >>= 1) { sm += shx(sm, o); sq += shx(sq, o); }
            float mean_b, rden;
            ln_finish(sm, sq, mean_b, rden);
            x01 = ln_apply(x01, mean_b, rden);
            x2 = ln_apply(x2, mean_b, rden);
            put_x(x01, x2, xw, e2);
        } else {
            if (n >= 0 && head) {
                if (!last || n == NROUND - 1) mbar_wait(bar_at(B_Z), (k + last) & 1);
                const char* src = p.scr + SCR_O + head_off(h) + head_near(h, near) + last * 2048 + (w & 6) * 256 + (lane & 15) * 16;
                const uint32_t tag = (lds32(SM_EPOCH) * NB + k) | 0x80u;
                mbar_wait(bar_at(last ? B_RV : B_PS), k & 1);
                uint4 v, z;
                {
                    SPIN_DECL;
                    do {
                        v = ld_pkt(src); z = ld_pkt(src + 256);
                        SPIN_CHECK(n);
                    } while (__any_sync(0xffffffffu, (((v.w ^ tag) | (z.w ^ tag)) & 0xffu) != 0));
                }
                TRACES(tr + 0);
                float a[3][4] = {};
                const uint32_t bb[3][2] = {{v.x, v.y}, {z.x, z.y}, {v.z, z.z}};
                float sa, sb, rl;
#pragma unroll
                for (int i = 0; i < 3; i++) {
                    const uint32_t l0 = g < 4 ? bb[i][0] : 0, l1 = g < 4 ? bb[i][1] : 0, h0 = g < 4 ? 0 : bb[i][0], h1 = g < 4 ? 0 : bb[i][1];
#pragma unroll
                    for (int mt = 0; mt < 5; mt++)
                        mma16816(a[mt % 3], wo[i][mt][0], wo[i][mt][1], wo[i][mt][2], wo[i][mt][3], mt < 3 ? l0 : h0, mt < 3 ? l1 : h1);
                    if (i == 0) {
                        int key = v.w & 0xffffff00u;
                        key ^= (key >> 31) & 0x7fffffff;
                        key = __reduce_max_sync(0xffffffffu, key);
                        key ^= (key >> 31) & 0x7fffffff;
                        const float ws = fast_ex2((F(v.w & 0xffffff00u) - __int_as_float(key)) * LOG2E);
                        sa = shi(ws, e1 ? 8 : 0); sb = shi(ws, e1 ? 12 : 4);
                        rl = ws * F(z.w & 0xffffff00u);
                        rl += shx(rl, 4);
                    }
                    if (i == 1) rl += shx(rl, 8);
                }
                float y[3];
#pragma unroll
                for (int j = 2; j < 5; j++) {
                    const int mt = j % 3;
                    y[mt] = fold(fmaf(a[mt][0], sa, a[mt][1] * sb), fmaf(a[mt][2], sa, a[mt][3] * sb), e1, 1);
                }
                const uint32_t pa = SM_PO + w * 512 + lane * 16;
                if (w < 2) {
                    const char* dst = opaque(cell + s * 16384);
                    rl = fast_rcp(rl);
                    bar_sync<1, 256>();
                    const uint4 c1 = lds128(pa), c2 = lds128(pa + 1024), c3 = lds128(pa + 2048);
                    red_cell2_if(true, dst, ((y[0] + F(c1.x)) + (F(c2.x) + F(c3.x))) * rl, ((y[1] + F(c1.y)) + (F(c2.y) + F(c3.y))) * rl,
                                 ((y[2] + F(c1.z)) + (F(c2.z) + F(c3.z))) * rl);
                } else {
                    stsf4(pa - 1024, y[0], y[1], y[2], 0.f);
                    bar_sync<1, 256>();
                }
                TRACES(tr + 1);
                if ((ORD_NO_TAIL >> n) & 1) continue;
                const uint32_t tsend = clk32();
                if (n == 0) {
                    st_pkt2_if(lane < 4, p.scr + SCR_O + head_off(h) + 2048 + w * 256 + s * 64 + lane * 16, 0, 0, 0, 0);
                    __syncwarp();
                } else if (!last) {
                    const char* nsrc = p.scr + acc_off(k - 1, 1, w) + near + g * 256 + t4 * 16;
                    SPIN_DECL;
                    do {
                        v = ld_pkt(nsrc);
                        SPIN_CHECK(n);
                        nx01 = pack2(F(v.x), F(v.y)); nx2 = pack2(F(v.z), 0.f);
                    } while (__any_sync(0xffffffffu, v.w != FULL_A));
                }
                wait_clk(tsend + (w < 2 ? 0 : 60) + (n < QUIET ? CFG(DLY_AL) : CFG(DLY_A)));
                {
                    SPIN_DECL;
                    do {
                        v = ld_pkt(cell + near);
                        SPIN_CHECK(n);
                        x01 = pack2(F(v.x), F(v.y));
                        x2 = pack2(F(v.z), 0.f);
                        put_x(x01, x2, xw, e2);
                    } while (__any_sync(0xffffffffu, v.w != FULL_A));
                }
                TRACES(tr + 2);
            } else if (n >= 0) {
                x01 = nx01; x2 = nx2;
                put_x(x01, x2, xw, e2);
            } else {
                mbar_wait(bar_at(B_W + 1), 0);
                const uint32_t ln = opaque(lane);
                const int mi = ln >> 3, mr = ln & 7;
                uint32_t zero = ln >> 5;
                TRACES(76);
#pragma unroll
                for (int i = 0; i < 3; i++) {
                    const int d = 16 * (w >> 1) + (mr >> 1) + 8 * (mr & 1) + (i < 2 ? 64 * (mi >> 1) + 4 * i : 128 + 4 * (mi >> 1));
#pragma unroll
                    for (int mt = 0; mt < 5; mt++) ldsm4t(wo[i][mt], ST_WO + d * 320 + 160 * (w & 1) + 32 * mt + 16 * (mi & 1), zero);
                }
                fence_async();
                __syncwarp();
                mbar_arrive_if(lane == 0, bar_at(B_WC + 1));
                mbar_wait(bar_at(B_W + 2), 0);
                TRACES(77);
#pragma unroll
                for (int i = 0; i < 5; i++) {
                    const uint32_t ga = ST_WG + (mi & 1) * 20480 + (80 * w + 16 * i + mr + 8 * (mi >> 1)) * 32;
                    uint32_t r[4];
                    ldsm4t(wg[i], ga + (odd ? 16 : 0), zero);
                    ldsm4t(r, ga + (odd ? 0 : 16), zero);
#pragma unroll
                    for (int kh = 0; kh < 2; kh++) {
                        const uint32_t moved = __shfl_xor_sync(0xffffffffu, odd ? r[2 * kh] : r[2 * kh + 1], 16);
                        wh[i][kh] = (g < 4) == odd ? moved : odd ? r[2 * kh + 1] : r[2 * kh];
                    }
                }
                fence_async();
                __syncwarp();
                mbar_arrive_if(lane == 0, bar_at(B_WC + 2));
                TRACES(72);
                x01 = 0x3f803f80u; x2 = 0x3f80u;
                put_x(x01, x2, xw, e2);
            }
            uint32_t b[10];
            get_x(b, xr);
            float a[2][4] = {};
#pragma unroll
            for (int i = 0; i < 5; i++) {
                mma16816(a[0], wg[i][0], wg[i][1], wg[i][2], wg[i][3], b[2 * i], b[2 * i + 1]);
                mma16816(a[1], wh[i][0], b[2 * i], wh[i][1], b[2 * i + 1], b[2 * i], b[2 * i + 1]);
            }
            stsf(SM_PG + (w >> 2) * 512 + (g + 8 * t4) * 16 + (w & 3) * 4, e2 ? (e1 ? a[1][2] : a[1][0]) : (e1 ? a[0][2] : a[0][0]));
            const uint2 cs = lds64(SM_CSG + lane * 48);
            const char* dst = opaque(cell + 3 * HALF - near);
            bar_sync<2, 256>();
            const float S = sum8(lds128(SM_PG + lane * 16), lds128(SM_PG + 512 + lane * 16));
            const float sx = shi(S, 25), sq = shi(S, 24), Su = shi(S, lane + (lane < 16 ? 8 : 4));
            if (n < 0) {
                if (w == 0) stsf2(SM_CSG + lane * 48, S, Su);
            } else {
                float mean_b, rden;
                ln_fast(sx, sq, mean_b, rden);
                const float gv = bfr(fmaf(-mean_b, F(cs.x), S) * rden), uv = bfr(fmaf(-mean_b, F(cs.y), Su) * rden);
                const float sg = fast_rcp(1.f + fast_ex2(-LOG2E * gv));
                const uint32_t hb = pack2(bfr(gv * sg) * uv, 0.f);
                const uint32_t b0 = __byte_perm(shi(hb, 2 * t4), shi(hb, 2 * t4 + 1), 0x5410);
                const uint32_t b1 = __byte_perm(shi(hb, e1 ? 18 : 16), shi(hb, e1 ? 19 : 17), 0x5410);
                const bool up = g >= 4;
                const uint32_t l0 = up ? 0 : b0, h0 = up ? b0 : 0;
                const uint32_t m1 = up == e2 ? b1 : 0;
                float d[3][4] = {};
                mma16816(d[0], wd[0][0], wd[0][1], wd[0][2], wd[0][3], l0, h0);
                mma16816(d[1], wd[1][0], wd[1][1], wd[1][2], wd[1][3], l0, h0);
                mma16816(d[2], wd[2][0], wd[2][1], wd[2][2], wd[2][3], l0, up ? 0 : m1);
                mma1688(d[0], wd[3][0], wd[3][1], m1);
                mma1688(d[1], wd[3][2], wd[3][3], m1);
                red_cell(dst, e1 ? d[0][2] : d[0][0], e1 ? d[1][2] : d[1][0], e1 ? d[2][2] : d[2][0]);
                const uint32_t tsend = clk32();
                TRACES(tr + 3);
                if (last && w != cta >> 4) continue;
                const float sgr = shi(sg, 27);
                const uint32_t sg2 = pack2(sgr, sgr);
                const uint32_t n01 = opaque(pack2((bf_lo(x01) - mean_b) * rden, (bf_hi(x01) - mean_b) * rden));
                const uint32_t n2 = opaque(pack2((bf_lo(x2) - mean_b) * rden, 0.f));
                if (last) {
                    sts128_if(lane >> 1 == (cta & 15), SM_FIN + (lane & 1) * 16, x01, n01, __byte_perm(x2, n2, 0x5410), sg2);
                    mbar_arrive_if(lane >> 1 == (cta & 15), bar_at(B_FIN));
                    __syncwarp();
                    continue;
                }
                wait_clk(tsend + (n < QUIET ? CFG(DLY_BL) : CFG(DLY_B)));
                const uint32_t r01 = x01, r2 = x2;
                float cnt;
                SPIN_DECL;
                do {
                    const uint4 v = ld_pkt(cell + 2 * HALF), z = ld_pkt(cell + 3 * HALF);
                    SPIN_CHECK(n);
                    cnt = F(v.w) + F(z.w);
                    x01 = badd2(r01, badd2(n01, bmul2(pack2(F(v.x) + F(z.x), F(v.y) + F(z.y)), sg2)));
                    x2 = badd2(r2, badd2(n2, bmul2(pack2(F(v.z) + F(z.z), 0.f), sg2)));
                    put_x(x01, x2, xw, e2);
                } while (__any_sync(0xffffffffu, cnt != NCTA));
                TRACES(tr + 4);
            }
        }
        {
            uint32_t b[10];
            get_x(b, xr);
            float a[3][4] = {};
            const float f0 = bf_lo(x01), f1 = bf_hi(x01), f2 = e2 ? 0.f : bf_lo(x2);
            float st;
#pragma unroll
            for (int i = 0; i < 5; i++) {
#pragma unroll
                for (int mt = 0; mt < 3; mt++) {
                    mma16816(a[mt], wq[i][mt][0], wq[i][mt][1], wq[i][mt][2], wq[i][mt][3], b[2 * i], b[2 * i + 1]);
                    if (i == 0 && mt == 0) st = fold(fmaf(f0, f0, fmaf(f1, f1, f2 * f2)), (f0 + f1) + f2, g & 1, 4);
                }
                if (i < 4) st += shx(st, i < 2 ? 1 << i : 2 << i);
            }
            const uint32_t pa = SM_PQ + (w >> 2) * 1024 + (g & 1) * 512 + ((e2 ? 16 : 0) + (e1 ? 4 : 0) + (g >> 1)) * 16 + (w & 3) * 4;
            stsf(pa + 128, e2 ? st : e1 ? a[1][2] : a[1][0]);
            stsf(pa, e2 ? (e1 ? a[2][2] : a[2][0]) : (e1 ? a[0][2] : a[0][0]));
            bar_sync<3, 288>();
            if (n >= 0 && w == cta >> 4) {
                red_cell2_if(lane >> 1 == (cta & 15), cell + (acc_off(k, 1, 0) - acc_off(k, 0, 0)), f0, f1, f2);
                __syncwarp();
            }
        }
    }
}

__host__ __device__ constexpr int bar_count(int i) {
    return i < 16 ? 1 : i < B_RR ? 0 : i < B_RK ? 2 : i <= B_RV ? 4 : i == B_Z ? 1 : i == B_EP ? 9 : i < B_WC ? 0 : i < B_FIN ? 8 :
           i == B_FIN ? 2 : i == B_PS || i == B_RP ? 4 : i == B_QR ? 32 : 1;
}
template <int I, int END> __device__ __forceinline__ void init_bars() {
    if constexpr (I < END) {
        if (bar_count(I)) mbar_init(bar_at(I), bar_count(I));
        init_bars<I + 1, END>();
    }
}
template <int ID> __device__ __forceinline__ void role_exit() { asm volatile("exit; // %0" ::"n"(ID)); }
constexpr int NTHREADS = 512;
#define STR2(x) #x
#define STR(x) STR2(x)
__global__ void __launch_bounds__(NTHREADS, 1)
decode_kernel(const Params p, const __grid_constant__ Maps tm) {
    extern __shared__ __align__(1024) unsigned char smem[];
    if (threadIdx.x == 0) l2_prefetch(p.wq + (size_t)blockIdx.x * 12288, 12288);
    const uint32_t t0 = now_ns() - CFG(LEAD);
    const int lane = threadIdx.x & 31;
    const int warp = __reduce_max_sync(0xffffffffu, threadIdx.x >> 5);
    if (warp < 8) {
        asm volatile("setmaxnreg.inc.sync.aligned.u32 " STR(CFG_REG_CHAIN) ";");
        bar_arrive<5, 480>();
        const uint32_t vote = probe_near(p, warp, lane);
        bar_sync<2, 256 + 32>();
        sts32(SM_NEAR + warp * 4, vote);
        mbar_arrive_if(lane == 0, bar_at(B_EP));
        chain_role(p, warp, __shfl_sync(0xffffffffu, lane, lane));
        role_exit<3>();
    } else if (warp < 12) {
        asm volatile("setmaxnreg.dec.sync.aligned.u32 " STR(CFG_REG_ATT) ";");
        if (elect_one()) {
            if (warp == 8) init_bars<0, 12>();
            else if (warp == 9) init_bars<12, 30>();
            else if (warp == 10) init_bars<30, 42>();
            else init_bars<42, NBAR>();
            asm volatile("fence.mbarrier_init.release.cluster;" ::: "memory");
            fence_async();
        }
        if (warp == 8) TRACE(236);
        bar_sync<5, 480>();
        if (warp == 8) TRACE(237);
        attention_role(p, warp - 8, lane);
        role_exit<2>();
    } else {
        asm volatile("setmaxnreg.dec.sync.aligned.u32 " STR(CFG_REG_HELP) ";");
        if (warp == 12) {
            load_role(p, &tm.k, lane, t0);
            role_exit<0>();
        } else {
            if (warp == 14) {
                if (smem_u32(smem) != SB) __trap();
                if (elect_one()) {
                    asm volatile("prefetch.tensormap [%0];" ::"l"(&tm.q) : "memory");
                    mbar_init(bar_at(B_W), 1); mbar_init(bar_at(B_W + 1), 1); mbar_init(bar_at(B_W + 2), 1);
                    asm volatile("fence.mbarrier_init.release.cluster;" ::: "memory");
                    fence_async();
                    mbar_expect_tx(bar_at(B_W), 61440 + 15360 + 6400); mbar_expect_tx(bar_at(B_W + 1), 61440); mbar_expect_tx(bar_at(B_W + 2), 40960);
                    bulk_load(ST_X, p.x, 5120, bar_at(B_W));
                    bulk_load(ST_X + 5120, p.wr, 1280, bar_at(B_W));
                }
                TRACE(238);
                reload_role(p, &tm, t0);
            } else {
                if (warp == 13 && elect_one()) {
                    asm volatile("prefetch.tensormap [%0];" ::"l"(&tm.g) : "memory");
                    asm volatile("prefetch.tensormap [%0];" ::"l"(&tm.u) : "memory");
                    asm volatile("prefetch.tensormap [%0];" ::"l"(&tm.o) : "memory");
                    asm volatile("prefetch.tensormap [%0];" ::"l"(&tm.k) : "memory");
                    asm volatile("prefetch.tensormap [%0];" ::"l"(&tm.v) : "memory");
                }
                TRACE(233 + warp);
                bar_sync<5, 480>();
                if (warp == 13) { bar_arrive<6, 64>(); q_role(p, lane); }
                else { bar_arrive<2, 256 + 32>(); zero_role(p, lane, t0); }
            }
            role_exit<1>();
        }
    }
}

typedef CUresult (*EncodeFn)(CUtensorMap*, CUtensorMapDataType, cuuint32_t, void*, const cuuint64_t*, const cuuint64_t*,
                             const cuuint32_t*, const cuuint32_t*, CUtensorMapInterleave, CUtensorMapSwizzle,
                             CUtensorMapL2promotion, CUtensorMapFloatOOBfill);

bool make_map(EncodeFn fn, CUtensorMap* m, const void* ptr, uint64_t cols, uint64_t rows, uint32_t bc, uint32_t br) {
    cuuint64_t dims[2] = {cols, rows};
    cuuint64_t strides[1] = {cols * 2};
    cuuint32_t box[2] = {bc, br};
    cuuint32_t es[2] = {1, 1};
    return fn(m, CU_TENSOR_MAP_DATA_TYPE_BFLOAT16, 2, const_cast<void*>(ptr), dims, strides, box, es, CU_TENSOR_MAP_INTERLEAVE_NONE,
              CU_TENSOR_MAP_SWIZZLE_NONE, CU_TENSOR_MAP_L2_PROMOTION_L2_128B, CU_TENSOR_MAP_FLOAT_OOB_FILL_NONE) == CUDA_SUCCESS;
}

bool make_kv_map(EncodeFn fn, CUtensorMap* m, const void* ptr) {
    cuuint64_t dims[4] = {64, 8, 3, (cuuint64_t)NB * NHEAD * SK / 8};
    cuuint64_t strides[3] = {DH * 2, 128, 8 * DH * 2};
    cuuint32_t box[4] = {64, 8, 3, 4};
    cuuint32_t es[4] = {1, 1, 1, 1};
    return fn(m, CU_TENSOR_MAP_DATA_TYPE_BFLOAT16, 4, const_cast<void*>(ptr), dims, strides, box, es, CU_TENSOR_MAP_INTERLEAVE_NONE,
              CU_TENSOR_MAP_SWIZZLE_128B, CU_TENSOR_MAP_L2_PROMOTION_L2_128B, CU_TENSOR_MAP_FLOAT_OOB_FILL_NONE) == CUDA_SUCCESS;
}

}

extern "C" void kernel_launch(void* const* d_in, const int* in_sizes, int n_in, void* d_out, int out_size) {
    (void)in_sizes; (void)n_in; (void)out_size;
    static EncodeFn fn = nullptr;
    static const char* scr = nullptr;
    if (!fn) {
        void* f = nullptr;
        cudaDriverEntryPointQueryResult qr;
        if (cudaGetDriverEntryPoint("cuTensorMapEncodeTiled", &f, cudaEnableDefault, &qr) != cudaSuccess || !f) return;
        void* sp = nullptr;
        if (cudaGetSymbolAddress(&sp, g_scratch) != cudaSuccess) return;
        scr = (const char*)(((uintptr_t)sp + (2 << 20) - 1) & ~(uintptr_t)((2 << 20) - 1));
        fn = (EncodeFn)f;
        cudaFuncSetAttribute(decode_kernel, cudaFuncAttributeMaxDynamicSharedMemorySize, SMEM_BYTES);
    }
    Maps tm;
    if (!make_kv_map(fn, &tm.k, d_in[1]) || !make_kv_map(fn, &tm.v, d_in[2])) return;
    if (!make_map(fn, &tm.q, d_in[3], NHEAD * DH, DM, 48, 128) || !make_map(fn, &tm.o, d_in[4], DM, NHEAD * DH, 160, 32)) return;
    if (!make_map(fn, &tm.g, d_in[7], FF, DM, 16, 128) || !make_map(fn, &tm.u, d_in[8], FF, DM, 16, 128)) return;
    Params p;
    p.x = (const unsigned short*)d_in[0];
    p.wq = (const char*)d_in[3];
    p.wo = (const char*)d_in[4];
    p.wr = (const unsigned short*)d_in[6];
    p.wg = (const char*)d_in[7];
    p.wu = (const char*)d_in[8];
    p.wd = (const char*)d_in[9];
    p.out = (unsigned short*)d_out;
    p.scr = scr;
    decode_kernel<<<NCTA, NTHREADS, SMEM_BYTES>>>(p, tm);
}
```

```cpp
#include <cuda_runtime.h>
#include <cuda_bf16.h>
#include <cuda.h>
#include <stdint.h>

namespace {

constexpr int NB = 4, DM = 640, NHEAD = 32, DH = 192, SK = 4096, WIN = 1024, FF = 1536;
constexpr int NCTA = 128;
constexpr int TILE = 12288, PAIR = 2 * TILE;

#define CFG_LIST(X) \
    X(TICK0, 479)        \
    X(TICK, 495)        \
    X(LEAD, 600)        \
    X(STAG, 500)        \
    X(WLAG, 350)        \
    X(GSTEP, 750)        \
    X(WIN, 5)        \
    X(PMAX, 2)        \
    X(PGRACE, 50)        \
    X(LMAX0, 150)        \
    X(LMAX, 160) \
    X(GAIN, 5)        \
    X(VSTEP, 150)        \
    X(RSTEP, 670)        \
    X(RSTEP3, 450) \
    X(ZTILE, 11)        \
    X(DLY_A, 410)        \
    X(DLY_AL, 100) \
    X(DLY_B, 570) \
    X(DLY_BL, 950) \
    X(DLY_F, 290) \
    X(MAP, 0) \
    X(PERM, 13) \
    X(FLIP, 0) \

#define X(n, v) constexpr int CFG_##n = v;
CFG_LIST(X)
#undef X
#define CFG(n) CFG_##n
constexpr int QUIET = 8;
#define CFG_REG_CHAIN 216
#define CFG_REG_ATT 48
#define CFG_REG_HELP 32
__device__ __forceinline__ int cta_id() {
    const int b = blockIdx.x;
    return CFG(MAP) == 0 ? b : CFG(MAP) == 1 ? (b & 31) << 2 | b >> 5 : CFG(MAP) == 2 ? (b & 1) << 6 | b >> 1 : ((b >> 1) & 31) << 2 | (b >> 6) << 1 | (b & 1);
}
constexpr int KB_KV0 = 165;
__device__ __forceinline__ int kb_ns(int kb) { return kb * CFG(TICK0) / 12; }
__device__ __forceinline__ int tick_ns(int j) { return j <= 16 ? CFG(TICK0) : CFG(TICK); }
__device__ __forceinline__ int batch_ns(int k) { return kb_ns(KB_KV0) + (k ? 16 * (CFG(TICK0) + (k - 1) * CFG(TICK)) : 0); }

__device__ __forceinline__ uint32_t slots(int k) { return k & 2 ? (k & 1 ? 0x21304768u : 0x76835214u) : (k & 1 ? 0x21480765u : 0x76543210u); }
__device__ __forceinline__ int pass_nibble(int k, int u) { return k > 0 ? 4 + (u & 1) : u; }
__device__ __forceinline__ uint32_t slot_at(uint32_t tab, int u) { return (tab >> (4 * u)) & 15; }

constexpr int NROUND = 11;
constexpr uint32_t ORD_BATCH = 0x3b9910, ORD_LAST = 0x6da, ORD_NO_HEAD = 0x248, ORD_NO_TAIL = 0x092;

constexpr uint32_t SB = 1024;
constexpr uint32_t SM_BAR = SB + 9 * PAIR;
constexpr int B_F1 = 0;
constexpr int B_RR = 24;
constexpr int B_RK = 32;
constexpr int B_RV = 36;
constexpr int B_Z = 37;
constexpr int B_EP = 38;
constexpr int B_W = 39;
constexpr int B_WC = 42;
constexpr int B_FIN = 45;
constexpr int B_F3 = 46;
constexpr int B_PS = 48;
constexpr int B_RP = 49;
constexpr int B_FL = 50;
constexpr int B_QR = 51;
constexpr int NBAR = 52;
__host__ __device__ constexpr uint32_t bar_at(int i) { return SM_BAR + 8 * i; }
constexpr uint32_t SM_EPOCH = SM_BAR + 416;
constexpr uint32_t SM_MAX = SM_EPOCH + 16;
constexpr uint32_t SM_SUM = SM_MAX + 16;
constexpr uint32_t SM_NEAR = SM_SUM + 32;
constexpr uint32_t SM_FIN = SM_NEAR + 32;
constexpr uint32_t SM_Q = SM_FIN + 32;
constexpr uint32_t PSTR = 144;
constexpr uint32_t SM_P = SM_Q + 5 * 384;
constexpr uint32_t SM_X = SM_P + 8 * PSTR;
constexpr uint32_t SM_CSG = SM_X + 40;
constexpr uint32_t SM_ONES = SM_X + 8 * 384;
constexpr uint32_t SM_PG = SM_ONES + 48;
constexpr uint32_t SM_PO = SM_PG + 1024;
constexpr uint32_t SM_PQ = SM_PO;
constexpr int SMEM_BYTES = SM_PO + 3072 - SB;
static_assert(SMEM_BYTES <= 232448 && SM_Q % 16 == 0 && SM_P % 16 == 0 && SM_X % 16 == 0 && SM_PO % 16 == 0, "smem");
constexpr uint32_t ST_WQ = SB, ST_WD = SB + 3 * PAIR, ST_WO = SB + 4 * PAIR, ST_WG = SB + 7 * PAIR, ST_X = ST_WG + 40960;

__device__ unsigned g_epoch;
__device__ unsigned char g_scratch[4 << 20];
constexpr uint32_t HALF = 4096, SCR_O = 1 << 16, SCR_Q = 1 << 17, SCR_COUNT = 3 << 16;
__device__ __forceinline__ uint32_t acc_off(int k, int layer, int w) {
    return (k & 1) << 6 | layer << 7 | (w & 1) << 11 | (w >> 1) << 14 | (k + layer == NB) << 18;
}
__device__ __forceinline__ uint32_t head_off(int h) { return (h & 3) << 14 | (h & 4) << 16 | (h & 8) << 17 | (h & 16) << 9; }
__device__ __forceinline__ uint32_t head_near(int h, uint32_t near) { return near ^ HALF ^ (h & 16) << 8; }
constexpr uint32_t FULL_A = 0x42040000u;

struct Params {
    const char* wq;
    const unsigned short* x;
    const char* wo;
    const unsigned short* wr;
    const char* wg;
    const char* wu;
    const char* wd;
    unsigned short* out;
    const char* scr;
};

__device__ __forceinline__ uint32_t smem_u32(const void* p) { return (uint32_t)__cvta_generic_to_shared(p); }
__device__ __forceinline__ void mbar_init(uint32_t a, uint32_t c) { asm volatile("mbarrier.init.shared::cta.b64 [%0], %1;" ::"r"(a), "r"(c) : "memory"); }
__device__ __forceinline__ void mbar_expect_tx(uint32_t a, uint32_t b) {
    asm volatile("mbarrier.arrive.expect_tx.shared::cta.b64 _, [%0], %1;" ::"r"(a), "r"(b) : "memory");
}
__device__ __forceinline__ void mbar_arrive(uint32_t a) { asm volatile("mbarrier.arrive.shared::cta.b64 _, [%0];" ::"r"(a) : "memory"); }
constexpr uint32_t SPIN_LIMIT = 1u << 22;
#define SPIN_DECL uint32_t spins = 0
#define SPIN_CHECK(info) { if (++spins > SPIN_LIMIT) __trap(); }
__device__ __forceinline__ void jitter() {}
__device__ __forceinline__ void mbar_wait(uint32_t a, uint32_t parity) {
    jitter();
    uint32_t ok;
    SPIN_DECL;
    while (true) {
        asm volatile("{\n.reg .pred p;\nmbarrier.try_wait.parity.shared::cta.b64 p, [%1], %2;\nselp.u32 %0, 1, 0, p;\n}"
                     : "=r"(ok) : "r"(a), "r"(parity) : "memory");
        if (ok) break;
        SPIN_CHECK((a - SM_BAR) / 8 * 10 + parity);
    }
    jitter();
}
__device__ __forceinline__ bool mbar_test2(uint32_t a, uint32_t pa, uint32_t b, uint32_t pb) {
    uint32_t ok;
    asm volatile("{\n.reg .pred p, q;\nmbarrier.test_wait.parity.shared::cta.b64 p, [%1], %2;\n"
                 "mbarrier.test_wait.parity.shared::cta.b64 q, [%3], %4;\nand.pred p, p, q;\nvote.sync.all.pred p, p, 0xffffffff;\nselp.u32 %0, 1, 0, p;\n}"
                 : "=r"(ok) : "r"(a), "r"(pa), "r"(b), "r"(pb) : "memory");
    return ok;
}
__device__ __forceinline__ uint32_t now_ns() { uint32_t t; asm volatile("mov.u32 %0, %%globaltimer_lo;" : "=r"(t) :: "memory"); return t; }
__device__ __forceinline__ uint32_t clk32() { uint32_t c; asm volatile("mov.u32 %0, %%clock;" : "=r"(c) :: "memory"); return c; }
__device__ __forceinline__ void wait_ns(uint32_t t) { jitter(); while ((int)(now_ns() - t) < 0) {} }
__device__ __forceinline__ void wait_clk(uint32_t t) { jitter(); while ((int)(clk32() - t) < 0) {} }
__device__ __forceinline__ bool elect_one() {
    uint32_t e;
    asm volatile("{\n.reg .pred p;\nelect.sync _|p, 0xffffffff;\nselp.u32 %0, 1, 0, p;\n}" : "=r"(e));
    return e;
}
constexpr uint64_t POL_FIRST = 0x12F0000000000000ull, POL_NORMAL = 0x1000000000000000ull;
__device__ __forceinline__ void tma_tile(uint32_t dst, const CUtensorMap* tm, int group, uint32_t bar, uint64_t pol) {
    asm volatile("cp.async.bulk.tensor.4d.shared::cluster.global.mbarrier::complete_tx::bytes.L2::cache_hint"
                 " [%0], [%1, {%3, %3, %3, %4}], [%2], %5;"
                 ::"r"(dst), "l"(tm), "r"(bar), "r"(0), "r"(group), "l"(pol) : "memory");
}
__device__ __forceinline__ void tma2d(uint32_t dst, const CUtensorMap* tm, int x, int y, uint32_t bar) {
    asm volatile("cp.async.bulk.tensor.2d.shared::cluster.global.mbarrier::complete_tx::bytes [%0], [%1, {%3, %4}], [%2];"
                 ::"r"(dst), "l"(tm), "r"(bar), "r"(x), "r"(y) : "memory");
}
__device__ __forceinline__ void bulk_load(uint32_t dst, const void* src, uint32_t bytes, uint32_t bar) {
    asm volatile("cp.async.bulk.shared::cluster.global.mbarrier::complete_tx::bytes [%0], [%1], %2, [%3];"
                 ::"r"(dst), "l"(src), "r"(bytes), "r"(bar) : "memory");
}
__device__ __forceinline__ void l2_prefetch(const void* p, uint32_t bytes) {
    asm volatile("cp.async.bulk.prefetch.L2.global [%0], %1;" ::"l"(p), "r"(bytes) : "memory");
}
__device__ __forceinline__ void mma16816(float (&c)[4], uint32_t a0, uint32_t a1, uint32_t a2, uint32_t a3, uint32_t b0, uint32_t b1) {
    asm volatile("mma.sync.aligned.m16n8k16.row.col.f32.bf16.bf16.f32 {%0,%1,%2,%3}, {%4,%5,%6,%7}, {%8,%9}, {%0,%1,%2,%3};"
                 : "+f"(c[0]), "+f"(c[1]), "+f"(c[2]), "+f"(c[3]) : "r"(a0), "r"(a1), "r"(a2), "r"(a3), "r"(b0), "r"(b1));
}
__device__ __forceinline__ void mma1688(float (&c)[4], uint32_t a0, uint32_t a1, uint32_t b0) {
    asm volatile("mma.sync.aligned.m16n8k8.row.col.f32.bf16.bf16.f32 {%0,%1,%2,%3}, {%4,%5}, {%6}, {%0,%1,%2,%3};"
                 : "+f"(c[0]), "+f"(c[1]), "+f"(c[2]), "+f"(c[3]) : "r"(a0), "r"(a1), "r"(b0));
}
__device__ __forceinline__ void ldsm4(uint32_t (&r)[4], uint32_t a) {
    asm volatile("ldmatrix.sync.aligned.m8n8.x4.shared.b16 {%0,%1,%2,%3}, [%4];"
                 : "=r"(r[0]), "=r"(r[1]), "=r"(r[2]), "=r"(r[3]) : "r"(a) : "memory");
}
__device__ __forceinline__ void ldsm4t(uint32_t (&r)[4], uint32_t a, uint32_t& zero) {
    asm volatile("ldmatrix.sync.aligned.m8n8.x4.trans.shared.b16 {%0,%1,%2,%3}, [%4];"
                 : "=r"(r[0]), "=r"(r[1]), "=r"(r[2]), "=r"(r[3]) : "r"(a + zero) : "memory");
    zero &= r[3];
}
__device__ __forceinline__ uint4 ld_pkt(const void* p) {
    uint4 v;
    asm volatile("{\n.reg .b128 t;\nld.relaxed.gpu.global.b128 t, [%4];\nmov.b128 {%0,%1,%2,%3}, t;\n}"
                 : "=r"(v.x), "=r"(v.y), "=r"(v.z), "=r"(v.w) : "l"(p) : "memory");
    return v;
}
__device__ __forceinline__ void st_pkt(const void* p, uint32_t a, uint32_t b, uint32_t c, uint32_t d) {
    asm volatile("{\n.reg .b128 t;\nmov.b128 t, {%1,%2,%3,%4};\nst.relaxed.gpu.global.b128 [%0], t;\n}"
                 ::"l"(p), "r"(a), "r"(b), "r"(c), "r"(d) : "memory");
}
__device__ __forceinline__ uint2 ld_pkt8(const void* p) {
    uint2 v;
    asm volatile("{\n.reg .b64 t;\nld.relaxed.gpu.global.b64 t, [%2];\nmov.b64 {%0,%1}, t;\n}" : "=r"(v.x), "=r"(v.y) : "l"(p) : "memory");
    return v;
}
__device__ __forceinline__ void red_cell(const char* p, float a, float b, float c) {
    jitter();
    asm volatile("red.relaxed.gpu.global.add.v4.f32 [%0], {%1,%2,%3,%4};" ::"l"(p), "f"(a), "f"(b), "f"(c), "f"(1.0f) : "memory");
}
#define PRED(n) "{\n.reg .pred p;\nsetp.ne.u32 p, %" #n ", 0;\n"
__device__ __forceinline__ void red_cell2_if(bool on, const char* p, float a, float b, float c) {
    jitter();
    asm volatile(PRED(5) "@p red.relaxed.gpu.global.add.v4.f32 [%0], {%1,%2,%3,%4};\n@p red.relaxed.gpu.global.add.v4.f32 [%0+4096], {%1,%2,%3,%4};\n}"
                 ::"l"(p), "f"(a), "f"(b), "f"(c), "f"(1.0f), "r"((uint32_t)on) : "memory");
}
__device__ __forceinline__ void st_pkt8_if(bool on, const void* p, uint32_t a, uint32_t b) {
    jitter();
    asm volatile(PRED(3) ".reg .b64 t;\nmov.b64 t, {%1,%2};\n@p st.relaxed.gpu.global.b64 [%0], t;\n}" ::"l"(p), "r"(a), "r"(b), "r"((uint32_t)on) : "memory");
}
__device__ __forceinline__ void st_pkt82_if(bool on, const void* p, uint32_t a, uint32_t b) {
    asm volatile(PRED(3) ".reg .b64 t;\nmov.b64 t, {%1,%2};\n@p st.relaxed.gpu.global.b64 [%0], t;\n@p st.relaxed.gpu.global.b64 [%0+4096], t;\n}"
                 ::"l"(p), "r"(a), "r"(b), "r"((uint32_t)on) : "memory");
}
__device__ __forceinline__ void st_pkt2_if(bool on, const void* p, uint32_t a, uint32_t b, uint32_t c, uint32_t d) {
    jitter();
    asm volatile(PRED(5) ".reg .b128 t;\nmov.b128 t, {%1,%2,%3,%4};\n@p st.relaxed.gpu.global.b128 [%0], t;\n@p st.relaxed.gpu.global.b128 [%0+4096], t;\n}"
                 ::"l"(p), "r"(a), "r"(b), "r"(c), "r"(d), "r"((uint32_t)on) : "memory");
}
__device__ __forceinline__ void mbar_arrive_if(bool on, uint32_t a) {
    jitter();
    asm volatile(PRED(1) "@p mbarrier.arrive.shared::cta.b64 _, [%0];\n}" ::"r"(a), "r"((uint32_t)on) : "memory");
}
__device__ __forceinline__ void sts16_if(bool on, uint32_t a, uint32_t v) {
    asm volatile(PRED(2) "@p st.shared.u16 [%0], %1;\n}" ::"r"(a), "h"((unsigned short)v), "r"((uint32_t)on) : "memory");
}
__device__ __forceinline__ void sts32_if(bool on, uint32_t a, uint32_t v) {
    asm volatile(PRED(2) "@p st.shared.u32 [%0], %1;\n}" ::"r"(a), "r"(v), "r"((uint32_t)on) : "memory");
}
__device__ __forceinline__ void sts128_if(bool on, uint32_t a, uint32_t x, uint32_t y, uint32_t z, uint32_t w) {
    jitter();
    asm volatile(PRED(5) "@p st.shared.v4.u32 [%0], {%1,%2,%3,%4};\n}" ::"r"(a), "r"(x), "r"(y), "r"(z), "r"(w), "r"((uint32_t)on) : "memory");
}
__device__ __forceinline__ float fast_rcp(float x) { float r; asm("rcp.approx.ftz.f32 %0, %1;" : "=f"(r) : "f"(x)); return r; }
__device__ __forceinline__ float fast_sqrt(float x) { float r; asm("sqrt.approx.ftz.f32 %0, %1;" : "=f"(r) : "f"(x)); return r; }
__device__ __forceinline__ float fast_ex2(float x) { float r; asm("ex2.approx.ftz.f32 %0, %1;" : "=f"(r) : "f"(x)); return r; }
__device__ __forceinline__ uint32_t pack2(float lo, float hi) {
    uint32_t r;
    asm("cvt.rn.bf16x2.f32 %0, %1, %2;" : "=r"(r) : "f"(hi), "f"(lo));
    return r;
}
__device__ __forceinline__ float bfr(float x) { return __uint_as_float(pack2(0.f, x)); }
__device__ __forceinline__ uint32_t badd2(uint32_t a, uint32_t b) { uint32_t r; asm("add.rn.bf16x2 %0, %1, %2;" : "=r"(r) : "r"(a), "r"(b)); return r; }
__device__ __forceinline__ uint32_t bsub2(uint32_t a, uint32_t b) { uint32_t r; asm("sub.rn.bf16x2 %0, %1, %2;" : "=r"(r) : "r"(a), "r"(b)); return r; }
__device__ __forceinline__ uint32_t bmul2(uint32_t a, uint32_t b) { uint32_t r; asm("mul.rn.bf16x2 %0, %1, %2;" : "=r"(r) : "r"(a), "r"(b)); return r; }
__device__ __forceinline__ float bf_lo(uint32_t w) { return __uint_as_float(w << 16); }
__device__ __forceinline__ float bf_hi(uint32_t w) { return __uint_as_float(w & 0xffff0000u); }
__device__ __forceinline__ float F(uint32_t t) { return __uint_as_float(t); }
__device__ __forceinline__ uint32_t lds16(uint32_t a) { unsigned short h; asm volatile("ld.shared.u16 %0, [%1];" : "=h"(h) : "r"(a) : "memory"); return h; }
__device__ __forceinline__ uint32_t lds32(uint32_t a) { uint32_t v; asm volatile("ld.shared.u32 %0, [%1];" : "=r"(v) : "r"(a) : "memory"); return v; }
__device__ __forceinline__ uint2 lds64(uint32_t a) {
    uint2 v; asm volatile("ld.shared.v2.u32 {%0,%1}, [%2];" : "=r"(v.x), "=r"(v.y) : "r"(a) : "memory"); return v;
}
__device__ __forceinline__ uint4 lds128(uint32_t a) {
    uint4 v; asm volatile("ld.shared.v4.u32 {%0,%1,%2,%3}, [%4];" : "=r"(v.x), "=r"(v.y), "=r"(v.z), "=r"(v.w) : "r"(a) : "memory"); return v;
}
__device__ __forceinline__ float sum8(const uint4& u, const uint4& v) {
    return ((F(u.x) + F(u.y)) + (F(u.z) + F(u.w))) + ((F(v.x) + F(v.y)) + (F(v.z) + F(v.w)));
}
__device__ __forceinline__ void sts16(uint32_t a, uint32_t v) { asm volatile("st.shared.u16 [%0], %1;" ::"r"(a), "h"((unsigned short)v) : "memory"); }
__device__ __forceinline__ void sts32(uint32_t a, uint32_t v) { asm volatile("st.shared.u32 [%0], %1;" ::"r"(a), "r"(v) : "memory"); }
__device__ __forceinline__ void stsf(uint32_t a, float v) { asm volatile("st.shared.f32 [%0], %1;" ::"r"(a), "f"(v) : "memory"); }
__device__ __forceinline__ void stsf2(uint32_t a, float x, float y) { asm volatile("st.shared.v2.f32 [%0], {%1,%2};" ::"r"(a), "f"(x), "f"(y) : "memory"); }
__device__ __forceinline__ void stsf4(uint32_t a, float x, float y, float z, float w) {
    asm volatile("st.shared.v4.f32 [%0], {%1,%2,%3,%4};" ::"r"(a), "f"(x), "f"(y), "f"(z), "f"(w) : "memory");
}
template <int ID, int N> __device__ __forceinline__ void bar_sync() { jitter(); asm volatile("bar.sync %0, %1;" ::"n"(ID), "n"(N) : "memory"); jitter(); }
template <int ID, int N> __device__ __forceinline__ void bar_arrive() { jitter(); asm volatile("bar.arrive %0, %1;" ::"n"(ID), "n"(N) : "memory"); jitter(); }
__device__ __forceinline__ void fence_async() { asm volatile("fence.proxy.async.shared::cta;" ::: "memory"); }
__device__ __forceinline__ float shx(float v, int m) { return __shfl_xor_sync(0xffffffffu, v, m); }
__device__ __forceinline__ float shi(float v, int l) { return __shfl_sync(0xffffffffu, v, l); }
__device__ __forceinline__ uint32_t shi(uint32_t v, int l) { return __shfl_sync(0xffffffffu, v, l); }
__device__ __forceinline__ uint32_t opaque(uint32_t x) { asm volatile("mov.u32 %0, %0;" : "+r"(x)); return x; }
__device__ __forceinline__ const char* opaque(const char* x) { asm volatile("mov.u64 %0, %0;" : "+l"(x)); return x; }
constexpr float LOG2E = 1.4426950408889634f, SCALE = 0.07216878364870322f;

#define TRACE(idx) do {} while (0)
#define TRACES(slot) do {} while (0)

__device__ __forceinline__ uint32_t probe_near(const Params& p, int w, int lane) {
    const int cta = cta_id();
    const char* pr = p.scr + SCR_O + head_off(cta >> 2) + 2048 + w * 256 + (cta & 3) * 64;
    st_pkt2_if(lane < 4, pr + lane * 16, 0, 0, 0, 0);
    uint32_t best0 = ~0u, best1 = ~0u;
#pragma unroll 1
    for (int i = w & 1; i < 6 + (w & 1); i++) {
        uint32_t c = clk32(), v = 0;
        if (lane == 0) asm volatile("atom.relaxed.gpu.global.add.u32 %0, [%1], 1;" : "=r"(v) : "l"(pr + (i & 1) * HALF) : "memory");
        c += __shfl_sync(0xffffffffu, v, 0) >> 16;
        c = clk32() - c;
        if (i & 1) best1 = min(best1, c); else best0 = min(best0, c);
    }
    return min(best0, 0xffffu) | min(best1, 0xffffu) << 16;
}
__device__ __forceinline__ uint32_t near_half() {
    const uint4 a = lds128(SM_NEAR), b = lds128(SM_NEAR + 16);
    const uint32_t m = __vminu2(__vminu2(__vminu2(a.x, a.y), __vminu2(a.z, a.w)), __vminu2(__vminu2(b.x, b.y), __vminu2(b.z, b.w)));
    return head_near(cta_id() >> 2, ((m & 0xffffu) > m >> 16) != (CFG(FLIP) != 0) ? HALF : 0);
}

__device__ __forceinline__ int kv_group(int k, int t) {
    const int cta = cta_id();
    return ((k * NHEAD + (cta >> 2)) * SK + (SK - WIN) + (cta & 3) * 32 + t * 128) / 8;
}
__device__ __forceinline__ uint32_t phase_ns() { return (((cta_id() >> 2) * CFG(PERM)) & 31) * CFG(STAG) / 32; }

__device__ __forceinline__ void ln_fast(float s, float q, float& mean, float& rstd) {
    mean = s * (1.f / DM);
    asm("rsqrt.approx.ftz.f32 %0, %1;" : "=f"(rstd) : "f"(fmaxf(fmaf(-mean, mean, fmaf(q, 1.f / DM, 1e-5f)), 1e-5f)));
}
__device__ __forceinline__ void q_role(const Params& p, int lane) {
    const int cta = cta_id();
    mbar_wait(bar_at(B_EP), 0);
    const uint32_t epoch = lds32(SM_EPOCH), near = head_near(cta >> 2, near_half());
    auto sums = [&](float& S0, float& S1) {
        bar_sync<3, 288>();
        const uint32_t ra = SM_PQ + lane * 16;
        S0 = sum8(lds128(ra), lds128(ra + 1024)); S1 = sum8(lds128(ra + 512), lds128(ra + 1536));
    };
    float cs0, cs1;
    {
        uint32_t q0 = 0, q1 = 0, q2 = 0, q3 = 0;
#pragma unroll 1
        for (int r = 0; r < NB; r++) {
            sums(cs0, cs1);
            bar_arrive<7, 288>();
            q0 = q1; q1 = q2; q2 = q3; q3 = pack2(cs0, cs1);
        }
        const uint32_t t0 = shi(q3, 3 * lane - 72), t1 = shi(q3, 3 * lane - 71), t2 = shi(q3, 3 * lane - 70), tag = epoch << 8 | 0x40;
        const char* box = p.scr + SCR_O + head_off(cta >> 2) + 2048 + (lane >> 2) * 256 + (lane & 3) * 16;
        st_pkt2_if(true, box + (cta & 3) * 64, lane < 24 ? q0 : t0, lane < 24 ? q1 : t1, lane < 24 ? q2 : t2, tag);
        const uint32_t qd = SM_Q + (lane < 24 ? lane * 4 : 3 * 384 + (lane - 24) * 12), step = lane < 24 ? 384 : 4;
#pragma unroll 1
        for (int j = 0; j < 4; j++) {
            uint4 v;
            SPIN_DECL;
            do {
                __nanosleep(200);
                v = ld_pkt(box + near + j * 64);
                SPIN_CHECK(j);
            } while (__any_sync(0xffffffffu, v.w != tag));
            sts32(qd + j * 96, v.x); sts32(qd + j * 96 + step, v.y); sts32(qd + j * 96 + 2 * step, v.z);
        }
        mbar_arrive(bar_at(B_QR));
    }
    sums(cs0, cs1);
    bar_arrive<7, 288>();
    const char* const src = p.scr + SCR_Q + head_off(cta >> 2) + lane * 8 + near;
    const char* const dst = src + (cta & 3) * 192;
    const uint32_t qd = SM_Q + NB * 384 + lane * 4;
    st_pkt82_if(lane < 24, dst - near, 0, 0);
#pragma unroll 1
    for (int k = 0; k < NB; k++) {
        float S0, S1, mean, rstd;
        sums(S0, S1);
        ln_fast(shi(S1, 24), shi(S0, 24), mean, rstd);
        const uint32_t qq = pack2(fmaf(-mean, cs0, S0) * rstd, fmaf(-mean, cs1, S1) * rstd), tag = epoch * NB + k;
        st_pkt8_if(lane < 24, dst + ((int)HALF - 2 * (int)near), qq, tag);
        st_pkt8_if(lane < 24, dst, qq, tag);
        TRACES(k * 12 + 5);
        uint2 a, b, c;
        SPIN_DECL;
        do {
            a = ld_pkt8(src); b = ld_pkt8(src + 256); c = ld_pkt8(src + 512);
            SPIN_CHECK(k);
            sts32(qd, a.x); sts32(qd + 128, b.x); sts32(qd + 256, c.x);
        } while (__any_sync(0xffffffffu, a.y != tag || b.y != tag || c.y != tag));
        mbar_arrive(bar_at(B_QR));
    }
}

struct Maps { CUtensorMap k, v, q, o, g, u; };
__device__ __forceinline__ void load_role(const Params& p, const CUtensorMap* tmKV, int lane, uint32_t t0) {
    const int cta = cta_id();
    t0 += phase_ns();
#pragma unroll 1
    for (int i = 1; i < 5; i++) {
        wait_ns(t0 + i * CFG(TICK0));
        if (elect_one()) l2_prefetch(p.wq + (size_t)(128 * i + cta) * 12288, 12288);
        TRACE(230 + i);
    }
    uint32_t plan[2];
#pragma unroll
    for (int i = 0; i < 2; i++) {
        const int j = lane + 32 * i, k = j >> 4, t = j & 15, u = t >> 1, jw = j - CFG(WIN);
        const int sb = k == 0 ? B_WC + (t >= 8) + (t >= 14) : t >= 12 ? B_RK + u - 5 : t >= 4 ? B_RR + t - 4 : t >= 2 ? B_RP : k > 1 ? B_RK + 3 : B_RR + t;
        const uint32_t sw = sb * 8 | (j < 18 ? 0 : (t >= 12 || u == 1 ? k - 1 : k) & 1) << 9;
        plan[i] = sw | (jw < 0 ? sw : (B_F1 + (jw & 15)) * 8 | ((jw >> 4) & 1) << 9) << 10 |
                  (slot_at(slots(k), t < 8 ? pass_nibble(k, u) : u) * 2 + (t & 1)) << 20 | (t < 10 && j >= 8 && j < 56) << 25;
    }
    bar_sync<6, 64>();
    wait_ns(t0 + kb_ns(60));
    if (elect_one()) bulk_load(ST_WD, p.wd + cta * 15360, 15360, bar_at(B_W));
    TRACE(235);
#pragma unroll 1
    for (int i = 0; i < 5; i++) {
        wait_ns(t0 + kb_ns(75) + i * kb_ns(6));
        if (elect_one()) { l2_prefetch(p.wg + (128 * i + cta) * 3072, 3072); l2_prefetch(p.wu + (128 * i + cta) * 3072, 3072); }
    }
#pragma unroll 1
    for (int i = 0; i < 6; i++) {
        wait_ns(t0 + kb_ns(105) + min(i, 4) * kb_ns(10));
        if (elect_one()) l2_prefetch(p.wo + (size_t)((cta >> 2) * DH + 32 * i + 8 * (cta & 3)) * 1280, 10240);
    }
    t0 += batch_ns(0);
    int jp = 0, shift = 0;
    uint32_t earliest = t0;
    auto requested = [&](uint32_t now) {
        shift = max(max(shift - CFG(GAIN), 0), (int)(now - t0) - (jp < 12 ? CFG(LMAX0) : CFG(LMAX)));
        TRACE(128 + jp);
        t0 += tick_ns(++jp);
    };
    const int grp0 = kv_group(0, 0);
    auto group = [&](int j) { return grp0 + (j >> 4) * (NHEAD * SK / 8) + (j & 7) * 16; };
#pragma unroll 1
    for (int j = 0; j < 16 * NB; j++) {
        const uint32_t pl = __shfl_sync(0xffffffffu, j & 32 ? plan[1] : plan[0], j);
        const int jmax = min(j + CFG(PMAX), 16 * NB);
        jitter();
        uint32_t now;
        SPIN_DECL;
        while (true) {
            const bool ok = mbar_test2(SM_BAR + (pl & 511), (pl >> 9) & 1, SM_BAR + ((pl >> 10) & 511), (pl >> 19) & 1);
            now = now_ns();
            const int late = now - t0 - shift;
            if (ok && (jp > j ? (int)(now - earliest) : late) >= 0) break;
            if (late >= (jp > j ? 0 : CFG(PGRACE)) && jp < jmax) {
                if (elect_one())
                    asm volatile("cp.async.bulk.prefetch.tensor.4d.L2.global [%0, {%1, %1, %1, %2}];" ::"l"(tmKV + ((jp >> 3) & 1)), "r"(0), "r"(group(jp)) : "memory");
                requested(now);
            }
            SPIN_CHECK(j);
        }
        if (elect_one()) {
            mbar_expect_tx(bar_at(B_F1 + (j & 15)), TILE);
            tma_tile(SB + ((pl >> 20) & 31) * TILE, tmKV + ((j >> 3) & 1), group(j), bar_at(B_F1 + (j & 15)), pl >> 25 ? POL_NORMAL : POL_FIRST);
        }
        TRACE(256 + j);
        if ((j & 15) == 15) TRACES(88 + (j >> 4));
        earliest = now + CFG(VSTEP);
        if (jp == j) requested(now);
    }
}

__device__ __forceinline__ void reload_role(const Params& p, const Maps* tm, uint32_t t0) {
    const CUtensorMap* const tmK = &tm->k;
    const CUtensorMap* const tmV = &tm->v;
    const int cta = cta_id();
    t0 += CFG(TICK0) + CFG(WLAG) + phase_ns();
#pragma unroll 1
    for (int i = 0; i < 5; i++) {
        wait_ns(t0 + i * CFG(TICK0));
        if (elect_one()) tma2d(ST_WQ + i * 12288, &tm->q, 48 * cta, 128 * i, bar_at(B_W));
        TRACE(240 + i);
        if (i == 1) bar_sync<5, 480>();
    }
#pragma unroll 1
    for (int i = 0, o = 0; i < 10;) {
        const uint32_t now = now_ns() - t0;
        if (o < 6 && (int)now >= kb_ns(105) + o * kb_ns(10)) {
            if (elect_one()) tma2d(ST_WO + o * 10240, &tm->o, 160 * (cta & 3), (cta >> 2) * DH + 32 * o, bar_at(B_W + 1));
            o++;
        } else if ((int)now >= kb_ns(77) + i * CFG(GSTEP) && (i < 9 || o == 6)) {
            if (elect_one()) tma2d(ST_WG + (i & 1) * 20480 + (i >> 1) * 4096, i & 1 ? &tm->u : &tm->g, (12 * cta) & ~7, 128 * (i >> 1), bar_at(B_W + 2));
            i++;
        }
    }
#pragma unroll 1
    for (int k = 0; k < NB - 1; k++) {
        mbar_wait(bar_at(B_RK), k & 1);
        if (elect_one()) {
            const uint32_t dst = SB + slot_at(slots(k), 0) * PAIR;
            mbar_expect_tx(bar_at(B_FL), PAIR);
            tma_tile(dst, tmV, kv_group(k, 0), bar_at(B_FL), POL_FIRST);
            tma_tile(dst + TILE, tmV, kv_group(k, 1), bar_at(B_FL), POL_FIRST);
        }
        mbar_wait(bar_at(B_RV), k & 1);
        uint32_t due = now_ns();
        if (elect_one()) mbar_expect_tx(bar_at(B_F3), 4 * PAIR);
#pragma unroll 1
        for (int t = 0; t < 8; t++) {
            wait_ns(due);
            due += k == NB - 2 ? CFG(RSTEP3) : CFG(RSTEP);
            if (elect_one())
                tma_tile(SB + slot_at(slots(k + 1), t >> 1) * PAIR + (t & 1) * TILE, tmK, kv_group(k + 1, t), bar_at(B_F3), POL_FIRST);
        }
        TRACE(121 + k);
    }
}

__device__ __forceinline__ void zero_role(const Params& p, int lane, uint32_t t0) {
    const int cta = cta_id();
    unsigned ticket = 0;
    if (lane == 0) ticket = atomicAdd(&g_epoch, 1u);
    const uint32_t epoch = __shfl_sync(0xffffffffu, ticket, 0) / NCTA + 1;
    if (lane == 0) { sts32(SM_EPOCH, epoch); mbar_arrive(bar_at(B_EP)); }
    mbar_wait(bar_at(B_EP), 0);
#pragma unroll 1
    for (int k = 0; k < NB + 2; k++) {
        lane = opaque(lane);
        const int cl = 2 * (cta & 15) + (lane & 1);
        const int col = 80 * (cta >> 4) + (cl & 2 ? 48 : 0) + (cl >> 2) + (cl & 1 ? 8 : 0);
        const char* own = p.scr + (cl >> 2) * 256 + (cl & 3) * 16;
        uint32_t v0 = 0, v1 = 0, v2 = 0;
        if (lane < 4 && k < NB) {
            const unsigned short* xp = p.x + k * DM + col;
            v0 = __ldg(xp) << 16; v1 = __ldg(xp + 16) << 16; v2 = cl & 2 ? 0 : __ldg(xp + 32) << 16;
        }
        uint4 r;
        if (k == 1) mbar_wait(bar_at(B_RK), 0);
        if (k > 1) {
            mbar_wait(bar_at(B_FIN), k & 1);
            r = lds128(SM_FIN + (lane & 1) * 16);
        }
        if (k < NB) {
            const int lg = lane >> 3, ty = (lane & 7) >> 1;
            const char* dst = own + acc_off((k - (lg >> 1)) & 3, lg != 0, cta >> 4) + ty * HALF;
            wait_ns(t0 + batch_ns(k) + CFG(ZTILE) * CFG(TICK0));
            if (lg == 0 || (lg == 1 && (ty < 2 || k == NB - 1)) || (lg == 2 && k > 0 && ty > 1)) {
                st_pkt(dst, v0, v1, v2, ~0u);
                asm volatile("atom.relaxed.gpu.global.exch.b32 %0, [%1+12], %2;" : "=r"(v0) : "l"(dst), "r"(lane < 4 ? 0x3f800000u : 0u) : "memory");
                v0 = ~v0;
            }
            if (__any_sync(0xffffffffu, v0 != 0)) __trap();
            const char* cnt = p.scr + SCR_COUNT;
            if (lane < 2) asm volatile("red.relaxed.gpu.global.add.u32 [%0], 1;" ::"l"(cnt + lane * HALF) : "memory");
            const uint32_t target = ((epoch - 1) * NB + k + 1) * NCTA;
            cnt += near_half();
            SPIN_DECL;
            uint32_t v;
            do {
                __nanosleep(100);
                asm volatile("ld.relaxed.gpu.global.u32 %0, [%1];" : "=r"(v) : "l"(cnt) : "memory");
                SPIN_CHECK(v);
            } while (__any_sync(0xffffffffu, (int)(v - target) < 0));
        }
        __syncwarp();
        if (lane == 0) mbar_arrive(bar_at(B_Z));
        if (k > 1) {
            const int b = k - 2;
            const char* src = own + acc_off(b, 1, cta >> 4) + (2 + ((lane >> 1) & 1)) * HALF;
            unsigned short* o = p.out + b * DM + col + (lane >> 2) * 16;
            const bool on = !(lane & 2) && lane < (cl & 2 ? 8 : 12);
            wait_clk(clk32() + CFG(DLY_F));
            float cnt;
            SPIN_DECL;
            do {
                const uint4 v = ld_pkt(src);
                SPIN_CHECK(k);
                cnt = F(v.w) + shx(F(v.w), 2);
                const float y0 = F(v.x) + shx(F(v.x), 2), y1 = F(v.y) + shx(F(v.y), 2), y2 = F(v.z) + shx(F(v.z), 2);
                const uint32_t x01 = badd2(r.x, badd2(r.y, bmul2(pack2(y0, y1), r.w)));
                const uint32_t x2 = badd2(r.z, badd2(r.z >> 16, bmul2(pack2(y2, 0.f), r.w)));
                if (cnt == NCTA && on) *o = lane < 4 ? x01 : lane < 8 ? x01 >> 16 : x2;
            } while (__any_sync(0xffffffffu, cnt != NCTA));
            TRACES((2 * b + 1) * 6 + 4);
        }
    }
}

__host__ __device__ constexpr uint32_t desc_lo(uint32_t addr) { return ((addr & 0x3FFFFu) >> 4) | (1u << 16); }
constexpr uint32_t DESC_HI_TILE = (3072u >> 4) | (1u << 30);
constexpr uint32_t DESC_HI_VEC = 1u;
template <int TA, int AOFF, int BOFF>
__device__ __forceinline__ void wgmma_n8(float (&d)[4], uint32_t alo, uint32_t blo, int accumulate) {
    asm volatile("{\n.reg .pred p;\n.reg .b32 a, b;\n.reg .b64 da, db;\nsetp.ne.b32 p, %6, 0;\n"
                 "add.u32 a, %4, %8;\nadd.u32 b, %5, %9;\nmov.b64 da, {a, %10};\nmov.b64 db, {b, %11};\n"
                 "wgmma.mma_async.sync.aligned.m64n8k16.f32.bf16.bf16 {%0,%1,%2,%3}, da, db, p, 1, 1, %7, 0;\n}"
                 : "+f"(d[0]), "+f"(d[1]), "+f"(d[2]), "+f"(d[3])
                 : "r"(alo), "r"(blo), "r"(accumulate), "n"(TA), "n"(AOFF >> 4), "n"(BOFF >> 4), "n"(DESC_HI_TILE), "n"(DESC_HI_VEC));
}
template <int KS, int END>
__device__ __forceinline__ void qk_steps(float (&d)[4], uint32_t alo, uint32_t blo) {
    if constexpr (KS < END) {
        wgmma_n8<0, (KS >> 2) * 1024 + (KS & 3) * 32, KS * 32>(d, alo, blo, KS > 0);
        qk_steps<KS + 1, END>(d, alo, blo);
    }
}
__device__ __forceinline__ void pv_steps(float (&e)[3][4], uint32_t alo, uint32_t blo, int acc) {
    wgmma_n8<1, 0, 0>(e[0], alo, blo, acc); wgmma_n8<1, 1024, 0>(e[1], alo, blo, acc); wgmma_n8<1, 2048, 0>(e[2], alo, blo, acc);
    wgmma_n8<1, 6144, 32>(e[0], alo, blo, 1); wgmma_n8<1, 7168, 32>(e[1], alo, blo, 1); wgmma_n8<1, 8192, 32>(e[2], alo, blo, 1);
}
__device__ __forceinline__ void wg_fence() { asm volatile("wgmma.fence.sync.aligned;" ::: "memory"); }
__device__ __forceinline__ void wg_commit() { asm volatile("wgmma.commit_group.sync.aligned;" ::: "memory"); }
template <int N> __device__ __forceinline__ void wg_wait() { asm volatile("wgmma.wait_group.sync.aligned %0;" ::"n"(N) : "memory"); }
__device__ __forceinline__ void acc_ready(float (&d)[4]) { asm volatile("" : "+f"(d[0]), "+f"(d[1]), "+f"(d[2]), "+f"(d[3]) :: "memory"); }
__device__ __forceinline__ uint32_t score_pair(float (&d)[4]) {
    acc_ready(d);
    const uint32_t r = pack2(d[0], d[2]);
    return pack2(bf_lo(r) * SCALE, bf_hi(r) * SCALE);
}

__device__ __forceinline__ void attention_role(const Params& p, int w, int lane) {
    const int cta = cta_id(), t4 = lane & 3, g = lane >> 2;
    mbar_wait(bar_at(B_EP), 0);
    const uint32_t tag0 = lds32(SM_EPOCH) * NB;
    const char* const odst = p.scr + SCR_O + head_off(cta >> 2) + (2 * w + (g >> 2)) * 256 + (cta & 3) * 64 + (g & 3) * 16;
    const uint32_t pdst = SM_P + ((t4 + 3) & 3) * PSTR + (16 * w + g) * 2;
    auto softmax = [&](uint32_t& sc, int ps) -> uint32_t {
        const float s0 = bf_lo(sc), s1 = bf_hi(sc);
        int key = __float_as_int(fmaxf(s0, s1));
        key ^= (key >> 31) & 0x7fffffff;
        key = __reduce_max_sync(0xffffffffu, key);
        sts32(SM_MAX + w * 4, key);
        bar_sync<4, 128>();
        const uint4 mx = lds128(SM_MAX);
        key = max(max((int)mx.x, (int)mx.y), max((int)mx.z, (int)mx.w));
        key ^= (key >> 31) & 0x7fffffff;
        const float mb = __int_as_float(key) * LOG2E;
        const uint32_t pp = pack2(fast_ex2(fmaf(s0, LOG2E, -mb)), fast_ex2(fmaf(s1, LOG2E, -mb)));
        sts16(pdst + ps * 4 * PSTR, pp); sts16(pdst + ps * 4 * PSTR + 16, pp >> 16);
        fence_async();
        bar_sync<4, 128>();
        sc = pp;
        return key;
    };
    auto put_sum = [&](uint32_t pp, int ps) {
        uint32_t fs;
        asm volatile("redux.sync.add.u32 %0, %1, 0xffffffff;" : "=r"(fs) : "r"(__float2uint_rn((bf_lo(pp) + bf_hi(pp)) * 8388608.f)) : "memory");
        sts32(SM_SUM + ps * 16 + w * 4, fs);
    };
    auto aux_word = [&](uint32_t mx, const uint4& u, int k) {
        const float l = __uint2float_rn((u.x + u.y) + (u.z + u.w)) * (1.f / 8388608.f);
        return (g < 4 ? mx : (__float_as_uint(l) + 0x80u) & 0xffffff00u) | ((tag0 + k) & 0x7fu) | 0x80u;
    };
    auto send = [&](float (&e)[3][4], uint32_t aux, int ps) {
        acc_ready(e[0]); acc_ready(e[1]); acc_ready(e[2]);
        const uint32_t o0 = pack2(e[0][0], e[0][2]), o1 = pack2(e[1][0], e[1][2]), o2 = pack2(e[2][0], e[2][2]);
        st_pkt2_if(t4 == 0, odst + ps * 2048, o0, o1, o2, aux);
        mbar_arrive_if(lane == 0, bar_at(ps ? B_RV : B_PS));
    };
    mbar_wait(bar_at(B_QR), 0);
    TRACES(73);
#pragma unroll 1
    for (int it = 0; it <= NB; it++) {
        uint32_t m1 = 0;
        if (it < NB) {
            const uint32_t tab = slots(it);
            const uint32_t ka = SB + (2 * w + ((lane >> 3) & 1)) * 3072 + (lane & 7) * 128 + (((lane >> 4) ^ (lane & 7)) << 4);
            const uint32_t qa = SM_Q + it * 384 + (lane >> 3) * 16;
            uint32_t sc = 0;
#pragma unroll 1
            for (int u = 0; u < 4; u++) {
                const uint32_t base = ka + slot_at(tab, pass_nibble(it, u)) * PAIR;
                mbar_wait(bar_at(B_F1 + 2 * u + (w >> 1)), it & 1);
                float d0[4] = {}, d1[4] = {};
#pragma unroll
                for (int c = 0; c < 6; c++) {
                    uint32_t a0[4], a1[4], b[4];
                    ldsm4(b, qa + c * 64);
                    ldsm4(a0, (base ^ ((c & 1) * 64)) + (c >> 1) * 1024);
                    ldsm4(a1, (base ^ ((c & 1) * 64 + 32)) + (c >> 1) * 1024);
                    mma16816(d0, a0[0], a0[1], a0[2], a0[3], b[0], b[1]);
                    mma16816(d1, a1[0], a1[1], a1[2], a1[3], b[2], b[3]);
                }
                const uint32_t r = pack2(d0[0] + d1[0], d0[2] + d1[2]);
                mbar_arrive_if(lane == 0, bar_at(B_RR + 2 * u + (w >> 1)));
                if (t4 == ((u + 1) & 3)) sc = pack2(bf_lo(r) * SCALE, bf_hi(r) * SCALE);
            }
            m1 = softmax(sc, 0);
            put_sum(sc, 0);
        }
        if (it > 0) {
            const int k = it - 1;
            const uint32_t tab = slots(k);
            const uint32_t v0 = slot_at(tab, k < NB - 1 ? 0 : 4);
            TRACES(48 + k * 6);
            if (k > 0) mbar_wait(bar_at(B_F3), it & 1);
            mbar_wait(bar_at(B_QR), it & 1);
            fence_async();
            TRACES(49 + k * 6);
            float d[4][4] = {};
            const bool busy = k < NB - 1;
#pragma unroll
            for (int u = 0; u < 4; u++) {
                const uint32_t alo = desc_lo(SB) + slot_at(tab, u) * (PAIR >> 4), blo = desc_lo(SM_Q + 4 * 384);
                wg_fence();
                qk_steps<0, 6>(d[u], alo, blo);
                wg_commit();
                if (busy) {
                    wg_wait<1>();
                    if (u > 0) mbar_arrive_if(lane == 0, bar_at(B_RK + u - 1));
                }
                wg_fence();
                qk_steps<6, 12>(d[u], alo, blo);
                wg_commit();
                if (u < 3 && busy) wg_wait<1>();
            }
            wg_wait<2>();
            uint32_t sc = shi(score_pair(d[0]), lane & 28), s = shi(score_pair(d[1]), lane & 28);
            if (t4 == 2) sc = s;
            s = shi(score_pair(d[2]), lane & 28);
            if (t4 == 3) sc = s;
            wg_wait<0>();
            s = score_pair(d[3]);
            if (t4 == 0) sc = s;
            mbar_arrive_if(lane == 0, bar_at(B_RK + 3));
            TRACES(50 + k * 6);
            const uint32_t m2 = softmax(sc, 1);
            TRACES(51 + k * 6);
            float e[3][4] = {};
#pragma unroll
            for (int t = 0; t < 8; t++) {
                const int pr = ((t >> 1) + 1) & 3;
                if (t == 6 && k < NB - 1) mbar_wait(bar_at(B_FL), k & 1);
                wg_fence();
                pv_steps(e, desc_lo(SB + (t & 1) * TILE) + (pr ? slot_at(tab, 4 + pr) : v0) * (PAIR >> 4), desc_lo(SM_P + (4 + pr) * PSTR + (t & 1) * 64), t > 0);
                wg_commit();
                if (t < 7 && busy) wg_wait<1>();
                if (t == 1) put_sum(sc, 1);
            }
            bar_sync<4, 128>();
            const uint32_t aux = opaque(aux_word(m2, lds128(SM_SUM + 16), k));
            wg_wait<0>();
            send(e, aux, 1);
            TRACES(52 + k * 6);
        }
        if (it < NB) {
            const uint32_t tab = slots(it);
            if (it == 0) st_pkt2_if(t4 == 0, odst, 0, 0, 0, 0);
            bar_sync<4, 128>();
            const uint32_t aux = opaque(aux_word(m1, lds128(SM_SUM), it));
            float e[3][4] = {};
#pragma unroll 1
            for (int u = 0; u < 4; u++) {
                const uint32_t alo = desc_lo(SB) + slot_at(tab, 4 + u) * (PAIR >> 4), blo = desc_lo(SM_P) + u * (PSTR >> 4);
                mbar_wait(bar_at(B_F1 + 8 + 2 * u), it & 1);
                wg_fence();
                pv_steps(e, alo, blo, u > 0);
                wg_commit();
                wg_wait<1>();
                if (u == 1) mbar_arrive_if(lane == 0, bar_at(B_RP));
                mbar_wait(bar_at(B_F1 + 9 + 2 * u), it & 1);
                wg_fence();
                pv_steps(e, alo + (TILE >> 4), blo + 4, 1);
                wg_commit();
                wg_wait<1>();
            }
            wg_wait<0>();
            send(e, aux, 0);
            TRACES(53 + it * 6);
        }
    }
}

__device__ __forceinline__ void ln_finish(float s, float q, float& mean_b, float& rden) {
    const float mean = s * (1.f / DM);
    const float var = fmaxf(fmaf(q, 1.f / DM, -mean * mean), 0.f);
    mean_b = bfr(mean);
    rden = fast_rcp(bfr(fast_sqrt(bfr(bfr(var) + 1e-5f))));
}
__device__ __forceinline__ uint32_t ln_apply(uint32_t w, float mean_b, float rden) {
    const uint32_t d = bsub2(w, __byte_perm(__float_as_uint(mean_b), 0, 0x3232));
    return pack2(bf_lo(d) * rden, bf_hi(d) * rden);
}
__device__ __forceinline__ void put_x(uint32_t x01, uint32_t x2, uint32_t wa, bool e2) {
    jitter();
    sts16(wa, x01); sts16(wa + 8, x01 >> 16);
    sts16_if(!e2, wa + 16, x2);
}
__device__ __forceinline__ void get_x(uint32_t (&b)[10], uint32_t ra) {
    __syncwarp();
    const uint4 u = lds128(ra), v = lds128(ra + 16);
    const uint2 z = lds64(ra + 32);
    b[0] = u.x; b[1] = u.y; b[2] = u.z; b[3] = u.w; b[4] = v.x; b[5] = v.y; b[6] = v.z; b[7] = v.w; b[8] = z.x; b[9] = z.y;
}
__device__ __forceinline__ float fold(float a, float b, bool sel, int m) { return (sel ? b : a) + shx(sel ? a : b, m); }

__device__ __forceinline__ void chain_role(const Params& p, int w, int lane) {
    const int cta = cta_id(), h = cta >> 2, s = cta & 3;
    const int g = lane >> 2, t4 = lane & 3;
    const bool e1 = t4 & 1, e2 = t4 & 2;
    uint32_t wq[5][3][4], wo[3][5][4], wg[5][4], wh[5][2], wd[4][4];
    const int col0 = 80 * w + (e2 ? 48 : 0) + g + (e1 ? 8 : 0);
    const uint32_t xw = opaque(SM_X + w * 384 + 48 * (g >> 1) + (e2 ? 24 : 0) + (e1 ? 4 : 0) + 2 * (g & 1));
    const uint32_t xr = opaque(g == 1 ? SM_ONES : SM_X + w * 384 + (g == 3 ? 192 : 0) + 48 * t4);
    TRACES(75);
    sts32_if(lane < 12, SM_ONES + lane * 4, 0x3f803f80u);
    uint32_t zero = lane >> 5;
    const int mi = lane >> 3, mr = lane & 7;
    mbar_wait(bar_at(B_W), 0);
    TRACES(74);
    sts16(xw + 192, lds16(ST_X + 5120 + col0 * 2)); sts16(xw + 200, lds16(ST_X + 5120 + col0 * 2 + 32));
    sts16_if(!e2, xw + 208, lds16(ST_X + 5120 + col0 * 2 + 64));
#pragma unroll
    for (int i = 0; i < 5; i++)
#pragma unroll
        for (int mt = 0; mt < 3; mt++) ldsm4t(wq[i][mt], ST_WQ + (80 * w + 16 * i + mr + 8 * (mi >> 1)) * 96 + 32 * mt + 16 * (mi & 1), zero);
    const bool odd = cta & 1;
    const uint32_t lo = ST_WD + (mr + (odd ? 4 : 0)) * 1280 + 160 * w + 16 * (mi & 1);
    const uint32_t hi = ST_WD + ((mr & 3) + (odd ? 0 : 8)) * 1280 + 160 * w + 16 * (mi & 1);
    ldsm4t(wd[0], lo + 96 * (mi >> 1), zero);
    ldsm4t(wd[1], lo + 96 * (mi >> 1) + 32, zero);
    ldsm4t(wd[2], (mi < 2 ? lo : hi) + 64, zero);
    ldsm4t(wd[3], hi + 32 * (mi >> 1) + 96 * (mr >> 2), zero);
    fence_async();
    __syncwarp();
    mbar_arrive_if(lane == 0, bar_at(B_WC));
    mbar_wait(bar_at(B_EP), 0);
    const uint32_t near = __shfl_sync(0xffffffffu, near_half(), 0);
    uint32_t x01 = 0, x2 = 0, nx01 = 0, nx2 = 0;
#pragma unroll 1
    for (int n = -5; n < NROUND; n++) {
        const bool last = (ORD_LAST >> (n & 15)) & 1, head = !((ORD_NO_HEAD >> (n & 15)) & 1);
        const int k = (ORD_BATCH >> (2 * (n & 15))) & 3;
        if (n > -5 && n <= 0) bar_sync<7, 288>();
        else if (!last) bar_sync<2, 256>();
        TRACES(n <= 0 ? 83 + n : 95);
        const char* const slice = p.scr + acc_off(k, last, w);
        const char* const cell = opaque(slice + g * 256 + t4 * 16);
        if (n < -1) {
            const uint32_t xa = ST_X + (n + 5) * 1280, ln = opaque(lane);
            const int col0 = 80 * w + (ln & 2 ? 48 : 0) + (ln >> 2) + (ln & 1 ? 8 : 0);
            float sm = 0.f, sq = 0.f;
#pragma unroll
            for (int i = 0; i < 5; i++) {
                const uint2 c = lds64(xa + i * 256 + ln * 8);
                sm += (bf_lo(c.x) + bf_hi(c.x)) + (bf_lo(c.y) + bf_hi(c.y));
                sq = fmaf(bf_lo(c.x), bf_lo(c.x), fmaf(bf_hi(c.x), bf_hi(c.x), fmaf(bf_lo(c.y), bf_lo(c.y), fmaf(bf_hi(c.y), bf_hi(c.y), sq))));
            }
            x01 = lds16(xa + col0 * 2) | lds16(xa + col0 * 2 + 32) << 16;
            x2 = lds16(xa + col0 * 2 + 64);
#pragma unroll
            for (int o = 16; o; o >>= 1) { sm += shx(sm, o); sq += shx(sq, o); }
            float mean_b, rden;
            ln_finish(sm, sq, mean_b, rden);
            x01 = ln_apply(x01, mean_b, rden);
            x2 = ln_apply(x2, mean_b, rden);
            put_x(x01, x2, xw, e2);
        } else {
            if (n >= 0 && head) {
                if (!last || n == NROUND - 1) mbar_wait(bar_at(B_Z), (k + last) & 1);
                const char* src = p.scr + SCR_O + head_off(h) + head_near(h, near) + last * 2048 + (w & 6) * 256 + (lane & 15) * 16;
                const uint32_t tag = (lds32(SM_EPOCH) * NB + k) | 0x80u;
                mbar_wait(bar_at(last ? B_RV : B_PS), k & 1);
                uint4 v, z;
                {
                    SPIN_DECL;
                    do {
                        v = ld_pkt(src); z = ld_pkt(src + 256);
                        SPIN_CHECK(n);
                    } while (__any_sync(0xffffffffu, (((v.w ^ tag) | (z.w ^ tag)) & 0xffu) != 0));
                }
                TRACES(tr + 0);
                float a[3][4] = {};
                const uint32_t bb[3][2] = {{v.x, v.y}, {z.x, z.y}, {v.z, z.z}};
                float sa, sb, rl;
#pragma unroll
                for (int i = 0; i < 3; i++) {
                    const uint32_t l0 = g < 4 ? bb[i][0] : 0, l1 = g < 4 ? bb[i][1] : 0, h0 = g < 4 ? 0 : bb[i][0], h1 = g < 4 ? 0 : bb[i][1];
#pragma unroll
                    for (int mt = 0; mt < 5; mt++)
                        mma16816(a[mt % 3], wo[i][mt][0], wo[i][mt][1], wo[i][mt][2], wo[i][mt][3], mt < 3 ? l0 : h0, mt < 3 ? l1 : h1);
                    if (i == 0) {
                        int key = v.w & 0xffffff00u;
                        key ^= (key >> 31) & 0x7fffffff;
                        key = __reduce_max_sync(0xffffffffu, key);
                        key ^= (key >> 31) & 0x7fffffff;
                        const float ws = fast_ex2((F(v.w & 0xffffff00u) - __int_as_float(key)) * LOG2E);
                        sa = shi(ws, e1 ? 8 : 0); sb = shi(ws, e1 ? 12 : 4);
                        rl = ws * F(z.w & 0xffffff00u);
                        rl += shx(rl, 4);
                    }
                    if (i == 1) rl += shx(rl, 8);
                }
                float y[3];
#pragma unroll
                for (int j = 2; j < 5; j++) {
                    const int mt = j % 3;
                    y[mt] = fold(fmaf(a[mt][0], sa, a[mt][1] * sb), fmaf(a[mt][2], sa, a[mt][3] * sb), e1, 1);
                }
                const uint32_t pa = SM_PO + w * 512 + lane * 16;
                if (w < 2) {
                    const char* dst = opaque(cell + s * 16384);
                    rl = fast_rcp(rl);
                    bar_sync<1, 256>();
                    const uint4 c1 = lds128(pa), c2 = lds128(pa + 1024), c3 = lds128(pa + 2048);
                    red_cell2_if(true, dst, ((y[0] + F(c1.x)) + (F(c2.x) + F(c3.x))) * rl, ((y[1] + F(c1.y)) + (F(c2.y) + F(c3.y))) * rl,
                                 ((y[2] + F(c1.z)) + (F(c2.z) + F(c3.z))) * rl);
                } else {
                    stsf4(pa - 1024, y[0], y[1], y[2], 0.f);
                    bar_sync<1, 256>();
                }
                TRACES(tr + 1);
                if ((ORD_NO_TAIL >> n) & 1) continue;
                const uint32_t tsend = clk32();
                if (n == 0) {
                    st_pkt2_if(lane < 4, p.scr + SCR_O + head_off(h) + 2048 + w * 256 + s * 64 + lane * 16, 0, 0, 0, 0);
                    __syncwarp();
                } else if (!last) {
                    const char* nsrc = p.scr + acc_off(k - 1, 1, w) + near + g * 256 + t4 * 16;
                    SPIN_DECL;
                    do {
                        v = ld_pkt(nsrc);
                        SPIN_CHECK(n);
                        nx01 = pack2(F(v.x), F(v.y)); nx2 = pack2(F(v.z), 0.f);
                    } while (__any_sync(0xffffffffu, v.w != FULL_A));
                }
                wait_clk(tsend + (w < 2 ? 0 : 60) + (n < QUIET ? CFG(DLY_AL) : CFG(DLY_A)));
                {
                    SPIN_DECL;
                    do {
                        v = ld_pkt(cell + near);
                        SPIN_CHECK(n);
                        x01 = pack2(F(v.x), F(v.y));
                        x2 = pack2(F(v.z), 0.f);
                        put_x(x01, x2, xw, e2);
                    } while (__any_sync(0xffffffffu, v.w != FULL_A));
                }
                TRACES(tr + 2);
            } else if (n >= 0) {
                x01 = nx01; x2 = nx2;
                put_x(x01, x2, xw, e2);
            } else {
                mbar_wait(bar_at(B_W + 1), 0);
                const uint32_t ln = opaque(lane);
                const int mi = ln >> 3, mr = ln & 7;
                uint32_t zero = ln >> 5;
                TRACES(76);
#pragma unroll
                for (int i = 0; i < 3; i++) {
                    const int d = 16 * (w >> 1) + (mr >> 1) + 8 * (mr & 1) + (i < 2 ? 64 * (mi >> 1) + 4 * i : 128 + 4 * (mi >> 1));
#pragma unroll
                    for (int mt = 0; mt < 5; mt++) ldsm4t(wo[i][mt], ST_WO + d * 320 + 160 * (w & 1) + 32 * mt + 16 * (mi & 1), zero);
                }
                fence_async();
                __syncwarp();
                mbar_arrive_if(lane == 0, bar_at(B_WC + 1));
                mbar_wait(bar_at(B_W + 2), 0);
                TRACES(77);
#pragma unroll
                for (int i = 0; i < 5; i++) {
                    const uint32_t ga = ST_WG + (mi & 1) * 20480 + (80 * w + 16 * i + mr + 8 * (mi >> 1)) * 32;
                    uint32_t r[4];
                    ldsm4t(wg[i], ga + (odd ? 16 : 0), zero);
                    ldsm4t(r, ga + (odd ? 0 : 16), zero);
#pragma unroll
                    for (int kh = 0; kh < 2; kh++) {
                        const uint32_t moved = __shfl_xor_sync(0xffffffffu, odd ? r[2 * kh] : r[2 * kh + 1], 16);
                        wh[i][kh] = (g < 4) == odd ? moved : odd ? r[2 * kh + 1] : r[2 * kh];
                    }
                }
                fence_async();
                __syncwarp();
                mbar_arrive_if(lane == 0, bar_at(B_WC + 2));
                TRACES(72);
                x01 = 0x3f803f80u; x2 = 0x3f80u;
                put_x(x01, x2, xw, e2);
            }
            uint32_t b[10];
            get_x(b, xr);
            float a[2][4] = {};
#pragma unroll
            for (int i = 0; i < 5; i++) {
                mma16816(a[0], wg[i][0], wg[i][1], wg[i][2], wg[i][3], b[2 * i], b[2 * i + 1]);
                mma16816(a[1], wh[i][0], b[2 * i], wh[i][1], b[2 * i + 1], b[2 * i], b[2 * i + 1]);
            }
            stsf(SM_PG + (w >> 2) * 512 + (g + 8 * t4) * 16 + (w & 3) * 4, e2 ? (e1 ? a[1][2] : a[1][0]) : (e1 ? a[0][2] : a[0][0]));
            const uint2 cs = lds64(SM_CSG + lane * 48);
            const char* dst = opaque(cell + 3 * HALF - near);
            bar_sync<2, 256>();
            const float S = sum8(lds128(SM_PG + lane * 16), lds128(SM_PG + 512 + lane * 16));
            const float sx = shi(S, 25), sq = shi(S, 24), Su = shi(S, lane + (lane < 16 ? 8 : 4));
            if (n < 0) {
                if (w == 0) stsf2(SM_CSG + lane * 48, S, Su);
            } else {
                float mean_b, rden;
                ln_fast(sx, sq, mean_b, rden);
                const float gv = bfr(fmaf(-mean_b, F(cs.x), S) * rden), uv = bfr(fmaf(-mean_b, F(cs.y), Su) * rden);
                const float sg = fast_rcp(1.f + fast_ex2(-LOG2E * gv));
                const uint32_t hb = pack2(bfr(gv * sg) * uv, 0.f);
                const uint32_t b0 = __byte_perm(shi(hb, 2 * t4), shi(hb, 2 * t4 + 1), 0x5410);
                const uint32_t b1 = __byte_perm(shi(hb, e1 ? 18 : 16), shi(hb, e1 ? 19 : 17), 0x5410);
                const bool up = g >= 4;
                const uint32_t l0 = up ? 0 : b0, h0 = up ? b0 : 0;
                const uint32_t m1 = up == e2 ? b1 : 0;
                float d[3][4] = {};
                mma16816(d[0], wd[0][0], wd[0][1], wd[0][2], wd[0][3], l0, h0);
                mma16816(d[1], wd[1][0], wd[1][1], wd[1][2], wd[1][3], l0, h0);
                mma16816(d[2], wd[2][0], wd[2][1], wd[2][2], wd[2][3], l0, up ? 0 : m1);
                mma1688(d[0], wd[3][0], wd[3][1], m1);
                mma1688(d[1], wd[3][2], wd[3][3], m1);
                red_cell(dst, e1 ? d[0][2] : d[0][0], e1 ? d[1][2] : d[1][0], e1 ? d[2][2] : d[2][0]);
                const uint32_t tsend = clk32();
                TRACES(tr + 3);
                if (last && w != cta >> 4) continue;
                const float sgr = shi(sg, 27);
                const uint32_t sg2 = pack2(sgr, sgr);
                const uint32_t n01 = opaque(pack2((bf_lo(x01) - mean_b) * rden, (bf_hi(x01) - mean_b) * rden));
                const uint32_t n2 = opaque(pack2((bf_lo(x2) - mean_b) * rden, 0.f));
                if (last) {
                    sts128_if(lane >> 1 == (cta & 15), SM_FIN + (lane & 1) * 16, x01, n01, __byte_perm(x2, n2, 0x5410), sg2);
                    mbar_arrive_if(lane >> 1 == (cta & 15), bar_at(B_FIN));
                    __syncwarp();
                    continue;
                }
                wait_clk(tsend + (n < QUIET ? CFG(DLY_BL) : CFG(DLY_B)));
                const uint32_t r01 = x01, r2 = x2;
                float cnt;
                SPIN_DECL;
                do {
                    const uint4 v = ld_pkt(cell + 2 * HALF), z = ld_pkt(cell + 3 * HALF);
                    SPIN_CHECK(n);
                    cnt = F(v.w) + F(z.w);
                    x01 = badd2(r01, badd2(n01, bmul2(pack2(F(v.x) + F(z.x), F(v.y) + F(z.y)), sg2)));
                    x2 = badd2(r2, badd2(n2, bmul2(pack2(F(v.z) + F(z.z), 0.f), sg2)));
                    put_x(x01, x2, xw, e2);
                } while (__any_sync(0xffffffffu, cnt != NCTA));
                TRACES(tr + 4);
            }
        }
        {
            uint32_t b[10];
            get_x(b, xr);
            float a[3][4] = {};
            const float f0 = bf_lo(x01), f1 = bf_hi(x01), f2 = e2 ? 0.f : bf_lo(x2);
            float st;
#pragma unroll
            for (int i = 0; i < 5; i++) {
#pragma unroll
                for (int mt = 0; mt < 3; mt++) {
                    mma16816(a[mt], wq[i][mt][0], wq[i][mt][1], wq[i][mt][2], wq[i][mt][3], b[2 * i], b[2 * i + 1]);
                    if (i == 0 && mt == 0) st = fold(fmaf(f0, f0, fmaf(f1, f1, f2 * f2)), (f0 + f1) + f2, g & 1, 4);
                }
                if (i < 4) st += shx(st, i < 2 ? 1 << i : 2 << i);
            }
            const uint32_t pa = SM_PQ + (w >> 2) * 1024 + (g & 1) * 512 + ((e2 ? 16 : 0) + (e1 ? 4 : 0) + (g >> 1)) * 16 + (w & 3) * 4;
            stsf(pa + 128, e2 ? st : e1 ? a[1][2] : a[1][0]);
            stsf(pa, e2 ? (e1 ? a[2][2] : a[2][0]) : (e1 ? a[0][2] : a[0][0]));
            bar_sync<3, 288>();
            if (n >= 0 && w == cta >> 4) {
                red_cell2_if(lane >> 1 == (cta & 15), cell + (acc_off(k, 1, 0) - acc_off(k, 0, 0)), f0, f1, f2);
                __syncwarp();
            }
        }
    }
}

__host__ __device__ constexpr int bar_count(int i) {
    return i < 16 ? 1 : i < B_RR ? 0 : i < B_RK ? 2 : i <= B_RV ? 4 : i == B_Z ? 1 : i == B_EP ? 9 : i < B_WC ? 0 : i < B_FIN ? 8 :
           i == B_FIN ? 2 : i == B_PS || i == B_RP ? 4 : i == B_QR ? 32 : 1;
}
template <int I, int END> __device__ __forceinline__ void init_bars() {
    if constexpr (I < END) {
        if (bar_count(I)) mbar_init(bar_at(I), bar_count(I));
        init_bars<I + 1, END>();
    }
}
template <int ID> __device__ __forceinline__ void role_exit() { asm volatile("exit; // %0" ::"n"(ID)); }
constexpr int NTHREADS = 512;
#define STR2(x) #x
#define STR(x) STR2(x)
__global__ void __launch_bounds__(NTHREADS, 1)
decode_kernel(const Params p, const __grid_constant__ Maps tm) {
    extern __shared__ __align__(1024) unsigned char smem[];
    if (threadIdx.x == 0) l2_prefetch(p.wq + (size_t)blockIdx.x * 12288, 12288);
    const uint32_t t0 = now_ns() - CFG(LEAD);
    const int lane = threadIdx.x & 31;
    const int warp = __reduce_max_sync(0xffffffffu, threadIdx.x >> 5);
    if (warp < 8) {
        asm volatile("setmaxnreg.inc.sync.aligned.u32 " STR(CFG_REG_CHAIN) ";");
        bar_arrive<5, 480>();
        const uint32_t vote = probe_near(p, warp, lane);
        bar_sync<2, 256 + 32>();
        sts32(SM_NEAR + warp * 4, vote);
        mbar_arrive_if(lane == 0, bar_at(B_EP));
        chain_role(p, warp, __shfl_sync(0xffffffffu, lane, lane));
        role_exit<3>();
    } else if (warp < 12) {
        asm volatile("setmaxnreg.dec.sync.aligned.u32 " STR(CFG_REG_ATT) ";");
        if (elect_one()) {
            if (warp == 8) init_bars<0, 12>();
            else if (warp == 9) init_bars<12, 30>();
            else if (warp == 10) init_bars<30, 42>();
            else init_bars<42, NBAR>();
            asm volatile("fence.mbarrier_init.release.cluster;" ::: "memory");
            fence_async();
        }
        if (warp == 8) TRACE(236);
        bar_sync<5, 480>();
        if (warp == 8) TRACE(237);
        attention_role(p, warp - 8, lane);
        role_exit<2>();
    } else {
        asm volatile("setmaxnreg.dec.sync.aligned.u32 " STR(CFG_REG_HELP) ";");
        if (warp == 12) {
            load_role(p, &tm.k, lane, t0);
            role_exit<0>();
        } else {
            if (warp == 14) {
                if (smem_u32(smem) != SB) __trap();
                if (elect_one()) {
                    asm volatile("prefetch.tensormap [%0];" ::"l"(&tm.q) : "memory");
                    mbar_init(bar_at(B_W), 1); mbar_init(bar_at(B_W + 1), 1); mbar_init(bar_at(B_W + 2), 1);
                    asm volatile("fence.mbarrier_init.release.cluster;" ::: "memory");
                    fence_async();
                    mbar_expect_tx(bar_at(B_W), 61440 + 15360 + 6400); mbar_expect_tx(bar_at(B_W + 1), 61440); mbar_expect_tx(bar_at(B_W + 2), 40960);
                    bulk_load(ST_X, p.x, 5120, bar_at(B_W));
                    bulk_load(ST_X + 5120, p.wr, 1280, bar_at(B_W));
                }
                TRACE(238);
                reload_role(p, &tm, t0);
            } else {
                if (warp == 13 && elect_one()) {
                    asm volatile("prefetch.tensormap [%0];" ::"l"(&tm.g) : "memory");
                    asm volatile("prefetch.tensormap [%0];" ::"l"(&tm.u) : "memory");
                    asm volatile("prefetch.tensormap [%0];" ::"l"(&tm.o) : "memory");
                    asm volatile("prefetch.tensormap [%0];" ::"l"(&tm.k) : "memory");
                    asm volatile("prefetch.tensormap [%0];" ::"l"(&tm.v) : "memory");
                }
                TRACE(233 + warp);
                bar_sync<5, 480>();
                if (warp == 13) { bar_arrive<6, 64>(); q_role(p, lane); }
                else { bar_arrive<2, 256 + 32>(); zero_role(p, lane, t0); }
            }
            role_exit<1>();
        }
    }
}

typedef CUresult (*EncodeFn)(CUtensorMap*, CUtensorMapDataType, cuuint32_t, void*, const cuuint64_t*, const cuuint64_t*,
                             const cuuint32_t*, const cuuint32_t*, CUtensorMapInterleave, CUtensorMapSwizzle,
                             CUtensorMapL2promotion, CUtensorMapFloatOOBfill);

bool make_map(EncodeFn fn, CUtensorMap* m, const void* ptr, uint64_t cols, uint64_t rows, uint32_t bc, uint32_t br) {
    cuuint64_t dims[2] = {cols, rows};
    cuuint64_t strides[1] = {cols * 2};
    cuuint32_t box[2] = {bc, br};
    cuuint32_t es[2] = {1, 1};
    return fn(m, CU_TENSOR_MAP_DATA_TYPE_BFLOAT16, 2, const_cast<void*>(ptr), dims, strides, box, es, CU_TENSOR_MAP_INTERLEAVE_NONE,
              CU_TENSOR_MAP_SWIZZLE_NONE, CU_TENSOR_MAP_L2_PROMOTION_L2_128B, CU_TENSOR_MAP_FLOAT_OOB_FILL_NONE) == CUDA_SUCCESS;
}

bool make_kv_map(EncodeFn fn, CUtensorMap* m, const void* ptr) {
    cuuint64_t dims[4] = {64, 8, 3, (cuuint64_t)NB * NHEAD * SK / 8};
    cuuint64_t strides[3] = {DH * 2, 128, 8 * DH * 2};
    cuuint32_t box[4] = {64, 8, 3, 4};
    cuuint32_t es[4] = {1, 1, 1, 1};
    return fn(m, CU_TENSOR_MAP_DATA_TYPE_BFLOAT16, 4, const_cast<void*>(ptr), dims, strides, box, es, CU_TENSOR_MAP_INTERLEAVE_NONE,
              CU_TENSOR_MAP_SWIZZLE_128B, CU_TENSOR_MAP_L2_PROMOTION_L2_128B, CU_TENSOR_MAP_FLOAT_OOB_FILL_NONE) == CUDA_SUCCESS;
}

}

extern "C" void kernel_launch(void* const* d_in, const int* in_sizes, int n_in, void* d_out, int out_size) {
    (void)in_sizes; (void)n_in; (void)out_size;
    static EncodeFn fn = nullptr;
    static const char* scr = nullptr;
    if (!fn) {
        void* f = nullptr;
        cudaDriverEntryPointQueryResult qr;
        if (cudaGetDriverEntryPoint("cuTensorMapEncodeTiled", &f, cudaEnableDefault, &qr) != cudaSuccess || !f) return;
        void* sp = nullptr;
        if (cudaGetSymbolAddress(&sp, g_scratch) != cudaSuccess) return;
        scr = (const char*)(((uintptr_t)sp + (2 << 20) - 1) & ~(uintptr_t)((2 << 20) - 1));
        fn = (EncodeFn)f;
        cudaFuncSetAttribute(decode_kernel, cudaFuncAttributeMaxDynamicSharedMemorySize, SMEM_BYTES);
    }
    Maps tm;
    if (!make_kv_map(fn, &tm.k, d_in[1]) || !make_kv_map(fn, &tm.v, d_in[2])) return;
    if (!make_map(fn, &tm.q, d_in[3], NHEAD * DH, DM, 48, 128) || !make_map(fn, &tm.o, d_in[4], DM, NHEAD * DH, 160, 32)) return;
    if (!make_map(fn, &tm.g, d_in[7], FF, DM, 16, 128) || !make_map(fn, &tm.u, d_in[8], FF, DM, 16, 128)) return;
    Params p;
    p.x = (const unsigned short*)d_in[0];
    p.wq = (const char*)d_in[3];
    p.wo = (const char*)d_in[4];
    p.wr = (const unsigned short*)d_in[6];
    p.wg = (const char*)d_in[7];
    p.wu = (const char*)d_in[8];
    p.wd = (const char*)d_in[9];
    p.out = (unsigned short*)d_out;
    p.scr = scr;
    decode_kernel<<<NCTA, NTHREADS, SMEM_BYTES>>>(p, tm);
}
```

```cpp
#include <cuda_runtime.h>
#include <cuda_bf16.h>
#include <cuda.h>
#include <stdint.h>

namespace {

constexpr int NB = 4, DM = 640, NHEAD = 32, DH = 192, SK = 4096, WIN = 1024, FF = 1536;
constexpr int NCTA = 128;
constexpr int TILE = 12288, PAIR = 2 * TILE;

#define CFG_LIST(X) \
    X(TICK0, 479)        \
    X(TICK, 495)        \
    X(LEAD, 600)        \
    X(STAG, 500)        \
    X(WLAG, 350)        \
    X(GSTEP, 750)        \
    X(WIN, 5)        \
    X(PMAX, 2)        \
    X(PGRACE, 50)        \
    X(LMAX0, 150)        \
    X(LMAX, 160) \
    X(GAIN, 5)        \
    X(VSTEP, 150)        \
    X(RSTEP, 670)        \
    X(RSTEP3, 450) \
    X(ZTILE, 11)        \
    X(DLY_A, 410)        \
    X(DLY_AL, 100) \
    X(DLY_B, 570) \
    X(DLY_BL, 950) \
    X(DLY_F, 290) \
    X(MAP, 2) \
    X(ILV, 1) \
    X(ROT, 5) \
    X(LW, 3) \
    X(UP, 0) \
    X(JL0, 8) \
    X(MUL, 0) \
    X(BYC, 0) \
    X(PERM, 13) \
    X(FLIP, 0) \

#define X(n, v) constexpr int CFG_##n = v;
CFG_LIST(X)
#undef X
#define CFG(n) CFG_##n
constexpr int QUIET = 8;
#define CFG_REG_CHAIN 216
#define CFG_REG_ATT 48
#define CFG_REG_HELP 32
__device__ __forceinline__ int cta_id() {
    const int b = blockIdx.x;
    return CFG(MAP) == 0 ? b : CFG(MAP) == 1 ? (b & 31) << 2 | b >> 5 : CFG(MAP) == 2 ? (b & 1) << 6 | b >> 1 : ((b >> 1) & 31) << 2 | (b >> 6) << 1 | (b & 1);
}
constexpr int KB_KV0 = 165;
__device__ __forceinline__ int kb_ns(int kb) { return kb * CFG(TICK0) / 12; }
__device__ __forceinline__ int tick_ns(int j) { return j <= 16 ? CFG(TICK0) : CFG(TICK); }
__device__ __forceinline__ int batch_ns(int k) { return kb_ns(KB_KV0) + (k ? 16 * (CFG(TICK0) + (k - 1) * CFG(TICK)) : 0); }

__device__ __forceinline__ uint32_t slots(int k) { return k & 2 ? (k & 1 ? 0x21304768u : 0x76835214u) : (k & 1 ? 0x21480765u : 0x76543210u); }
__device__ __forceinline__ int pass_nibble(int k, int u) { return k > 0 ? 4 + (u & 1) : u; }
__device__ __forceinline__ uint32_t slot_at(uint32_t tab, int u) { return (tab >> (4 * u)) & 15; }

constexpr int NROUND = 11;
constexpr uint32_t ORD_BATCH = 0x3b9910, ORD_LAST = 0x6da, ORD_NO_HEAD = 0x248, ORD_NO_TAIL = 0x092;

constexpr uint32_t SB = 1024;
constexpr uint32_t SM_BAR = SB + 9 * PAIR;
constexpr int B_F1 = 0;
constexpr int B_RR = 24;
constexpr int B_RK = 32;
constexpr int B_RV = 36;
constexpr int B_Z = 37;
constexpr int B_EP = 38;
constexpr int B_W = 39;
constexpr int B_WC = 42;
constexpr int B_FIN = 45;
constexpr int B_F3 = 46;
constexpr int B_PS = 48;
constexpr int B_RP = 49;
constexpr int B_FL = 50;
constexpr int B_QR = 51;
constexpr int NBAR = 52;
__host__ __device__ constexpr uint32_t bar_at(int i) { return SM_BAR + 8 * i; }
constexpr uint32_t SM_EPOCH = SM_BAR + 416;
constexpr uint32_t SM_MAX = SM_EPOCH + 16;
constexpr uint32_t SM_SUM = SM_MAX + 16;
constexpr uint32_t SM_NEAR = SM_SUM + 32;
constexpr uint32_t SM_FIN = SM_NEAR + 32;
constexpr uint32_t SM_Q = SM_FIN + 32;
constexpr uint32_t PSTR = 144;
constexpr uint32_t SM_P = SM_Q + 5 * 384;
constexpr uint32_t SM_X = SM_P + 8 * PSTR;
constexpr uint32_t SM_CSG = SM_X + 40;
constexpr uint32_t SM_ONES = SM_X + 8 * 384;
constexpr uint32_t SM_PG = SM_ONES + 48;
constexpr uint32_t SM_PO = SM_PG + 1024;
constexpr uint32_t SM_PQ = SM_PO;
constexpr int SMEM_BYTES = SM_PO + 3072 - SB;
static_assert(SMEM_BYTES <= 232448 && SM_Q % 16 == 0 && SM_P % 16 == 0 && SM_X % 16 == 0 && SM_PO % 16 == 0, "smem");
constexpr uint32_t ST_WQ = SB, ST_WD = SB + 3 * PAIR, ST_WO = SB + 4 * PAIR, ST_WG = SB + 7 * PAIR, ST_X = ST_WG + 40960;

__device__ unsigned g_epoch;
__device__ unsigned char g_scratch[4 << 20];
constexpr uint32_t HALF = 4096, SCR_O = 1 << 16, SCR_Q = 1 << 17, SCR_COUNT = 3 << 16;
__device__ __forceinline__ uint32_t acc_off(int k, int layer, int w) {
    return (k & 1) << 6 | layer << 7 | (w & 1) << 11 | (w >> 1) << 14 | (k + layer == NB) << 18;
}
__device__ __forceinline__ uint32_t head_off(int h) { return (h & 3) << 14 | (h & 4) << 16 | (h & 8) << 17 | (h & 16) << 9; }
__device__ __forceinline__ uint32_t head_near(int h, uint32_t near) { return near ^ HALF ^ (h & 16) << 8; }
constexpr uint32_t FULL_A = 0x42040000u;

struct Params {
    const char* wq;
    const unsigned short* x;
    const char* wo;
    const unsigned short* wr;
    const char* wg;
    const char* wu;
    const char* wd;
    unsigned short* out;
    const char* scr;
};

__device__ __forceinline__ uint32_t smem_u32(const void* p) { return (uint32_t)__cvta_generic_to_shared(p); }
__device__ __forceinline__ void mbar_init(uint32_t a, uint32_t c) { asm volatile("mbarrier.init.shared::cta.b64 [%0], %1;" ::"r"(a), "r"(c) : "memory"); }
__device__ __forceinline__ void mbar_expect_tx(uint32_t a, uint32_t b) {
    asm volatile("mbarrier.arrive.expect_tx.shared::cta.b64 _, [%0], %1;" ::"r"(a), "r"(b) : "memory");
}
__device__ __forceinline__ void mbar_arrive(uint32_t a) { asm volatile("mbarrier.arrive.shared::cta.b64 _, [%0];" ::"r"(a) : "memory"); }
constexpr uint32_t SPIN_LIMIT = 1u << 22;
#define SPIN_DECL uint32_t spins = 0
#define SPIN_CHECK(info) { if (++spins > SPIN_LIMIT) __trap(); }
__device__ __forceinline__ void jitter() {}
__device__ __forceinline__ void mbar_wait(uint32_t a, uint32_t parity) {
    jitter();
    uint32_t ok;
    SPIN_DECL;
    while (true) {
        asm volatile("{\n.reg .pred p;\nmbarrier.try_wait.parity.shared::cta.b64 p, [%1], %2;\nselp.u32 %0, 1, 0, p;\n}"
                     : "=r"(ok) : "r"(a), "r"(parity) : "memory");
        if (ok) break;
        SPIN_CHECK((a - SM_BAR) / 8 * 10 + parity);
    }
    jitter();
}
__device__ __forceinline__ bool mbar_test2(uint32_t a, uint32_t pa, uint32_t b, uint32_t pb) {
    uint32_t ok;
    asm volatile("{\n.reg .pred p, q;\nmbarrier.test_wait.parity.shared::cta.b64 p, [%1], %2;\n"
                 "mbarrier.test_wait.parity.shared::cta.b64 q, [%3], %4;\nand.pred p, p, q;\nvote.sync.all.pred p, p, 0xffffffff;\nselp.u32 %0, 1, 0, p;\n}"
                 : "=r"(ok) : "r"(a), "r"(pa), "r"(b), "r"(pb) : "memory");
    return ok;
}
__device__ __forceinline__ uint32_t now_ns() { uint32_t t; asm volatile("mov.u32 %0, %%globaltimer_lo;" : "=r"(t) :: "memory"); return t; }
__device__ __forceinline__ uint32_t clk32() { uint32_t c; asm volatile("mov.u32 %0, %%clock;" : "=r"(c) :: "memory"); return c; }
__device__ __forceinline__ void wait_ns(uint32_t t) { jitter(); while ((int)(now_ns() - t) < 0) {} }
__device__ __forceinline__ void wait_clk(uint32_t t) { jitter(); while ((int)(clk32() - t) < 0) {} }
__device__ __forceinline__ bool elect_one() {
    uint32_t e;
    asm volatile("{\n.reg .pred p;\nelect.sync _|p, 0xffffffff;\nselp.u32 %0, 1, 0, p;\n}" : "=r"(e));
    return e;
}
constexpr uint64_t POL_FIRST = 0x12F0000000000000ull, POL_NORMAL = 0x1000000000000000ull;
__device__ __forceinline__ void tma_tile(uint32_t dst, const CUtensorMap* tm, int group, uint32_t bar, uint64_t pol) {
    asm volatile("cp.async.bulk.tensor.4d.shared::cluster.global.mbarrier::complete_tx::bytes.L2::cache_hint"
                 " [%0], [%1, {%3, %3, %3, %4}], [%2], %5;"
                 ::"r"(dst), "l"(tm), "r"(bar), "r"(0), "r"(group), "l"(pol) : "memory");
}
__device__ __forceinline__ void tma2d(uint32_t dst, const CUtensorMap* tm, int x, int y, uint32_t bar) {
    asm volatile("cp.async.bulk.tensor.2d.shared::cluster.global.mbarrier::complete_tx::bytes [%0], [%1, {%3, %4}], [%2];"
                 ::"r"(dst), "l"(tm), "r"(bar), "r"(x), "r"(y) : "memory");
}
__device__ __forceinline__ void bulk_load(uint32_t dst, const void* src, uint32_t bytes, uint32_t bar) {
    asm volatile("cp.async.bulk.shared::cluster.global.mbarrier::complete_tx::bytes [%0], [%1], %2, [%3];"
                 ::"r"(dst), "l"(src), "r"(bytes), "r"(bar) : "memory");
}
__device__ __forceinline__ void l2_prefetch(const void* p, uint32_t bytes) {
    asm volatile("cp.async.bulk.prefetch.L2.global [%0], %1;" ::"l"(p), "r"(bytes) : "memory");
}
__device__ __forceinline__ void mma16816(float (&c)[4], uint32_t a0, uint32_t a1, uint32_t a2, uint32_t a3, uint32_t b0, uint32_t b1) {
    asm volatile("mma.sync.aligned.m16n8k16.row.col.f32.bf16.bf16.f32 {%0,%1,%2,%3}, {%4,%5,%6,%7}, {%8,%9}, {%0,%1,%2,%3};"
                 : "+f"(c[0]), "+f"(c[1]), "+f"(c[2]), "+f"(c[3]) : "r"(a0), "r"(a1), "r"(a2), "r"(a3), "r"(b0), "r"(b1));
}
__device__ __forceinline__ void mma1688(float (&c)[4], uint32_t a0, uint32_t a1, uint32_t b0) {
    asm volatile("mma.sync.aligned.m16n8k8.row.col.f32.bf16.bf16.f32 {%0,%1,%2,%3}, {%4,%5}, {%6}, {%0,%1,%2,%3};"
                 : "+f"(c[0]), "+f"(c[1]), "+f"(c[2]), "+f"(c[3]) : "r"(a0), "r"(a1), "r"(b0));
}
__device__ __forceinline__ void ldsm4(uint32_t (&r)[4], uint32_t a) {
    asm volatile("ldmatrix.sync.aligned.m8n8.x4.shared.b16 {%0,%1,%2,%3}, [%4];"
                 : "=r"(r[0]), "=r"(r[1]), "=r"(r[2]), "=r"(r[3]) : "r"(a) : "memory");
}
__device__ __forceinline__ void ldsm4t(uint32_t (&r)[4], uint32_t a, uint32_t& zero) {
    asm volatile("ldmatrix.sync.aligned.m8n8.x4.trans.shared.b16 {%0,%1,%2,%3}, [%4];"
                 : "=r"(r[0]), "=r"(r[1]), "=r"(r[2]), "=r"(r[3]) : "r"(a + zero) : "memory");
    zero &= r[3];
}
__device__ __forceinline__ uint4 ld_pkt(const void* p) {
    uint4 v;
    asm volatile("{\n.reg .b128 t;\nld.relaxed.gpu.global.b128 t, [%4];\nmov.b128 {%0,%1,%2,%3}, t;\n}"
                 : "=r"(v.x), "=r"(v.y), "=r"(v.z), "=r"(v.w) : "l"(p) : "memory");
    return v;
}
__device__ __forceinline__ void st_pkt(const void* p, uint32_t a, uint32_t b, uint32_t c, uint32_t d) {
    asm volatile("{\n.reg .b128 t;\nmov.b128 t, {%1,%2,%3,%4};\nst.relaxed.gpu.global.b128 [%0], t;\n}"
                 ::"l"(p), "r"(a), "r"(b), "r"(c), "r"(d) : "memory");
}
__device__ __forceinline__ uint2 ld_pkt8(const void* p) {
    uint2 v;
    asm volatile("{\n.reg .b64 t;\nld.relaxed.gpu.global.b64 t, [%2];\nmov.b64 {%0,%1}, t;\n}" : "=r"(v.x), "=r"(v.y) : "l"(p) : "memory");
    return v;
}
__device__ __forceinline__ void red_cell(const char* p, float a, float b, float c) {
    jitter();
    asm volatile("red.relaxed.gpu.global.add.v4.f32 [%0], {%1,%2,%3,%4};" ::"l"(p), "f"(a), "f"(b), "f"(c), "f"(1.0f) : "memory");
}
#define PRED(n) "{\n.reg .pred p;\nsetp.ne.u32 p, %" #n ", 0;\n"
__device__ __forceinline__ void red_cell2_if(bool on, const char* p, float a, float b, float c) {
    jitter();
    asm volatile(PRED(5) "@p red.relaxed.gpu.global.add.v4.f32 [%0], {%1,%2,%3,%4};\n@p red.relaxed.gpu.global.add.v4.f32 [%0+4096], {%1,%2,%3,%4};\n}"
                 ::"l"(p), "f"(a), "f"(b), "f"(c), "f"(1.0f), "r"((uint32_t)on) : "memory");
}
__device__ __forceinline__ void st_pkt8_if(bool on, const void* p, uint32_t a, uint32_t b) {
    jitter();
    asm volatile(PRED(3) ".reg .b64 t;\nmov.b64 t, {%1,%2};\n@p st.relaxed.gpu.global.b64 [%0], t;\n}" ::"l"(p), "r"(a), "r"(b), "r"((uint32_t)on) : "memory");
}
__device__ __forceinline__ void st_pkt82_if(bool on, const void* p, uint32_t a, uint32_t b) {
    asm volatile(PRED(3) ".reg .b64 t;\nmov.b64 t, {%1,%2};\n@p st.relaxed.gpu.global.b64 [%0], t;\n@p st.relaxed.gpu.global.b64 [%0+4096], t;\n}"
                 ::"l"(p), "r"(a), "r"(b), "r"((uint32_t)on) : "memory");
}
__device__ __forceinline__ void st_pkt2_if(bool on, const void* p, uint32_t a, uint32_t b, uint32_t c, uint32_t d) {
    jitter();
    asm volatile(PRED(5) ".reg .b128 t;\nmov.b128 t, {%1,%2,%3,%4};\n@p st.relaxed.gpu.global.b128 [%0], t;\n@p st.relaxed.gpu.global.b128 [%0+4096], t;\n}"
                 ::"l"(p), "r"(a), "r"(b), "r"(c), "r"(d), "r"((uint32_t)on) : "memory");
}
__device__ __forceinline__ void mbar_arrive_if(bool on, uint32_t a) {
    jitter();
    asm volatile(PRED(1) "@p mbarrier.arrive.shared::cta.b64 _, [%0];\n}" ::"r"(a), "r"((uint32_t)on) : "memory");
}
__device__ __forceinline__ void sts16_if(bool on, uint32_t a, uint32_t v) {
    asm volatile(PRED(2) "@p st.shared.u16 [%0], %1;\n}" ::"r"(a), "h"((unsigned short)v), "r"((uint32_t)on) : "memory");
}
__device__ __forceinline__ void sts32_if(bool on, uint32_t a, uint32_t v) {
    asm volatile(PRED(2) "@p st.shared.u32 [%0], %1;\n}" ::"r"(a), "r"(v), "r"((uint32_t)on) : "memory");
}
__device__ __forceinline__ void sts128_if(bool on, uint32_t a, uint32_t x, uint32_t y, uint32_t z, uint32_t w) {
    jitter();
    asm volatile(PRED(5) "@p st.shared.v4.u32 [%0], {%1,%2,%3,%4};\n}" ::"r"(a), "r"(x), "r"(y), "r"(z), "r"(w), "r"((uint32_t)on) : "memory");
}
__device__ __forceinline__ float fast_rcp(float x) { float r; asm("rcp.approx.ftz.f32 %0, %1;" : "=f"(r) : "f"(x)); return r; }
__device__ __forceinline__ float fast_sqrt(float x) { float r; asm("sqrt.approx.ftz.f32 %0, %1;" : "=f"(r) : "f"(x)); return r; }
__device__ __forceinline__ float fast_ex2(float x) { float r; asm("ex2.approx.ftz.f32 %0, %1;" : "=f"(r) : "f"(x)); return r; }
__device__ __forceinline__ uint32_t pack2(float lo, float hi) {
    uint32_t r;
    asm("cvt.rn.bf16x2.f32 %0, %1, %2;" : "=r"(r) : "f"(hi), "f"(lo));
    return r;
}
__device__ __forceinline__ float bfr(float x) { return __uint_as_float(pack2(0.f, x)); }
__device__ __forceinline__ uint32_t badd2(uint32_t a, uint32_t b) { uint32_t r; asm("add.rn.bf16x2 %0, %1, %2;" : "=r"(r) : "r"(a), "r"(b)); return r; }
__device__ __forceinline__ uint32_t bsub2(uint32_t a, uint32_t b) { uint32_t r; asm("sub.rn.bf16x2 %0, %1, %2;" : "=r"(r) : "r"(a), "r"(b)); return r; }
__device__ __forceinline__ uint32_t bmul2(uint32_t a, uint32_t b) { uint32_t r; asm("mul.rn.bf16x2 %0, %1, %2;" : "=r"(r) : "r"(a), "r"(b)); return r; }
__device__ __forceinline__ float bf_lo(uint32_t w) { return __uint_as_float(w << 16); }
__device__ __forceinline__ float bf_hi(uint32_t w) { return __uint_as_float(w & 0xffff0000u); }
__device__ __forceinline__ float F(uint32_t t) { return __uint_as_float(t); }
__device__ __forceinline__ uint32_t lds16(uint32_t a) { unsigned short h; asm volatile("ld.shared.u16 %0, [%1];" : "=h"(h) : "r"(a) : "memory"); return h; }
__device__ __forceinline__ uint32_t lds32(uint32_t a) { uint32_t v; asm volatile("ld.shared.u32 %0, [%1];" : "=r"(v) : "r"(a) : "memory"); return v; }
__device__ __forceinline__ uint2 lds64(uint32_t a) {
    uint2 v; asm volatile("ld.shared.v2.u32 {%0,%1}, [%2];" : "=r"(v.x), "=r"(v.y) : "r"(a) : "memory"); return v;
}
__device__ __forceinline__ uint4 lds128(uint32_t a) {
    uint4 v; asm volatile("ld.shared.v4.u32 {%0,%1,%2,%3}, [%4];" : "=r"(v.x), "=r"(v.y), "=r"(v.z), "=r"(v.w) : "r"(a) : "memory"); return v;
}
__device__ __forceinline__ float sum8(const uint4& u, const uint4& v) {
    return ((F(u.x) + F(u.y)) + (F(u.z) + F(u.w))) + ((F(v.x) + F(v.y)) + (F(v.z) + F(v.w)));
}
__device__ __forceinline__ void sts16(uint32_t a, uint32_t v) { asm volatile("st.shared.u16 [%0], %1;" ::"r"(a), "h"((unsigned short)v) : "memory"); }
__device__ __forceinline__ void sts32(uint32_t a, uint32_t v) { asm volatile("st.shared.u32 [%0], %1;" ::"r"(a), "r"(v) : "memory"); }
__device__ __forceinline__ void stsf(uint32_t a, float v) { asm volatile("st.shared.f32 [%0], %1;" ::"r"(a), "f"(v) : "memory"); }
__device__ __forceinline__ void stsf2(uint32_t a, float x, float y) { asm volatile("st.shared.v2.f32 [%0], {%1,%2};" ::"r"(a), "f"(x), "f"(y) : "memory"); }
__device__ __forceinline__ void stsf4(uint32_t a, float x, float y, float z, float w) {
    asm volatile("st.shared.v4.f32 [%0], {%1,%2,%3,%4};" ::"r"(a), "f"(x), "f"(y), "f"(z), "f"(w) : "memory");
}
template <int ID, int N> __device__ __forceinline__ void bar_sync() { jitter(); asm volatile("bar.sync %0, %1;" ::"n"(ID), "n"(N) : "memory"); jitter(); }
template <int ID, int N> __device__ __forceinline__ void bar_arrive() { jitter(); asm volatile("bar.arrive %0, %1;" ::"n"(ID), "n"(N) : "memory"); jitter(); }
__device__ __forceinline__ void fence_async() { asm volatile("fence.proxy.async.shared::cta;" ::: "memory"); }
__device__ __forceinline__ float shx(float v, int m) { return __shfl_xor_sync(0xffffffffu, v, m); }
__device__ __forceinline__ float shi(float v, int l) { return __shfl_sync(0xffffffffu, v, l); }
__device__ __forceinline__ uint32_t shi(uint32_t v, int l) { return __shfl_sync(0xffffffffu, v, l); }
__device__ __forceinline__ uint32_t opaque(uint32_t x) { asm volatile("mov.u32 %0, %0;" : "+r"(x)); return x; }
__device__ __forceinline__ const char* opaque(const char* x) { asm volatile("mov.u64 %0, %0;" : "+l"(x)); return x; }
constexpr float LOG2E = 1.4426950408889634f, SCALE = 0.07216878364870322f;

#define TRACE(idx) do {} while (0)
#define TRACES(slot) do {} while (0)

__device__ __forceinline__ uint32_t probe_near(const Params& p, int w, int lane) {
    const int cta = cta_id();
    const char* pr = p.scr + SCR_O + head_off(cta >> 2) + 2048 + w * 256 + (cta & 3) * 64;
    st_pkt2_if(lane < 4, pr + lane * 16, 0, 0, 0, 0);
    uint32_t best0 = ~0u, best1 = ~0u;
#pragma unroll 1
    for (int i = w & 1; i < 6 + (w & 1); i++) {
        uint32_t c = clk32(), v = 0;
        if (lane == 0) asm volatile("atom.relaxed.gpu.global.add.u32 %0, [%1], 1;" : "=r"(v) : "l"(pr + (i & 1) * HALF) : "memory");
        c += __shfl_sync(0xffffffffu, v, 0) >> 16;
        c = clk32() - c;
        if (i & 1) best1 = min(best1, c); else best0 = min(best0, c);
    }
    return min(best0, 0xffffu) | min(best1, 0xffffu) << 16;
}
__device__ __forceinline__ uint32_t near_half() {
    const uint4 a = lds128(SM_NEAR), b = lds128(SM_NEAR + 16);
    const uint32_t m = __vminu2(__vminu2(__vminu2(a.x, a.y), __vminu2(a.z, a.w)), __vminu2(__vminu2(b.x, b.y), __vminu2(b.z, b.w)));
    return head_near(cta_id() >> 2, ((m & 0xffffu) > m >> 16) != (CFG(FLIP) != 0) ? HALF : 0);
}

__device__ __forceinline__ int tile_pos(int t) {
    const int cta = cta_id(), u = CFG(BYC) ? cta * CFG(ROT) : (cta >> 2) * CFG(ROT);
    return (t * (CFG(MUL) ? ((u >> 2) & 6) | 1 : 1) + u) & 7;
}
__device__ __forceinline__ int kv_group(int k, int t) {
    const int cta = cta_id();
    return ((k * NHEAD + (cta >> 2)) * SK + (SK - WIN) + (cta & 3) * (CFG(ILV) ? 32 : 256) + tile_pos(t) * (CFG(ILV) ? 128 : 32)) / 8;
}
__device__ __forceinline__ uint32_t phase_ns() { return (((cta_id() >> 2) * CFG(PERM)) & 31) * CFG(STAG) / 32; }

__device__ __forceinline__ void ln_fast(float s, float q, float& mean, float& rstd) {
    mean = s * (1.f / DM);
    asm("rsqrt.approx.ftz.f32 %0, %1;" : "=f"(rstd) : "f"(fmaxf(fmaf(-mean, mean, fmaf(q, 1.f / DM, 1e-5f)), 1e-5f)));
}
__device__ __forceinline__ void q_role(const Params& p, int lane) {
    const int cta = cta_id();
    mbar_wait(bar_at(B_EP), 0);
    const uint32_t epoch = lds32(SM_EPOCH), near = head_near(cta >> 2, near_half());
    auto sums = [&](float& S0, float& S1) {
        bar_sync<3, 288>();
        const uint32_t ra = SM_PQ + lane * 16;
        S0 = sum8(lds128(ra), lds128(ra + 1024)); S1 = sum8(lds128(ra + 512), lds128(ra + 1536));
    };
    float cs0, cs1;
    {
        uint32_t q0 = 0, q1 = 0, q2 = 0, q3 = 0;
#pragma unroll 1
        for (int r = 0; r < NB; r++) {
            sums(cs0, cs1);
            bar_arrive<7, 288>();
            q0 = q1; q1 = q2; q2 = q3; q3 = pack2(cs0, cs1);
        }
        const uint32_t t0 = shi(q3, 3 * lane - 72), t1 = shi(q3, 3 * lane - 71), t2 = shi(q3, 3 * lane - 70), tag = epoch << 8 | 0x40;
        const char* box = p.scr + SCR_O + head_off(cta >> 2) + 2048 + (lane >> 2) * 256 + (lane & 3) * 16;
        st_pkt2_if(true, box + (cta & 3) * 64, lane < 24 ? q0 : t0, lane < 24 ? q1 : t1, lane < 24 ? q2 : t2, tag);
        const uint32_t qd = SM_Q + (lane < 24 ? lane * 4 : 3 * 384 + (lane - 24) * 12), step = lane < 24 ? 384 : 4;
#pragma unroll 1
        for (int j = 0; j < 4; j++) {
            uint4 v;
            SPIN_DECL;
            do {
                __nanosleep(200);
                v = ld_pkt(box + near + j * 64);
                SPIN_CHECK(j);
            } while (__any_sync(0xffffffffu, v.w != tag));
            sts32(qd + j * 96, v.x); sts32(qd + j * 96 + step, v.y); sts32(qd + j * 96 + 2 * step, v.z);
        }
        mbar_arrive(bar_at(B_QR));
    }
    sums(cs0, cs1);
    bar_arrive<7, 288>();
    const char* const src = p.scr + SCR_Q + head_off(cta >> 2) + lane * 8 + near;
    const char* const dst = src + (cta & 3) * 192;
    const uint32_t qd = SM_Q + NB * 384 + lane * 4;
    st_pkt82_if(lane < 24, dst - near, 0, 0);
#pragma unroll 1
    for (int k = 0; k < NB; k++) {
        float S0, S1, mean, rstd;
        sums(S0, S1);
        ln_fast(shi(S1, 24), shi(S0, 24), mean, rstd);
        const uint32_t qq = pack2(fmaf(-mean, cs0, S0) * rstd, fmaf(-mean, cs1, S1) * rstd), tag = epoch * NB + k;
        st_pkt8_if(lane < 24, dst + ((int)HALF - 2 * (int)near), qq, tag);
        st_pkt8_if(lane < 24, dst, qq, tag);
        TRACES(k * 12 + 5);
        uint2 a, b, c;
        SPIN_DECL;
        do {
            a = ld_pkt8(src); b = ld_pkt8(src + 256); c = ld_pkt8(src + 512);
            SPIN_CHECK(k);
            sts32(qd, a.x); sts32(qd + 128, b.x); sts32(qd + 256, c.x);
        } while (__any_sync(0xffffffffu, a.y != tag || b.y != tag || c.y != tag));
        mbar_arrive(bar_at(B_QR));
    }
}

struct Maps { CUtensorMap k, v, q, o, g, u; };
__device__ __forceinline__ void load_role(const Params& p, const CUtensorMap* tmKV, int lane, uint32_t t0) {
    const int cta = cta_id();
    t0 += phase_ns();
#pragma unroll 1
    for (int i = 1; i < 5; i++) {
        wait_ns(t0 + i * CFG(TICK0));
        if (elect_one()) l2_prefetch(p.wq + (size_t)(128 * i + cta) * 12288, 12288);
        TRACE(230 + i);
    }
    uint32_t plan[2];
#pragma unroll
    for (int i = 0; i < 2; i++) {
        const int j = lane + 32 * i, k = j >> 4, t = j & 15, u = t >> 1, jw = j - CFG(WIN);
        const int sb = k == 0 ? B_WC + (t >= 8) + (t >= 14) : t >= 12 ? B_RK + u - 5 : t >= 4 ? B_RR + t - 4 : t >= 2 ? B_RP : k > 1 ? B_RK + 3 : B_RR + t;
        const uint32_t sw = sb * 8 | (j < 18 ? 0 : (t >= 12 || u == 1 ? k - 1 : k) & 1) << 9;
        plan[i] = sw | (jw < 0 ? sw : (B_F1 + (jw & 15)) * 8 | ((jw >> 4) & 1) << 9) << 10 |
                  (slot_at(slots(k), t < 8 ? pass_nibble(k, u) : u) * 2 + (t & 1)) << 20 | (t < 10 && j >= 8 && j < 56) << 25;
    }
    bar_sync<6, 64>();
    wait_ns(t0 + kb_ns(60));
    if (elect_one()) bulk_load(ST_WD, p.wd + cta * 15360, 15360, bar_at(B_W));
    TRACE(235);
#pragma unroll 1
    for (int i = 0; i < 5; i++) {
        wait_ns(t0 + kb_ns(75) + i * kb_ns(6));
        if (elect_one()) { l2_prefetch(p.wg + (128 * i + cta) * 3072, 3072); l2_prefetch(p.wu + (128 * i + cta) * 3072, 3072); }
    }
#pragma unroll 1
    for (int i = 0; i < 6; i++) {
        wait_ns(t0 + kb_ns(105) + min(i, 4) * kb_ns(10));
        if (elect_one()) l2_prefetch(p.wo + (size_t)((cta >> 2) * DH + 32 * i + 8 * (cta & 3)) * 1280, 10240);
    }
    t0 += batch_ns(0);
    int jp = 0, shift = 0;
    uint32_t earliest = t0;
    auto requested = [&](uint32_t now) {
        shift = max(max(shift - CFG(GAIN), 0), (int)(now - t0) - (jp < 12 ? CFG(LMAX0) : CFG(LMAX)));
        TRACE(128 + jp);
        t0 += tick_ns(++jp);
    };
    uint32_t pos = 0;
#pragma unroll
    for (int t = 0; t < 8; t++) pos |= tile_pos(t) << (4 * t);
    const int grp0 = kv_group(0, 0) - tile_pos(0) * (CFG(ILV) ? 16 : 4);
    auto group = [&](int j) { return grp0 + (j >> 4) * (NHEAD * SK / 8) + ((pos >> (4 * (j & 7))) & 7) * (CFG(ILV) ? 16 : 4); };
#pragma unroll 1
    for (int j = 0; j < 16 * NB; j++) {
        const uint32_t pl = __shfl_sync(0xffffffffu, j & 32 ? plan[1] : plan[0], j);
        const int jmax = min(j + CFG(PMAX), 16 * NB);
        jitter();
        uint32_t now;
        SPIN_DECL;
        while (true) {
            const bool ok = mbar_test2(SM_BAR + (pl & 511), (pl >> 9) & 1, SM_BAR + ((pl >> 10) & 511), (pl >> 19) & 1);
            now = now_ns();
            const int late = now - t0 - shift;
            if (ok && (jp > j ? (int)(now - earliest) : late) >= 0) break;
            if (late >= (jp > j ? 0 : CFG(PGRACE)) && jp < jmax) {
                if (elect_one())
                    asm volatile("cp.async.bulk.prefetch.tensor.4d.L2.global [%0, {%1, %1, %1, %2}];" ::"l"(tmKV + ((jp >> 3) & 1)), "r"(0), "r"(group(jp)) : "memory");
                requested(now);
            }
            SPIN_CHECK(j);
        }
        if (elect_one()) {
            mbar_expect_tx(bar_at(B_F1 + (j & 15)), TILE);
            tma_tile(SB + ((pl >> 20) & 31) * TILE, tmKV + ((j >> 3) & 1), group(j), bar_at(B_F1 + (j & 15)), pl >> 25 ? POL_NORMAL : POL_FIRST);
        }
        TRACE(256 + j);
        if ((j & 15) == 15) TRACES(88 + (j >> 4));
        earliest = now + CFG(VSTEP);
        if (jp == j) requested(now);
        const int jl = j - CFG(LW);
        if (CFG(UP) && jl >= CFG(JL0) && !mbar_test2(bar_at(B_F1 + (jl & 15)), (jl >> 4) & 1, bar_at(B_F1 + (jl & 15)), (jl >> 4) & 1)) shift += CFG(UP);
    }
}

__device__ __forceinline__ void reload_role(const Params& p, const Maps* tm, uint32_t t0) {
    const CUtensorMap* const tmK = &tm->k;
    const CUtensorMap* const tmV = &tm->v;
    const int cta = cta_id();
    t0 += CFG(TICK0) + CFG(WLAG) + phase_ns();
#pragma unroll 1
    for (int i = 0; i < 5; i++) {
        wait_ns(t0 + i * CFG(TICK0));
        if (elect_one()) tma2d(ST_WQ + i * 12288, &tm->q, 48 * cta, 128 * i, bar_at(B_W));
        TRACE(240 + i);
        if (i == 1) bar_sync<5, 480>();
    }
#pragma unroll 1
    for (int i = 0, o = 0; i < 10;) {
        const uint32_t now = now_ns() - t0;
        if (o < 6 && (int)now >= kb_ns(105) + o * kb_ns(10)) {
            if (elect_one()) tma2d(ST_WO + o * 10240, &tm->o, 160 * (cta & 3), (cta >> 2) * DH + 32 * o, bar_at(B_W + 1));
            o++;
        } else if ((int)now >= kb_ns(77) + i * CFG(GSTEP) && (i < 9 || o == 6)) {
            if (elect_one()) tma2d(ST_WG + (i & 1) * 20480 + (i >> 1) * 4096, i & 1 ? &tm->u : &tm->g, (12 * cta) & ~7, 128 * (i >> 1), bar_at(B_W + 2));
            i++;
        }
    }
#pragma unroll 1
    for (int k = 0; k < NB - 1; k++) {
        mbar_wait(bar_at(B_RK), k & 1);
        if (elect_one()) {
            const uint32_t dst = SB + slot_at(slots(k), 0) * PAIR;
            mbar_expect_tx(bar_at(B_FL), PAIR);
            tma_tile(dst, tmV, kv_group(k, 0), bar_at(B_FL), POL_FIRST);
            tma_tile(dst + TILE, tmV, kv_group(k, 1), bar_at(B_FL), POL_FIRST);
        }
        mbar_wait(bar_at(B_RV), k & 1);
        uint32_t due = now_ns();
        if (elect_one()) mbar_expect_tx(bar_at(B_F3), 4 * PAIR);
#pragma unroll 1
        for (int t = 0; t < 8; t++) {
            wait_ns(due);
            due += k == NB - 2 ? CFG(RSTEP3) : CFG(RSTEP);
            if (elect_one())
                tma_tile(SB + slot_at(slots(k + 1), t >> 1) * PAIR + (t & 1) * TILE, tmK, kv_group(k + 1, t), bar_at(B_F3), POL_FIRST);
        }
        TRACE(121 + k);
    }
}

__device__ __forceinline__ void zero_role(const Params& p, int lane, uint32_t t0) {
    const int cta = cta_id();
    unsigned ticket = 0;
    if (lane == 0) ticket = atomicAdd(&g_epoch, 1u);
    const uint32_t epoch = __shfl_sync(0xffffffffu, ticket, 0) / NCTA + 1;
    if (lane == 0) { sts32(SM_EPOCH, epoch); mbar_arrive(bar_at(B_EP)); }
    mbar_wait(bar_at(B_EP), 0);
#pragma unroll 1
    for (int k = 0; k < NB + 2; k++) {
        lane = opaque(lane);
        const int cl = 2 * (cta & 15) + (lane & 1);
        const int col = 80 * (cta >> 4) + (cl & 2 ? 48 : 0) + (cl >> 2) + (cl & 1 ? 8 : 0);
        const char* own = p.scr + (cl >> 2) * 256 + (cl & 3) * 16;
        uint32_t v0 = 0, v1 = 0, v2 = 0;
        if (lane < 4 && k < NB) {
            const unsigned short* xp = p.x + k * DM + col;
            v0 = __ldg(xp) << 16; v1 = __ldg(xp + 16) << 16; v2 = cl & 2 ? 0 : __ldg(xp + 32) << 16;
        }
        uint4 r;
        if (k == 1) mbar_wait(bar_at(B_RK), 0);
        if (k > 1) {
            mbar_wait(bar_at(B_FIN), k & 1);
            r = lds128(SM_FIN + (lane & 1) * 16);
        }
        if (k < NB) {
            const int lg = lane >> 3, ty = (lane & 7) >> 1;
            const char* dst = own + acc_off((k - (lg >> 1)) & 3, lg != 0, cta >> 4) + ty * HALF;
            wait_ns(t0 + batch_ns(k) + CFG(ZTILE) * CFG(TICK0));
            if (lg == 0 || (lg == 1 && (ty < 2 || k == NB - 1)) || (lg == 2 && k > 0 && ty > 1)) {
                st_pkt(dst, v0, v1, v2, ~0u);
                asm volatile("atom.relaxed.gpu.global.exch.b32 %0, [%1+12], %2;" : "=r"(v0) : "l"(dst), "r"(lane < 4 ? 0x3f800000u : 0u) : "memory");
                v0 = ~v0;
            }
            if (__any_sync(0xffffffffu, v0 != 0)) __trap();
            const char* cnt = p.scr + SCR_COUNT;
            if (lane < 2) asm volatile("red.relaxed.gpu.global.add.u32 [%0], 1;" ::"l"(cnt + lane * HALF) : "memory");
            const uint32_t target = ((epoch - 1) * NB + k + 1) * NCTA;
            cnt += near_half();
            SPIN_DECL;
            uint32_t v;
            do {
                __nanosleep(100);
                asm volatile("ld.relaxed.gpu.global.u32 %0, [%1];" : "=r"(v) : "l"(cnt) : "memory");
                SPIN_CHECK(v);
            } while (__any_sync(0xffffffffu, (int)(v - target) < 0));
        }
        __syncwarp();
        if (lane == 0) mbar_arrive(bar_at(B_Z));
        if (k > 1) {
            const int b = k - 2;
            const char* src = own + acc_off(b, 1, cta >> 4) + (2 + ((lane >> 1) & 1)) * HALF;
            unsigned short* o = p.out + b * DM + col + (lane >> 2) * 16;
            const bool on = !(lane & 2) && lane < (cl & 2 ? 8 : 12);
            wait_clk(clk32() + CFG(DLY_F));
            float cnt;
            SPIN_DECL;
            do {
                const uint4 v = ld_pkt(src);
                SPIN_CHECK(k);
                cnt = F(v.w) + shx(F(v.w), 2);
                const float y0 = F(v.x) + shx(F(v.x), 2), y1 = F(v.y) + shx(F(v.y), 2), y2 = F(v.z) + shx(F(v.z), 2);
                const uint32_t x01 = badd2(r.x, badd2(r.y, bmul2(pack2(y0, y1), r.w)));
                const uint32_t x2 = badd2(r.z, badd2(r.z >> 16, bmul2(pack2(y2, 0.f), r.w)));
                if (cnt == NCTA && on) *o = lane < 4 ? x01 : lane < 8 ? x01 >> 16 : x2;
            } while (__any_sync(0xffffffffu, cnt != NCTA));
            TRACES((2 * b + 1) * 6 + 4);
        }
    }
}

__host__ __device__ constexpr uint32_t desc_lo(uint32_t addr) { return ((addr & 0x3FFFFu) >> 4) | (1u << 16); }
constexpr uint32_t DESC_HI_TILE = (3072u >> 4) | (1u << 30);
constexpr uint32_t DESC_HI_VEC = 1u;
template <int TA, int AOFF, int BOFF>
__device__ __forceinline__ void wgmma_n8(float (&d)[4], uint32_t alo, uint32_t blo, int accumulate) {
    asm volatile("{\n.reg .pred p;\n.reg .b32 a, b;\n.reg .b64 da, db;\nsetp.ne.b32 p, %6, 0;\n"
                 "add.u32 a, %4, %8;\nadd.u32 b, %5, %9;\nmov.b64 da, {a, %10};\nmov.b64 db, {b, %11};\n"
                 "wgmma.mma_async.sync.aligned.m64n8k16.f32.bf16.bf16 {%0,%1,%2,%3}, da, db, p, 1, 1, %7, 0;\n}"
                 : "+f"(d[0]), "+f"(d[1]), "+f"(d[2]), "+f"(d[3])
                 : "r"(alo), "r"(blo), "r"(accumulate), "n"(TA), "n"(AOFF >> 4), "n"(BOFF >> 4), "n"(DESC_HI_TILE), "n"(DESC_HI_VEC));
}
template <int KS, int END>
__device__ __forceinline__ void qk_steps(float (&d)[4], uint32_t alo, uint32_t blo) {
    if constexpr (KS < END) {
        wgmma_n8<0, (KS >> 2) * 1024 + (KS & 3) * 32, KS * 32>(d, alo, blo, KS > 0);
        qk_steps<KS + 1, END>(d, alo, blo);
    }
}
__device__ __forceinline__ void pv_steps(float (&e)[3][4], uint32_t alo, uint32_t blo, int acc) {
    wgmma_n8<1, 0, 0>(e[0], alo, blo, acc); wgmma_n8<1, 1024, 0>(e[1], alo, blo, acc); wgmma_n8<1, 2048, 0>(e[2], alo, blo, acc);
    wgmma_n8<1, 6144, 32>(e[0], alo, blo, 1); wgmma_n8<1, 7168, 32>(e[1], alo, blo, 1); wgmma_n8<1, 8192, 32>(e[2], alo, blo, 1);
}
__device__ __forceinline__ void wg_fence() { asm volatile("wgmma.fence.sync.aligned;" ::: "memory"); }
__device__ __forceinline__ void wg_commit() { asm volatile("wgmma.commit_group.sync.aligned;" ::: "memory"); }
template <int N> __device__ __forceinline__ void wg_wait() { asm volatile("wgmma.wait_group.sync.aligned %0;" ::"n"(N) : "memory"); }
__device__ __forceinline__ void acc_ready(float (&d)[4]) { asm volatile("" : "+f"(d[0]), "+f"(d[1]), "+f"(d[2]), "+f"(d[3]) :: "memory"); }
__device__ __forceinline__ uint32_t score_pair(float (&d)[4]) {
    acc_ready(d);
    const uint32_t r = pack2(d[0], d[2]);
    return pack2(bf_lo(r) * SCALE, bf_hi(r) * SCALE);
}

__device__ __forceinline__ void attention_role(const Params& p, int w, int lane) {
    const int cta = cta_id(), t4 = lane & 3, g = lane >> 2;
    mbar_wait(bar_at(B_EP), 0);
    const uint32_t tag0 = lds32(SM_EPOCH) * NB;
    const char* const odst = p.scr + SCR_O + head_off(cta >> 2) + (2 * w + (g >> 2)) * 256 + (cta & 3) * 64 + (g & 3) * 16;
    const uint32_t pdst = SM_P + ((t4 + 3) & 3) * PSTR + (16 * w + g) * 2;
    auto softmax = [&](uint32_t& sc, int ps) -> uint32_t {
        const float s0 = bf_lo(sc), s1 = bf_hi(sc);
        int key = __float_as_int(fmaxf(s0, s1));
        key ^= (key >> 31) & 0x7fffffff;
        key = __reduce_max_sync(0xffffffffu, key);
        sts32(SM_MAX + w * 4, key);
        bar_sync<4, 128>();
        const uint4 mx = lds128(SM_MAX);
        key = max(max((int)mx.x, (int)mx.y), max((int)mx.z, (int)mx.w));
        key ^= (key >> 31) & 0x7fffffff;
        const float mb = __int_as_float(key) * LOG2E;
        const uint32_t pp = pack2(fast_ex2(fmaf(s0, LOG2E, -mb)), fast_ex2(fmaf(s1, LOG2E, -mb)));
        sts16(pdst + ps * 4 * PSTR, pp); sts16(pdst + ps * 4 * PSTR + 16, pp >> 16);
        fence_async();
        bar_sync<4, 128>();
        sc = pp;
        return key;
    };
    auto put_sum = [&](uint32_t pp, int ps) {
        uint32_t fs;
        asm volatile("redux.sync.add.u32 %0, %1, 0xffffffff;" : "=r"(fs) : "r"(__float2uint_rn((bf_lo(pp) + bf_hi(pp)) * 8388608.f)) : "memory");
        sts32(SM_SUM + ps * 16 + w * 4, fs);
    };
    auto aux_word = [&](uint32_t mx, const uint4& u, int k) {
        const float l = __uint2float_rn((u.x + u.y) + (u.z + u.w)) * (1.f / 8388608.f);
        return (g < 4 ? mx : (__float_as_uint(l) + 0x80u) & 0xffffff00u) | ((tag0 + k) & 0x7fu) | 0x80u;
    };
    auto send = [&](float (&e)[3][4], uint32_t aux, int ps) {
        acc_ready(e[0]); acc_ready(e[1]); acc_ready(e[2]);
        const uint32_t o0 = pack2(e[0][0], e[0][2]), o1 = pack2(e[1][0], e[1][2]), o2 = pack2(e[2][0], e[2][2]);
        st_pkt2_if(t4 == 0, odst + ps * 2048, o0, o1, o2, aux);
        mbar_arrive_if(lane == 0, bar_at(ps ? B_RV : B_PS));
    };
    mbar_wait(bar_at(B_QR), 0);
    TRACES(73);
#pragma unroll 1
    for (int it = 0; it <= NB; it++) {
        uint32_t m1 = 0;
        if (it < NB) {
            const uint32_t tab = slots(it);
            const uint32_t ka = SB + (2 * w + ((lane >> 3) & 1)) * 3072 + (lane & 7) * 128 + (((lane >> 4) ^ (lane & 7)) << 4);
            const uint32_t qa = SM_Q + it * 384 + (lane >> 3) * 16;
            uint32_t sc = 0;
#pragma unroll 1
            for (int u = 0; u < 4; u++) {
                const uint32_t base = ka + slot_at(tab, pass_nibble(it, u)) * PAIR;
                mbar_wait(bar_at(B_F1 + 2 * u + (w >> 1)), it & 1);
                float d0[4] = {}, d1[4] = {};
#pragma unroll
                for (int c = 0; c < 6; c++) {
                    uint32_t a0[4], a1[4], b[4];
                    ldsm4(b, qa + c * 64);
                    ldsm4(a0, (base ^ ((c & 1) * 64)) + (c >> 1) * 1024);
                    ldsm4(a1, (base ^ ((c & 1) * 64 + 32)) + (c >> 1) * 1024);
                    mma16816(d0, a0[0], a0[1], a0[2], a0[3], b[0], b[1]);
                    mma16816(d1, a1[0], a1[1], a1[2], a1[3], b[2], b[3]);
                }
                const uint32_t r = pack2(d0[0] + d1[0], d0[2] + d1[2]);
                mbar_arrive_if(lane == 0, bar_at(B_RR + 2 * u + (w >> 1)));
                if (t4 == ((u + 1) & 3)) sc = pack2(bf_lo(r) * SCALE, bf_hi(r) * SCALE);
            }
            m1 = softmax(sc, 0);
            put_sum(sc, 0);
        }
        if (it > 0) {
            const int k = it - 1;
            const uint32_t tab = slots(k);
            const uint32_t v0 = slot_at(tab, k < NB - 1 ? 0 : 4);
            TRACES(48 + k * 6);
            if (k > 0) mbar_wait(bar_at(B_F3), it & 1);
            mbar_wait(bar_at(B_QR), it & 1);
            fence_async();
            TRACES(49 + k * 6);
            float d[4][4] = {};
            const bool busy = k < NB - 1;
#pragma unroll
            for (int u = 0; u < 4; u++) {
                const uint32_t alo = desc_lo(SB) + slot_at(tab, u) * (PAIR >> 4), blo = desc_lo(SM_Q + 4 * 384);
                wg_fence();
                qk_steps<0, 6>(d[u], alo, blo);
                wg_commit();
                if (busy) {
                    wg_wait<1>();
                    if (u > 0) mbar_arrive_if(lane == 0, bar_at(B_RK + u - 1));
                }
                wg_fence();
                qk_steps<6, 12>(d[u], alo, blo);
                wg_commit();
                if (u < 3 && busy) wg_wait<1>();
            }
            wg_wait<2>();
            uint32_t sc = shi(score_pair(d[0]), lane & 28), s = shi(score_pair(d[1]), lane & 28);
            if (t4 == 2) sc = s;
            s = shi(score_pair(d[2]), lane & 28);
            if (t4 == 3) sc = s;
            wg_wait<0>();
            s = score_pair(d[3]);
            if (t4 == 0) sc = s;
            mbar_arrive_if(lane == 0, bar_at(B_RK + 3));
            TRACES(50 + k * 6);
            const uint32_t m2 = softmax(sc, 1);
            TRACES(51 + k * 6);
            float e[3][4] = {};
#pragma unroll
            for (int t = 0; t < 8; t++) {
                const int pr = ((t >> 1) + 1) & 3;
                if (t == 6 && k < NB - 1) mbar_wait(bar_at(B_FL), k & 1);
                wg_fence();
                pv_steps(e, desc_lo(SB + (t & 1) * TILE) + (pr ? slot_at(tab, 4 + pr) : v0) * (PAIR >> 4), desc_lo(SM_P + (4 + pr) * PSTR + (t & 1) * 64), t > 0);
                wg_commit();
                if (t < 7 && busy) wg_wait<1>();
                if (t == 1) put_sum(sc, 1);
            }
            bar_sync<4, 128>();
            const uint32_t aux = opaque(aux_word(m2, lds128(SM_SUM + 16), k));
            wg_wait<0>();
            send(e, aux, 1);
            TRACES(52 + k * 6);
        }
        if (it < NB) {
            const uint32_t tab = slots(it);
            if (it == 0) st_pkt2_if(t4 == 0, odst, 0, 0, 0, 0);
            bar_sync<4, 128>();
            const uint32_t aux = opaque(aux_word(m1, lds128(SM_SUM), it));
            float e[3][4] = {};
#pragma unroll 1
            for (int u = 0; u < 4; u++) {
                const uint32_t alo = desc_lo(SB) + slot_at(tab, 4 + u) * (PAIR >> 4), blo = desc_lo(SM_P) + u * (PSTR >> 4);
                mbar_wait(bar_at(B_F1 + 8 + 2 * u), it & 1);
                wg_fence();
                pv_steps(e, alo, blo, u > 0);
                wg_commit();
                wg_wait<1>();
                if (u == 1) mbar_arrive_if(lane == 0, bar_at(B_RP));
                mbar_wait(bar_at(B_F1 + 9 + 2 * u), it & 1);
                wg_fence();
                pv_steps(e, alo + (TILE >> 4), blo + 4, 1);
                wg_commit();
                wg_wait<1>();
            }
            wg_wait<0>();
            send(e, aux, 0);
            TRACES(53 + it * 6);
        }
    }
}

__device__ __forceinline__ void ln_finish(float s, float q, float& mean_b, float& rden) {
    const float mean = s * (1.f / DM);
    const float var = fmaxf(fmaf(q, 1.f / DM, -mean * mean), 0.f);
    mean_b = bfr(mean);
    rden = fast_rcp(bfr(fast_sqrt(bfr(bfr(var) + 1e-5f))));
}
__device__ __forceinline__ uint32_t ln_apply(uint32_t w, float mean_b, float rden) {
    const uint32_t d = bsub2(w, __byte_perm(__float_as_uint(mean_b), 0, 0x3232));
    return pack2(bf_lo(d) * rden, bf_hi(d) * rden);
}
__device__ __forceinline__ void put_x(uint32_t x01, uint32_t x2, uint32_t wa, bool e2) {
    jitter();
    sts16(wa, x01); sts16(wa + 8, x01 >> 16);
    sts16_if(!e2, wa + 16, x2);
}
__device__ __forceinline__ void get_x(uint32_t (&b)[10], uint32_t ra) {
    __syncwarp();
    const uint4 u = lds128(ra), v = lds128(ra + 16);
    const uint2 z = lds64(ra + 32);
    b[0] = u.x; b[1] = u.y; b[2] = u.z; b[3] = u.w; b[4] = v.x; b[5] = v.y; b[6] = v.z; b[7] = v.w; b[8] = z.x; b[9] = z.y;
}
__device__ __forceinline__ float fold(float a, float b, bool sel, int m) { return (sel ? b : a) + shx(sel ? a : b, m); }

__device__ __forceinline__ void chain_role(const Params& p, int w, int lane) {
    const int cta = cta_id(), h = cta >> 2, s = cta & 3;
    const int g = lane >> 2, t4 = lane & 3;
    const bool e1 = t4 & 1, e2 = t4 & 2;
    uint32_t wq[5][3][4], wo[3][5][4], wg[5][4], wh[5][2], wd[4][4];
    const int col0 = 80 * w + (e2 ? 48 : 0) + g + (e1 ? 8 : 0);
    const uint32_t xw = opaque(SM_X + w * 384 + 48 * (g >> 1) + (e2 ? 24 : 0) + (e1 ? 4 : 0) + 2 * (g & 1));
    const uint32_t xr = opaque(g == 1 ? SM_ONES : SM_X + w * 384 + (g == 3 ? 192 : 0) + 48 * t4);
    TRACES(75);
    sts32_if(lane < 12, SM_ONES + lane * 4, 0x3f803f80u);
    uint32_t zero = lane >> 5;
    const int mi = lane >> 3, mr = lane & 7;
    mbar_wait(bar_at(B_W), 0);
    TRACES(74);
    sts16(xw + 192, lds16(ST_X + 5120 + col0 * 2)); sts16(xw + 200, lds16(ST_X + 5120 + col0 * 2 + 32));
    sts16_if(!e2, xw + 208, lds16(ST_X + 5120 + col0 * 2 + 64));
#pragma unroll
    for (int i = 0; i < 5; i++)
#pragma unroll
        for (int mt = 0; mt < 3; mt++) ldsm4t(wq[i][mt], ST_WQ + (80 * w + 16 * i + mr + 8 * (mi >> 1)) * 96 + 32 * mt + 16 * (mi & 1), zero);
    const bool odd = cta & 1;
    const uint32_t lo = ST_WD + (mr + (odd ? 4 : 0)) * 1280 + 160 * w + 16 * (mi & 1);
    const uint32_t hi = ST_WD + ((mr & 3) + (odd ? 0 : 8)) * 1280 + 160 * w + 16 * (mi & 1);
    ldsm4t(wd[0], lo + 96 * (mi >> 1), zero);
    ldsm4t(wd[1], lo + 96 * (mi >> 1) + 32, zero);
    ldsm4t(wd[2], (mi < 2 ? lo : hi) + 64, zero);
    ldsm4t(wd[3], hi + 32 * (mi >> 1) + 96 * (mr >> 2), zero);
    fence_async();
    __syncwarp();
    mbar_arrive_if(lane == 0, bar_at(B_WC));
    mbar_wait(bar_at(B_EP), 0);
    const uint32_t near = __shfl_sync(0xffffffffu, near_half(), 0);
    uint32_t x01 = 0, x2 = 0, nx01 = 0, nx2 = 0;
#pragma unroll 1
    for (int n = -5; n < NROUND; n++) {
        const bool last = (ORD_LAST >> (n & 15)) & 1, head = !((ORD_NO_HEAD >> (n & 15)) & 1);
        const int k = (ORD_BATCH >> (2 * (n & 15))) & 3;
        if (n > -5 && n <= 0) bar_sync<7, 288>();
        else if (!last) bar_sync<2, 256>();
        TRACES(n <= 0 ? 83 + n : 95);
        const char* const slice = p.scr + acc_off(k, last, w);
        const char* const cell = opaque(slice + g * 256 + t4 * 16);
        if (n < -1) {
            const uint32_t xa = ST_X + (n + 5) * 1280, ln = opaque(lane);
            const int col0 = 80 * w + (ln & 2 ? 48 : 0) + (ln >> 2) + (ln & 1 ? 8 : 0);
            float sm = 0.f, sq = 0.f;
#pragma unroll
            for (int i = 0; i < 5; i++) {
                const uint2 c = lds64(xa + i * 256 + ln * 8);
                sm += (bf_lo(c.x) + bf_hi(c.x)) + (bf_lo(c.y) + bf_hi(c.y));
                sq = fmaf(bf_lo(c.x), bf_lo(c.x), fmaf(bf_hi(c.x), bf_hi(c.x), fmaf(bf_lo(c.y), bf_lo(c.y), fmaf(bf_hi(c.y), bf_hi(c.y), sq))));
            }
            x01 = lds16(xa + col0 * 2) | lds16(xa + col0 * 2 + 32) << 16;
            x2 = lds16(xa + col0 * 2 + 64);
#pragma unroll
            for (int o = 16; o; o >>= 1) { sm += shx(sm, o); sq += shx(sq, o); }
            float mean_b, rden;
            ln_finish(sm, sq, mean_b, rden);
            x01 = ln_apply(x01, mean_b, rden);
            x2 = ln_apply(x2, mean_b, rden);
            put_x(x01, x2, xw, e2);
        } else {
            if (n >= 0 && head) {
                if (!last || n == NROUND - 1) mbar_wait(bar_at(B_Z), (k + last) & 1);
                const char* src = p.scr + SCR_O + head_off(h) + head_near(h, near) + last * 2048 + (w & 6) * 256 + (lane & 15) * 16;
                const uint32_t tag = (lds32(SM_EPOCH) * NB + k) | 0x80u;
                mbar_wait(bar_at(last ? B_RV : B_PS), k & 1);
                uint4 v, z;
                {
                    SPIN_DECL;
                    do {
                        v = ld_pkt(src); z = ld_pkt(src + 256);
                        SPIN_CHECK(n);
                    } while (__any_sync(0xffffffffu, (((v.w ^ tag) | (z.w ^ tag)) & 0xffu) != 0));
                }
                TRACES(tr + 0);
                float a[3][4] = {};
                const uint32_t bb[3][2] = {{v.x, v.y}, {z.x, z.y}, {v.z, z.z}};
                float sa, sb, rl;
#pragma unroll
                for (int i = 0; i < 3; i++) {
                    const uint32_t l0 = g < 4 ? bb[i][0] : 0, l1 = g < 4 ? bb[i][1] : 0, h0 = g < 4 ? 0 : bb[i][0], h1 = g < 4 ? 0 : bb[i][1];
#pragma unroll
                    for (int mt = 0; mt < 5; mt++)
                        mma16816(a[mt % 3], wo[i][mt][0], wo[i][mt][1], wo[i][mt][2], wo[i][mt][3], mt < 3 ? l0 : h0, mt < 3 ? l1 : h1);
                    if (i == 0) {
                        int key = v.w & 0xffffff00u;
                        key ^= (key >> 31) & 0x7fffffff;
                        key = __reduce_max_sync(0xffffffffu, key);
                        key ^= (key >> 31) & 0x7fffffff;
                        const float ws = fast_ex2((F(v.w & 0xffffff00u) - __int_as_float(key)) * LOG2E);
                        sa = shi(ws, e1 ? 8 : 0); sb = shi(ws, e1 ? 12 : 4);
                        rl = ws * F(z.w & 0xffffff00u);
                        rl += shx(rl, 4);
                    }
                    if (i == 1) rl += shx(rl, 8);
                }
                float y[3];
#pragma unroll
                for (int j = 2; j < 5; j++) {
                    const int mt = j % 3;
                    y[mt] = fold(fmaf(a[mt][0], sa, a[mt][1] * sb), fmaf(a[mt][2], sa, a[mt][3] * sb), e1, 1);
                }
                const uint32_t pa = SM_PO + w * 512 + lane * 16;
                if (w < 2) {
                    const char* dst = opaque(cell + s * 16384);
                    rl = fast_rcp(rl);
                    bar_sync<1, 256>();
                    const uint4 c1 = lds128(pa), c2 = lds128(pa + 1024), c3 = lds128(pa + 2048);
                    red_cell2_if(true, dst, ((y[0] + F(c1.x)) + (F(c2.x) + F(c3.x))) * rl, ((y[1] + F(c1.y)) + (F(c2.y) + F(c3.y))) * rl,
                                 ((y[2] + F(c1.z)) + (F(c2.z) + F(c3.z))) * rl);
                } else {
                    stsf4(pa - 1024, y[0], y[1], y[2], 0.f);
                    bar_sync<1, 256>();
                }
                TRACES(tr + 1);
                if ((ORD_NO_TAIL >> n) & 1) continue;
                const uint32_t tsend = clk32();
                if (n == 0) {
                    st_pkt2_if(lane < 4, p.scr + SCR_O + head_off(h) + 2048 + w * 256 + s * 64 + lane * 16, 0, 0, 0, 0);
                    __syncwarp();
                } else if (!last) {
                    const char* nsrc = p.scr + acc_off(k - 1, 1, w) + near + g * 256 + t4 * 16;
                    SPIN_DECL;
                    do {
                        v = ld_pkt(nsrc);
                        SPIN_CHECK(n);
                        nx01 = pack2(F(v.x), F(v.y)); nx2 = pack2(F(v.z), 0.f);
                    } while (__any_sync(0xffffffffu, v.w != FULL_A));
                }
                wait_clk(tsend + (w < 2 ? 0 : 60) + (n < QUIET ? CFG(DLY_AL) : CFG(DLY_A)));
                {
                    SPIN_DECL;
                    do {
                        v = ld_pkt(cell + near);
                        SPIN_CHECK(n);
                        x01 = pack2(F(v.x), F(v.y));
                        x2 = pack2(F(v.z), 0.f);
                        put_x(x01, x2, xw, e2);
                    } while (__any_sync(0xffffffffu, v.w != FULL_A));
                }
                TRACES(tr + 2);
            } else if (n >= 0) {
                x01 = nx01; x2 = nx2;
                put_x(x01, x2, xw, e2);
            } else {
                mbar_wait(bar_at(B_W + 1), 0);
                const uint32_t ln = opaque(lane);
                const int mi = ln >> 3, mr = ln & 7;
                uint32_t zero = ln >> 5;
                TRACES(76);
#pragma unroll
                for (int i = 0; i < 3; i++) {
                    const int d = 16 * (w >> 1) + (mr >> 1) + 8 * (mr & 1) + (i < 2 ? 64 * (mi >> 1) + 4 * i : 128 + 4 * (mi >> 1));
#pragma unroll
                    for (int mt = 0; mt < 5; mt++) ldsm4t(wo[i][mt], ST_WO + d * 320 + 160 * (w & 1) + 32 * mt + 16 * (mi & 1), zero);
                }
                fence_async();
                __syncwarp();
                mbar_arrive_if(lane == 0, bar_at(B_WC + 1));
                mbar_wait(bar_at(B_W + 2), 0);
                TRACES(77);
#pragma unroll
                for (int i = 0; i < 5; i++) {
                    const uint32_t ga = ST_WG + (mi & 1) * 20480 + (80 * w + 16 * i + mr + 8 * (mi >> 1)) * 32;
                    uint32_t r[4];
                    ldsm4t(wg[i], ga + (odd ? 16 : 0), zero);
                    ldsm4t(r, ga + (odd ? 0 : 16), zero);
#pragma unroll
                    for (int kh = 0; kh < 2; kh++) {
                        const uint32_t moved = __shfl_xor_sync(0xffffffffu, odd ? r[2 * kh] : r[2 * kh + 1], 16);
                        wh[i][kh] = (g < 4) == odd ? moved : odd ? r[2 * kh + 1] : r[2 * kh];
                    }
                }
                fence_async();
                __syncwarp();
                mbar_arrive_if(lane == 0, bar_at(B_WC + 2));
                TRACES(72);
                x01 = 0x3f803f80u; x2 = 0x3f80u;
                put_x(x01, x2, xw, e2);
            }
            uint32_t b[10];
            get_x(b, xr);
            float a[2][4] = {};
#pragma unroll
            for (int i = 0; i < 5; i++) {
                mma16816(a[0], wg[i][0], wg[i][1], wg[i][2], wg[i][3], b[2 * i], b[2 * i + 1]);
                mma16816(a[1], wh[i][0], b[2 * i], wh[i][1], b[2 * i + 1], b[2 * i], b[2 * i + 1]);
            }
            stsf(SM_PG + (w >> 2) * 512 + (g + 8 * t4) * 16 + (w & 3) * 4, e2 ? (e1 ? a[1][2] : a[1][0]) : (e1 ? a[0][2] : a[0][0]));
            const uint2 cs = lds64(SM_CSG + lane * 48);
            const char* dst = opaque(cell + 3 * HALF - near);
            bar_sync<2, 256>();
            const float S = sum8(lds128(SM_PG + lane * 16), lds128(SM_PG + 512 + lane * 16));
            const float sx = shi(S, 25), sq = shi(S, 24), Su = shi(S, lane + (lane < 16 ? 8 : 4));
            if (n < 0) {
                if (w == 0) stsf2(SM_CSG + lane * 48, S, Su);
            } else {
                float mean_b, rden;
                ln_fast(sx, sq, mean_b, rden);
                const float gv = bfr(fmaf(-mean_b, F(cs.x), S) * rden), uv = bfr(fmaf(-mean_b, F(cs.y), Su) * rden);
                const float sg = fast_rcp(1.f + fast_ex2(-LOG2E * gv));
                const uint32_t hb = pack2(bfr(gv * sg) * uv, 0.f);
                const uint32_t b0 = __byte_perm(shi(hb, 2 * t4), shi(hb, 2 * t4 + 1), 0x5410);
                const uint32_t b1 = __byte_perm(shi(hb, e1 ? 18 : 16), shi(hb, e1 ? 19 : 17), 0x5410);
                const bool up = g >= 4;
                const uint32_t l0 = up ? 0 : b0, h0 = up ? b0 : 0;
                const uint32_t m1 = up == e2 ? b1 : 0;
                float d[3][4] = {};
                mma16816(d[0], wd[0][0], wd[0][1], wd[0][2], wd[0][3], l0, h0);
                mma16816(d[1], wd[1][0], wd[1][1], wd[1][2], wd[1][3], l0, h0);
                mma16816(d[2], wd[2][0], wd[2][1], wd[2][2], wd[2][3], l0, up ? 0 : m1);
                mma1688(d[0], wd[3][0], wd[3][1], m1);
                mma1688(d[1], wd[3][2], wd[3][3], m1);
                red_cell(dst, e1 ? d[0][2] : d[0][0], e1 ? d[1][2] : d[1][0], e1 ? d[2][2] : d[2][0]);
                const uint32_t tsend = clk32();
                TRACES(tr + 3);
                if (last && w != cta >> 4) continue;
                const float sgr = shi(sg, 27);
                const uint32_t sg2 = pack2(sgr, sgr);
                const uint32_t n01 = opaque(pack2((bf_lo(x01) - mean_b) * rden, (bf_hi(x01) - mean_b) * rden));
                const uint32_t n2 = opaque(pack2((bf_lo(x2) - mean_b) * rden, 0.f));
                if (last) {
                    sts128_if(lane >> 1 == (cta & 15), SM_FIN + (lane & 1) * 16, x01, n01, __byte_perm(x2, n2, 0x5410), sg2);
                    mbar_arrive_if(lane >> 1 == (cta & 15), bar_at(B_FIN));
                    __syncwarp();
                    continue;
                }
                wait_clk(tsend + (n < QUIET ? CFG(DLY_BL) : CFG(DLY_B)));
                const uint32_t r01 = x01, r2 = x2;
                float cnt;
                SPIN_DECL;
                do {
                    const uint4 v = ld_pkt(cell + 2 * HALF), z = ld_pkt(cell + 3 * HALF);
                    SPIN_CHECK(n);
                    cnt = F(v.w) + F(z.w);
                    x01 = badd2(r01, badd2(n01, bmul2(pack2(F(v.x) + F(z.x), F(v.y) + F(z.y)), sg2)));
                    x2 = badd2(r2, badd2(n2, bmul2(pack2(F(v.z) + F(z.z), 0.f), sg2)));
                    put_x(x01, x2, xw, e2);
                } while (__any_sync(0xffffffffu, cnt != NCTA));
                TRACES(tr + 4);
            }
        }
        {
            uint32_t b[10];
            get_x(b, xr);
            float a[3][4] = {};
            const float f0 = bf_lo(x01), f1 = bf_hi(x01), f2 = e2 ? 0.f : bf_lo(x2);
            float st;
#pragma unroll
            for (int i = 0; i < 5; i++) {
#pragma unroll
                for (int mt = 0; mt < 3; mt++) {
                    mma16816(a[mt], wq[i][mt][0], wq[i][mt][1], wq[i][mt][2], wq[i][mt][3], b[2 * i], b[2 * i + 1]);
                    if (i == 0 && mt == 0) st = fold(fmaf(f0, f0, fmaf(f1, f1, f2 * f2)), (f0 + f1) + f2, g & 1, 4);
                }
                if (i < 4) st += shx(st, i < 2 ? 1 << i : 2 << i);
            }
            const uint32_t pa = SM_PQ + (w >> 2) * 1024 + (g & 1) * 512 + ((e2 ? 16 : 0) + (e1 ? 4 : 0) + (g >> 1)) * 16 + (w & 3) * 4;
            stsf(pa + 128, e2 ? st : e1 ? a[1][2] : a[1][0]);
            stsf(pa, e2 ? (e1 ? a[2][2] : a[2][0]) : (e1 ? a[0][2] : a[0][0]));
            bar_sync<3, 288>();
            if (n >= 0 && w == cta >> 4) {
                red_cell2_if(lane >> 1 == (cta & 15), cell + (acc_off(k, 1, 0) - acc_off(k, 0, 0)), f0, f1, f2);
                __syncwarp();
            }
        }
    }
}

__host__ __device__ constexpr int bar_count(int i) {
    return i < 16 ? 1 : i < B_RR ? 0 : i < B_RK ? 2 : i <= B_RV ? 4 : i == B_Z ? 1 : i == B_EP ? 9 : i < B_WC ? 0 : i < B_FIN ? 8 :
           i == B_FIN ? 2 : i == B_PS || i == B_RP ? 4 : i == B_QR ? 32 : 1;
}
template <int I, int END> __device__ __forceinline__ void init_bars() {
    if constexpr (I < END) {
        if (bar_count(I)) mbar_init(bar_at(I), bar_count(I));
        init_bars<I + 1, END>();
    }
}
template <int ID> __device__ __forceinline__ void role_exit() { asm volatile("exit; // %0" ::"n"(ID)); }
constexpr int NTHREADS = 512;
#define STR2(x) #x
#define STR(x) STR2(x)
__global__ void __launch_bounds__(NTHREADS, 1)
decode_kernel(const Params p, const __grid_constant__ Maps tm) {
    extern __shared__ __align__(1024) unsigned char smem[];
    if (threadIdx.x == 0) l2_prefetch(p.wq + (size_t)blockIdx.x * 12288, 12288);
    const uint32_t t0 = now_ns() - CFG(LEAD);
    const int lane = threadIdx.x & 31;
    const int warp = __reduce_max_sync(0xffffffffu, threadIdx.x >> 5);
    if (warp < 8) {
        asm volatile("setmaxnreg.inc.sync.aligned.u32 " STR(CFG_REG_CHAIN) ";");
        bar_arrive<5, 480>();
        const uint32_t vote = probe_near(p, warp, lane);
        bar_sync<2, 256 + 32>();
        sts32(SM_NEAR + warp * 4, vote);
        mbar_arrive_if(lane == 0, bar_at(B_EP));
        chain_role(p, warp, __shfl_sync(0xffffffffu, lane, lane));
        role_exit<3>();
    } else if (warp < 12) {
        asm volatile("setmaxnreg.dec.sync.aligned.u32 " STR(CFG_REG_ATT) ";");
        if (elect_one()) {
            if (warp == 8) init_bars<0, 12>();
            else if (warp == 9) init_bars<12, 30>();
            else if (warp == 10) init_bars<30, 42>();
            else init_bars<42, NBAR>();
            asm volatile("fence.mbarrier_init.release.cluster;" ::: "memory");
            fence_async();
        }
        if (warp == 8) TRACE(236);
        bar_sync<5, 480>();
        if (warp == 8) TRACE(237);
        attention_role(p, warp - 8, lane);
        role_exit<2>();
    } else {
        asm volatile("setmaxnreg.dec.sync.aligned.u32 " STR(CFG_REG_HELP) ";");
        if (warp == 12) {
            load_role(p, &tm.k, lane, t0);
            role_exit<0>();
        } else {
            if (warp == 14) {
                if (smem_u32(smem) != SB) __trap();
                if (elect_one()) {
                    asm volatile("prefetch.tensormap [%0];" ::"l"(&tm.q) : "memory");
                    mbar_init(bar_at(B_W), 1); mbar_init(bar_at(B_W + 1), 1); mbar_init(bar_at(B_W + 2), 1);
                    asm volatile("fence.mbarrier_init.release.cluster;" ::: "memory");
                    fence_async();
                    mbar_expect_tx(bar_at(B_W), 61440 + 15360 + 6400); mbar_expect_tx(bar_at(B_W + 1), 61440); mbar_expect_tx(bar_at(B_W + 2), 40960);
                    bulk_load(ST_X, p.x, 5120, bar_at(B_W));
                    bulk_load(ST_X + 5120, p.wr, 1280, bar_at(B_W));
                }
                TRACE(238);
                reload_role(p, &tm, t0);
            } else {
                if (warp == 13 && elect_one()) {
                    asm volatile("prefetch.tensormap [%0];" ::"l"(&tm.g) : "memory");
                    asm volatile("prefetch.tensormap [%0];" ::"l"(&tm.u) : "memory");
                    asm volatile("prefetch.tensormap [%0];" ::"l"(&tm.o) : "memory");
                    asm volatile("prefetch.tensormap [%0];" ::"l"(&tm.k) : "memory");
                    asm volatile("prefetch.tensormap [%0];" ::"l"(&tm.v) : "memory");
                }
                TRACE(233 + warp);
                bar_sync<5, 480>();
                if (warp == 13) { bar_arrive<6, 64>(); q_role(p, lane); }
                else { bar_arrive<2, 256 + 32>(); zero_role(p, lane, t0); }
            }
            role_exit<1>();
        }
    }
}

typedef CUresult (*EncodeFn)(CUtensorMap*, CUtensorMapDataType, cuuint32_t, void*, const cuuint64_t*, const cuuint64_t*,
                             const cuuint32_t*, const cuuint32_t*, CUtensorMapInterleave, CUtensorMapSwizzle,
                             CUtensorMapL2promotion, CUtensorMapFloatOOBfill);

bool make_map(EncodeFn fn, CUtensorMap* m, const void* ptr, uint64_t cols, uint64_t rows, uint32_t bc, uint32_t br) {
    cuuint64_t dims[2] = {cols, rows};
    cuuint64_t strides[1] = {cols * 2};
    cuuint32_t box[2] = {bc, br};
    cuuint32_t es[2] = {1, 1};
    return fn(m, CU_TENSOR_MAP_DATA_TYPE_BFLOAT16, 2, const_cast<void*>(ptr), dims, strides, box, es, CU_TENSOR_MAP_INTERLEAVE_NONE,
              CU_TENSOR_MAP_SWIZZLE_NONE, CU_TENSOR_MAP_L2_PROMOTION_L2_128B, CU_TENSOR_MAP_FLOAT_OOB_FILL_NONE) == CUDA_SUCCESS;
}

bool make_kv_map(EncodeFn fn, CUtensorMap* m, const void* ptr) {
    cuuint64_t dims[4] = {64, 8, 3, (cuuint64_t)NB * NHEAD * SK / 8};
    cuuint64_t strides[3] = {DH * 2, 128, 8 * DH * 2};
    cuuint32_t box[4] = {64, 8, 3, 4};
    cuuint32_t es[4] = {1, 1, 1, 1};
    return fn(m, CU_TENSOR_MAP_DATA_TYPE_BFLOAT16, 4, const_cast<void*>(ptr), dims, strides, box, es, CU_TENSOR_MAP_INTERLEAVE_NONE,
              CU_TENSOR_MAP_SWIZZLE_128B, CU_TENSOR_MAP_L2_PROMOTION_L2_128B, CU_TENSOR_MAP_FLOAT_OOB_FILL_NONE) == CUDA_SUCCESS;
}

}

extern "C" void kernel_launch(void* const* d_in, const int* in_sizes, int n_in, void* d_out, int out_size) {
    (void)in_sizes; (void)n_in; (void)out_size;
    static EncodeFn fn = nullptr;
    static const char* scr = nullptr;
    if (!fn) {
        void* f = nullptr;
        cudaDriverEntryPointQueryResult qr;
        if (cudaGetDriverEntryPoint("cuTensorMapEncodeTiled", &f, cudaEnableDefault, &qr) != cudaSuccess || !f) return;
        void* sp = nullptr;
        if (cudaGetSymbolAddress(&sp, g_scratch) != cudaSuccess) return;
        scr = (const char*)(((uintptr_t)sp + (2 << 20) - 1) & ~(uintptr_t)((2 << 20) - 1));
        fn = (EncodeFn)f;
        cudaFuncSetAttribute(decode_kernel, cudaFuncAttributeMaxDynamicSharedMemorySize, SMEM_BYTES);
    }
    Maps tm;
    if (!make_kv_map(fn, &tm.k, d_in[1]) || !make_kv_map(fn, &tm.v, d_in[2])) return;
    if (!make_map(fn, &tm.q, d_in[3], NHEAD * DH, DM, 48, 128) || !make_map(fn, &tm.o, d_in[4], DM, NHEAD * DH, 160, 32)) return;
    if (!make_map(fn, &tm.g, d_in[7], FF, DM, 16, 128) || !make_map(fn, &tm.u, d_in[8], FF, DM, 16, 128)) return;
    Params p;
    p.x = (const unsigned short*)d_in[0];
    p.wq = (const char*)d_in[3];
    p.wo = (const char*)d_in[4];
    p.wr = (const unsigned short*)d_in[6];
    p.wg = (const char*)d_in[7];
    p.wu = (const char*)d_in[8];
    p.wd = (const char*)d_in[9];
    p.out = (unsigned short*)d_out;
    p.scr = scr;
    decode_kernel<<<NCTA, NTHREADS, SMEM_BYTES>>>(p, tm);
}
```

```cpp
#include <cuda_runtime.h>
#include <cuda_bf16.h>
#include <cuda.h>
#include <stdint.h>

namespace {

constexpr int NB = 4, DM = 640, NHEAD = 32, DH = 192, SK = 4096, WIN = 1024, FF = 1536;
constexpr int NCTA = 128;
constexpr int TILE = 12288, PAIR = 2 * TILE;

#define CFG_LIST(X) \
    X(TICK0, 479)        \
    X(TICK, 492)        \
    X(LEAD, 600)        \
    X(STAG, 430)        \
    X(WLAG, 350)        \
    X(GSTEP, 750)        \
    X(WIN, 5)        \
    X(PMAX, 2)        \
    X(PGRACE, 50)        \
    X(LMAX0, 150)        \
    X(LMAX, 160) \
    X(UP, 50)        \
    X(VSTEP, 150)        \
    X(RSTEP, 670)        \
    X(RSTEP3, 450) \
    X(ZTILE, 11)        \
    X(DLY_A, 410)        \
    X(DLY_AL, 100) \
    X(DLY_B, 570) \
    X(DLY_BL, 950) \
    X(DLY_F, 290) \
    X(FLIP, 0) \

#define X(n, v) constexpr int CFG_##n = v;
CFG_LIST(X)
#undef X
#define CFG(n) CFG_##n
constexpr int QUIET = 8;
#define CFG_REG_CHAIN 216
#define CFG_REG_ATT 48
#define CFG_REG_HELP 32
__device__ __forceinline__ int cta_id() { return (blockIdx.x & 1) << 6 | blockIdx.x >> 1; }
constexpr int KB_KV0 = 165;
__device__ __forceinline__ int kb_ns(int kb) { return kb * CFG(TICK0) / 12; }
__device__ __forceinline__ int tick_ns(int j) { return j <= 16 ? CFG(TICK0) : CFG(TICK); }
__device__ __forceinline__ int batch_ns(int k) { return kb_ns(KB_KV0) + (k ? 16 * (CFG(TICK0) + (k - 1) * CFG(TICK)) : 0); }

__device__ __forceinline__ uint32_t slots(int k) { return k & 2 ? (k & 1 ? 0x21304765u : 0x76835214u) : (k & 1 ? 0x21480765u : 0x76543210u); }
__device__ __forceinline__ int pass_nibble(int k, int u) { return k > 0 ? 4 + (u & 1) : u; }
__device__ __forceinline__ uint32_t slot_at(uint32_t tab, int u) { return (tab >> (4 * u)) & 15; }

constexpr int NROUND = 11;
constexpr uint32_t ORD_BATCH = 0x3b9910, ORD_LAST = 0x6da, ORD_NO_HEAD = 0x248, ORD_NO_TAIL = 0x092;

constexpr uint32_t SB = 1024;
constexpr uint32_t SM_BAR = SB + 9 * PAIR;
constexpr int B_F1 = 0;
constexpr int B_RR = 24;
constexpr int B_RK = 32;
constexpr int B_RV = 36;
constexpr int B_Z = 37;
constexpr int B_EP = 38;
constexpr int B_W = 39;
constexpr int B_WC = 42;
constexpr int B_FIN = 45;
constexpr int B_F3 = 46;
constexpr int B_PS = 48;
constexpr int B_RP = 49;
constexpr int B_FL = 50;
constexpr int B_QR = 51;
constexpr int NBAR = 52;
__host__ __device__ constexpr uint32_t bar_at(int i) { return SM_BAR + 8 * i; }
constexpr uint32_t SM_EPOCH = SM_BAR + 416;
constexpr uint32_t SM_MAX = SM_EPOCH + 16;
constexpr uint32_t SM_SUM = SM_MAX + 16;
constexpr uint32_t SM_NEAR = SM_SUM + 32;
constexpr uint32_t SM_FIN = SM_NEAR + 32;
constexpr uint32_t SM_Q = SM_FIN + 32;
constexpr uint32_t PSTR = 144;
constexpr uint32_t SM_P = SM_Q + 5 * 384;
constexpr uint32_t SM_X = SM_P + 8 * PSTR;
constexpr uint32_t SM_CSG = SM_X + 40;
constexpr uint32_t SM_ONES = SM_X + 8 * 384;
constexpr uint32_t SM_PG = SM_ONES + 48;
constexpr uint32_t SM_PO = SM_PG + 1024;
constexpr uint32_t SM_PQ = SM_PO;
constexpr int SMEM_BYTES = SM_PO + 3072 - SB;
static_assert(SMEM_BYTES <= 232448 && SM_Q % 16 == 0 && SM_P % 16 == 0 && SM_X % 16 == 0 && SM_PO % 16 == 0, "smem");
constexpr uint32_t ST_WQ = SB, ST_WD = SB + 3 * PAIR, ST_WO = SB + 4 * PAIR, ST_WG = SB + 7 * PAIR, ST_X = ST_WG + 40960;

__device__ unsigned g_epoch;
__device__ unsigned char g_scratch[4 << 20];
constexpr uint32_t HALF = 4096, SCR_O = 1 << 16, SCR_Q = 1 << 17, SCR_COUNT = 3 << 16;
__device__ __forceinline__ uint32_t acc_off(int k, int layer, int w) {
    return (k & 1) << 6 | layer << 7 | (w & 1) << 11 | (w >> 1) << 14 | (k + layer == NB) << 18;
}
__device__ __forceinline__ uint32_t head_off(int h) { return (h & 3) << 14 | (h & 4) << 16 | (h & 8) << 17 | (h & 16) << 9; }
__device__ __forceinline__ uint32_t head_near(int h, uint32_t near) { return near ^ HALF ^ (h & 16) << 8; }
constexpr uint32_t FULL_A = 0x42040000u;

struct Params {
    const char* wq;
    const unsigned short* x;
    const char* wo;
    const unsigned short* wr;
    const char* wg;
    const char* wu;
    const char* wd;
    unsigned short* out;
    const char* scr;
};

__device__ __forceinline__ uint32_t smem_u32(const void* p) { return (uint32_t)__cvta_generic_to_shared(p); }
__device__ __forceinline__ void mbar_init(uint32_t a, uint32_t c) { asm volatile("mbarrier.init.shared::cta.b64 [%0], %1;" ::"r"(a), "r"(c) : "memory"); }
__device__ __forceinline__ void mbar_expect_tx(uint32_t a, uint32_t b) {
    asm volatile("mbarrier.arrive.expect_tx.shared::cta.b64 _, [%0], %1;" ::"r"(a), "r"(b) : "memory");
}
__device__ __forceinline__ void mbar_arrive(uint32_t a) { asm volatile("mbarrier.arrive.shared::cta.b64 _, [%0];" ::"r"(a) : "memory"); }
constexpr uint32_t SPIN_LIMIT = 1u << 22;
#define SPIN_DECL uint32_t spins = 0
#define SPIN_CHECK(info) { if (++spins > SPIN_LIMIT) __trap(); }
__device__ __forceinline__ void jitter() {}
__device__ __forceinline__ void mbar_wait(uint32_t a, uint32_t parity) {
    jitter();
    uint32_t ok;
    SPIN_DECL;
    while (true) {
        asm volatile("{\n.reg .pred p;\nmbarrier.try_wait.parity.shared::cta.b64 p, [%1], %2;\nselp.u32 %0, 1, 0, p;\n}"
                     : "=r"(ok) : "r"(a), "r"(parity) : "memory");
        if (ok) break;
        SPIN_CHECK((a - SM_BAR) / 8 * 10 + parity);
    }
    jitter();
}
__device__ __forceinline__ bool mbar_test2(uint32_t a, uint32_t pa, uint32_t b, uint32_t pb) {
    uint32_t ok;
    asm volatile("{\n.reg .pred p, q;\nmbarrier.test_wait.parity.shared::cta.b64 p, [%1], %2;\n"
                 "mbarrier.test_wait.parity.shared::cta.b64 q, [%3], %4;\nand.pred p, p, q;\nvote.sync.all.pred p, p, 0xffffffff;\nselp.u32 %0, 1, 0, p;\n}"
                 : "=r"(ok) : "r"(a), "r"(pa), "r"(b), "r"(pb) : "memory");
    return ok;
}
__device__ __forceinline__ uint32_t now_ns() { uint32_t t; asm volatile("mov.u32 %0, %%globaltimer_lo;" : "=r"(t) :: "memory"); return t; }
__device__ __forceinline__ uint32_t clk32() { uint32_t c; asm volatile("mov.u32 %0, %%clock;" : "=r"(c) :: "memory"); return c; }
__device__ __forceinline__ void wait_ns(uint32_t t) { jitter(); while ((int)(now_ns() - t) < 0) {} }
__device__ __forceinline__ void wait_clk(uint32_t t) { jitter(); while ((int)(clk32() - t) < 0) {} }
__device__ __forceinline__ bool elect_one() {
    uint32_t e;
    asm volatile("{\n.reg .pred p;\nelect.sync _|p, 0xffffffff;\nselp.u32 %0, 1, 0, p;\n}" : "=r"(e));
    return e;
}
constexpr uint64_t POL_FIRST = 0x12F0000000000000ull, POL_NORMAL = 0x1000000000000000ull;
__device__ __forceinline__ void tma_tile(uint32_t dst, const CUtensorMap* tm, int group, uint32_t bar, uint64_t pol) {
    asm volatile("cp.async.bulk.tensor.4d.shared::cluster.global.mbarrier::complete_tx::bytes.L2::cache_hint"
                 " [%0], [%1, {%3, %3, %3, %4}], [%2], %5;"
                 ::"r"(dst), "l"(tm), "r"(bar), "r"(0), "r"(group), "l"(pol) : "memory");
}
__device__ __forceinline__ void tma2d(uint32_t dst, const CUtensorMap* tm, int x, int y, uint32_t bar) {
    asm volatile("cp.async.bulk.tensor.2d.shared::cluster.global.mbarrier::complete_tx::bytes [%0], [%1, {%3, %4}], [%2];"
                 ::"r"(dst), "l"(tm), "r"(bar), "r"(x), "r"(y) : "memory");
}
__device__ __forceinline__ void bulk_load(uint32_t dst, const void* src, uint32_t bytes, uint32_t bar) {
    asm volatile("cp.async.bulk.shared::cluster.global.mbarrier::complete_tx::bytes [%0], [%1], %2, [%3];"
                 ::"r"(dst), "l"(src), "r"(bytes), "r"(bar) : "memory");
}
__device__ __forceinline__ void l2_prefetch(const void* p, uint32_t bytes) {
    asm volatile("cp.async.bulk.prefetch.L2.global [%0], %1;" ::"l"(p), "r"(bytes) : "memory");
}
__device__ __forceinline__ void mma16816(float (&c)[4], uint32_t a0, uint32_t a1, uint32_t a2, uint32_t a3, uint32_t b0, uint32_t b1) {
    asm volatile("mma.sync.aligned.m16n8k16.row.col.f32.bf16.bf16.f32 {%0,%1,%2,%3}, {%4,%5,%6,%7}, {%8,%9}, {%0,%1,%2,%3};"
                 : "+f"(c[0]), "+f"(c[1]), "+f"(c[2]), "+f"(c[3]) : "r"(a0), "r"(a1), "r"(a2), "r"(a3), "r"(b0), "r"(b1));
}
__device__ __forceinline__ void mma1688(float (&c)[4], uint32_t a0, uint32_t a1, uint32_t b0) {
    asm volatile("mma.sync.aligned.m16n8k8.row.col.f32.bf16.bf16.f32 {%0,%1,%2,%3}, {%4,%5}, {%6}, {%0,%1,%2,%3};"
                 : "+f"(c[0]), "+f"(c[1]), "+f"(c[2]), "+f"(c[3]) : "r"(a0), "r"(a1), "r"(b0));
}
__device__ __forceinline__ void ldsm4(uint32_t (&r)[4], uint32_t a) {
    asm volatile("ldmatrix.sync.aligned.m8n8.x4.shared.b16 {%0,%1,%2,%3}, [%4];"
                 : "=r"(r[0]), "=r"(r[1]), "=r"(r[2]), "=r"(r[3]) : "r"(a) : "memory");
}
__device__ __forceinline__ void ldsm4t(uint32_t (&r)[4], uint32_t a, uint32_t& zero) {
    asm volatile("ldmatrix.sync.aligned.m8n8.x4.trans.shared.b16 {%0,%1,%2,%3}, [%4];"
                 : "=r"(r[0]), "=r"(r[1]), "=r"(r[2]), "=r"(r[3]) : "r"(a + zero) : "memory");
    zero &= r[3];
}
__device__ __forceinline__ uint4 ld_pkt(const void* p) {
    uint4 v;
    asm volatile("{\n.reg .b128 t;\nld.relaxed.gpu.global.b128 t, [%4];\nmov.b128 {%0,%1,%2,%3}, t;\n}"
                 : "=r"(v.x), "=r"(v.y), "=r"(v.z), "=r"(v.w) : "l"(p) : "memory");
    return v;
}
__device__ __forceinline__ void st_pkt(const void* p, uint32_t a, uint32_t b, uint32_t c, uint32_t d) {
    asm volatile("{\n.reg .b128 t;\nmov.b128 t, {%1,%2,%3,%4};\nst.relaxed.gpu.global.b128 [%0], t;\n}"
                 ::"l"(p), "r"(a), "r"(b), "r"(c), "r"(d) : "memory");
}
__device__ __forceinline__ uint2 ld_pkt8(const void* p) {
    uint2 v;
    asm volatile("{\n.reg .b64 t;\nld.relaxed.gpu.global.b64 t, [%2];\nmov.b64 {%0,%1}, t;\n}" : "=r"(v.x), "=r"(v.y) : "l"(p) : "memory");
    return v;
}
__device__ __forceinline__ void red_cell(const char* p, float a, float b, float c) {
    jitter();
    asm volatile("red.relaxed.gpu.global.add.v4.f32 [%0], {%1,%2,%3,%4};" ::"l"(p), "f"(a), "f"(b), "f"(c), "f"(1.0f) : "memory");
}
#define PRED(n) "{\n.reg .pred p;\nsetp.ne.u32 p, %" #n ", 0;\n"
__device__ __forceinline__ void red_cell2_if(bool on, const char* p, float a, float b, float c) {
    jitter();
    asm volatile(PRED(5) "@p red.relaxed.gpu.global.add.v4.f32 [%0], {%1,%2,%3,%4};\n@p red.relaxed.gpu.global.add.v4.f32 [%0+4096], {%1,%2,%3,%4};\n}"
                 ::"l"(p), "f"(a), "f"(b), "f"(c), "f"(1.0f), "r"((uint32_t)on) : "memory");
}
__device__ __forceinline__ void st_pkt8_if(bool on, const void* p, uint32_t a, uint32_t b) {
    jitter();
    asm volatile(PRED(3) ".reg .b64 t;\nmov.b64 t, {%1,%2};\n@p st.relaxed.gpu.global.b64 [%0], t;\n}" ::"l"(p), "r"(a), "r"(b), "r"((uint32_t)on) : "memory");
}
__device__ __forceinline__ void st_pkt82_if(bool on, const void* p, uint32_t a, uint32_t b) {
    asm volatile(PRED(3) ".reg .b64 t;\nmov.b64 t, {%1,%2};\n@p st.relaxed.gpu.global.b64 [%0], t;\n@p st.relaxed.gpu.global.b64 [%0+4096], t;\n}"
                 ::"l"(p), "r"(a), "r"(b), "r"((uint32_t)on) : "memory");
}
__device__ __forceinline__ void st_pkt2_if(bool on, const void* p, uint32_t a, uint32_t b, uint32_t c, uint32_t d) {
    jitter();
    asm volatile(PRED(5) ".reg .b128 t;\nmov.b128 t, {%1,%2,%3,%4};\n@p st.relaxed.gpu.global.b128 [%0], t;\n@p st.relaxed.gpu.global.b128 [%0+4096], t;\n}"
                 ::"l"(p), "r"(a), "r"(b), "r"(c), "r"(d), "r"((uint32_t)on) : "memory");
}
__device__ __forceinline__ void mbar_arrive_if(bool on, uint32_t a) {
    jitter();
    asm volatile(PRED(1) "@p mbarrier.arrive.shared::cta.b64 _, [%0];\n}" ::"r"(a), "r"((uint32_t)on) : "memory");
}
__device__ __forceinline__ void sts16_if(bool on, uint32_t a, uint32_t v) {
    asm volatile(PRED(2) "@p st.shared.u16 [%0], %1;\n}" ::"r"(a), "h"((unsigned short)v), "r"((uint32_t)on) : "memory");
}
__device__ __forceinline__ void sts32_if(bool on, uint32_t a, uint32_t v) {
    asm volatile(PRED(2) "@p st.shared.u32 [%0], %1;\n}" ::"r"(a), "r"(v), "r"((uint32_t)on) : "memory");
}
__device__ __forceinline__ void sts128_if(bool on, uint32_t a, uint32_t x, uint32_t y, uint32_t z, uint32_t w) {
    jitter();
    asm volatile(PRED(5) "@p st.shared.v4.u32 [%0], {%1,%2,%3,%4};\n}" ::"r"(a), "r"(x), "r"(y), "r"(z), "r"(w), "r"((uint32_t)on) : "memory");
}
__device__ __forceinline__ float fast_rcp(float x) { float r; asm("rcp.approx.ftz.f32 %0, %1;" : "=f"(r) : "f"(x)); return r; }
__device__ __forceinline__ float fast_sqrt(float x) { float r; asm("sqrt.approx.ftz.f32 %0, %1;" : "=f"(r) : "f"(x)); return r; }
__device__ __forceinline__ float fast_ex2(float x) { float r; asm("ex2.approx.ftz.f32 %0, %1;" : "=f"(r) : "f"(x)); return r; }
__device__ __forceinline__ uint32_t pack2(float lo, float hi) {
    uint32_t r;
    asm("cvt.rn.bf16x2.f32 %0, %1, %2;" : "=r"(r) : "f"(hi), "f"(lo));
    return r;
}
__device__ __forceinline__ float bfr(float x) { return __uint_as_float(pack2(0.f, x)); }
__device__ __forceinline__ uint32_t badd2(uint32_t a, uint32_t b) { uint32_t r; asm("add.rn.bf16x2 %0, %1, %2;" : "=r"(r) : "r"(a), "r"(b)); return r; }
__device__ __forceinline__ uint32_t bsub2(uint32_t a, uint32_t b) { uint32_t r; asm("sub.rn.bf16x2 %0, %1, %2;" : "=r"(r) : "r"(a), "r"(b)); return r; }
__device__ __forceinline__ uint32_t bmul2(uint32_t a, uint32_t b) { uint32_t r; asm("mul.rn.bf16x2 %0, %1, %2;" : "=r"(r) : "r"(a), "r"(b)); return r; }
__device__ __forceinline__ float bf_lo(uint32_t w) { return __uint_as_float(w << 16); }
__device__ __forceinline__ float bf_hi(uint32_t w) { return __uint_as_float(w & 0xffff0000u); }
__device__ __forceinline__ float F(uint32_t t) { return __uint_as_float(t); }
__device__ __forceinline__ uint32_t lds16(uint32_t a) { unsigned short h; asm volatile("ld.shared.u16 %0, [%1];" : "=h"(h) : "r"(a) : "memory"); return h; }
__device__ __forceinline__ uint32_t lds32(uint32_t a) { uint32_t v; asm volatile("ld.shared.u32 %0, [%1];" : "=r"(v) : "r"(a) : "memory"); return v; }
__device__ __forceinline__ uint2 lds64(uint32_t a) {
    uint2 v; asm volatile("ld.shared.v2.u32 {%0,%1}, [%2];" : "=r"(v.x), "=r"(v.y) : "r"(a) : "memory"); return v;
}
__device__ __forceinline__ uint4 lds128(uint32_t a) {
    uint4 v; asm volatile("ld.shared.v4.u32 {%0,%1,%2,%3}, [%4];" : "=r"(v.x), "=r"(v.y), "=r"(v.z), "=r"(v.w) : "r"(a) : "memory"); return v;
}
__device__ __forceinline__ float sum8(const uint4& u, const uint4& v) {
    return ((F(u.x) + F(u.y)) + (F(u.z) + F(u.w))) + ((F(v.x) + F(v.y)) + (F(v.z) + F(v.w)));
}
__device__ __forceinline__ void sts16(uint32_t a, uint32_t v) { asm volatile("st.shared.u16 [%0], %1;" ::"r"(a), "h"((unsigned short)v) : "memory"); }
__device__ __forceinline__ void sts32(uint32_t a, uint32_t v) { asm volatile("st.shared.u32 [%0], %1;" ::"r"(a), "r"(v) : "memory"); }
__device__ __forceinline__ void stsf(uint32_t a, float v) { asm volatile("st.shared.f32 [%0], %1;" ::"r"(a), "f"(v) : "memory"); }
__device__ __forceinline__ void stsf2(uint32_t a, float x, float y) { asm volatile("st.shared.v2.f32 [%0], {%1,%2};" ::"r"(a), "f"(x), "f"(y) : "memory"); }
__device__ __forceinline__ void stsf4(uint32_t a, float x, float y, float z, float w) {
    asm volatile("st.shared.v4.f32 [%0], {%1,%2,%3,%4};" ::"r"(a), "f"(x), "f"(y), "f"(z), "f"(w) : "memory");
}
template <int ID, int N> __device__ __forceinline__ void bar_sync() { jitter(); asm volatile("bar.sync %0, %1;" ::"n"(ID), "n"(N) : "memory"); jitter(); }
template <int ID, int N> __device__ __forceinline__ void bar_arrive() { jitter(); asm volatile("bar.arrive %0, %1;" ::"n"(ID), "n"(N) : "memory"); jitter(); }
__device__ __forceinline__ void fence_async() { asm volatile("fence.proxy.async.shared::cta;" ::: "memory"); }
__device__ __forceinline__ float shx(float v, int m) { return __shfl_xor_sync(0xffffffffu, v, m); }
__device__ __forceinline__ float shi(float v, int l) { return __shfl_sync(0xffffffffu, v, l); }
__device__ __forceinline__ uint32_t shi(uint32_t v, int l) { return __shfl_sync(0xffffffffu, v, l); }
__device__ __forceinline__ uint32_t opaque(uint32_t x) { asm volatile("mov.u32 %0, %0;" : "+r"(x)); return x; }
__device__ __forceinline__ const char* opaque(const char* x) { asm volatile("mov.u64 %0, %0;" : "+l"(x)); return x; }
constexpr float LOG2E = 1.4426950408889634f, SCALE = 0.07216878364870322f;

#define TRACE(idx) do {} while (0)
#define TRACES(slot) do {} while (0)

__device__ __forceinline__ uint32_t probe_near(const Params& p, int w, int lane) {
    const int cta = cta_id();
    const char* pr = p.scr + SCR_O + head_off(cta >> 2) + 2048 + w * 256 + (cta & 3) * 64;
    st_pkt2_if(lane < 4, pr + lane * 16, 0, 0, 0, 0);
    uint32_t best0 = ~0u, best1 = ~0u;
#pragma unroll 1
    for (int i = w & 1; i < 6 + (w & 1); i++) {
        uint32_t c = clk32(), v = 0;
        if (lane == 0) asm volatile("atom.relaxed.gpu.global.add.u32 %0, [%1], 1;" : "=r"(v) : "l"(pr + (i & 1) * HALF) : "memory");
        c += __shfl_sync(0xffffffffu, v, 0) >> 16;
        c = clk32() - c;
        if (i & 1) best1 = min(best1, c); else best0 = min(best0, c);
    }
    return min(best0, 0xffffu) | min(best1, 0xffffu) << 16;
}
__device__ __forceinline__ uint32_t near_half() {
    const uint4 a = lds128(SM_NEAR), b = lds128(SM_NEAR + 16);
    const uint32_t m = __vminu2(__vminu2(__vminu2(a.x, a.y), __vminu2(a.z, a.w)), __vminu2(__vminu2(b.x, b.y), __vminu2(b.z, b.w)));
    return head_near(cta_id() >> 2, ((m & 0xffffu) > m >> 16) != (CFG(FLIP) != 0) ? HALF : 0);
}

__device__ __forceinline__ int kv_group(int k, int t) {
    const int cta = cta_id();
    return ((k * NHEAD + (cta >> 2)) * SK + (SK - WIN) + (cta & 3) * 32 + t * 128) / 8;
}
__device__ __forceinline__ uint32_t phase_ns() { return (((cta_id() >> 2) * 13) & 31) * CFG(STAG) / 32; }

__device__ __forceinline__ void ln_fast(float s, float q, float& mean, float& rstd) {
    mean = s * (1.f / DM);
    asm("rsqrt.approx.ftz.f32 %0, %1;" : "=f"(rstd) : "f"(fmaxf(fmaf(-mean, mean, fmaf(q, 1.f / DM, 1e-5f)), 1e-5f)));
}
__device__ __forceinline__ void q_role(const Params& p, int lane) {
    const int cta = cta_id();
    mbar_wait(bar_at(B_EP), 0);
    const uint32_t epoch = lds32(SM_EPOCH), near = head_near(cta >> 2, near_half());
    auto sums = [&](float& S0, float& S1) {
        bar_sync<3, 288>();
        const uint32_t ra = SM_PQ + lane * 16;
        S0 = sum8(lds128(ra), lds128(ra + 1024)); S1 = sum8(lds128(ra + 512), lds128(ra + 1536));
    };
    float cs0, cs1;
    {
        uint32_t q0 = 0, q1 = 0, q2 = 0, q3 = 0;
#pragma unroll 1
        for (int r = 0; r < NB; r++) {
            sums(cs0, cs1);
            bar_arrive<7, 288>();
            q0 = q1; q1 = q2; q2 = q3; q3 = pack2(cs0, cs1);
        }
        const uint32_t t0 = shi(q3, 3 * lane - 72), t1 = shi(q3, 3 * lane - 71), t2 = shi(q3, 3 * lane - 70), tag = epoch << 8 | 0x40;
        const char* box = p.scr + SCR_O + head_off(cta >> 2) + 2048 + (lane >> 2) * 256 + (lane & 3) * 16;
        st_pkt2_if(true, box + (cta & 3) * 64, lane < 24 ? q0 : t0, lane < 24 ? q1 : t1, lane < 24 ? q2 : t2, tag);
        const uint32_t qd = SM_Q + (lane < 24 ? lane * 4 : 3 * 384 + (lane - 24) * 12), step = lane < 24 ? 384 : 4;
#pragma unroll 1
        for (int j = 0; j < 4; j++) {
            uint4 v;
            SPIN_DECL;
            do {
                __nanosleep(200);
                v = ld_pkt(box + near + j * 64);
                SPIN_CHECK(j);
            } while (__any_sync(0xffffffffu, v.w != tag));
            sts32(qd + j * 96, v.x); sts32(qd + j * 96 + step, v.y); sts32(qd + j * 96 + 2 * step, v.z);
        }
        mbar_arrive(bar_at(B_QR));
    }
    sums(cs0, cs1);
    bar_arrive<7, 288>();
    const char* const src = p.scr + SCR_Q + head_off(cta >> 2) + lane * 8 + near;
    const char* const dst = src + (cta & 3) * 192;
    const uint32_t qd = SM_Q + NB * 384 + lane * 4;
    st_pkt82_if(lane < 24, dst - near, 0, 0);
#pragma unroll 1
    for (int k = 0; k < NB; k++) {
        float S0, S1, mean, rstd;
        sums(S0, S1);
        ln_fast(shi(S1, 24), shi(S0, 24), mean, rstd);
        const uint32_t qq = pack2(fmaf(-mean, cs0, S0) * rstd, fmaf(-mean, cs1, S1) * rstd), tag = epoch * NB + k;
        st_pkt8_if(lane < 24, dst + ((int)HALF - 2 * (int)near), qq, tag);
        st_pkt8_if(lane < 24, dst, qq, tag);
        TRACES(k * 12 + 5);
        uint2 a, b, c;
        SPIN_DECL;
        do {
            a = ld_pkt8(src); b = ld_pkt8(src + 256); c = ld_pkt8(src + 512);
            SPIN_CHECK(k);
            sts32(qd, a.x); sts32(qd + 128, b.x); sts32(qd + 256, c.x);
        } while (__any_sync(0xffffffffu, a.y != tag || b.y != tag || c.y != tag));
        mbar_arrive(bar_at(B_QR));
    }
}

struct Maps { CUtensorMap k, v, q, o, g, u; };
__device__ __forceinline__ void load_role(const Params& p, const CUtensorMap* tmKV, int lane, uint32_t t0) {
    const int cta = cta_id();
    t0 += phase_ns();
#pragma unroll 1
    for (int i = 1; i < 5; i++) {
        wait_ns(t0 + i * CFG(TICK0));
        if (elect_one()) l2_prefetch(p.wq + (size_t)(128 * i + cta) * 12288, 12288);
        TRACE(230 + i);
    }
    uint32_t plan[2];
#pragma unroll
    for (int i = 0; i < 2; i++) {
        const int j = lane + 32 * i, k = j >> 4, t = j & 15, u = t >> 1, jw = j - CFG(WIN);
        const int sb = k == 0 ? B_WC + (t >= 8) + (t >= 14) : t >= 12 ? B_RK + u - 5 : t >= 4 ? B_RR + t - 4 : t >= 2 ? B_RP : k > 1 ? B_RK + 3 : B_RR + t;
        const uint32_t sw = sb * 8 | (j < 18 ? 0 : (t >= 12 || u == 1 ? k - 1 : k) & 1) << 9;
        plan[i] = sw | (jw < 0 ? sw : (B_F1 + (jw & 15)) * 8 | ((jw >> 4) & 1) << 9) << 10 |
                  (slot_at(slots(k), t < 8 ? pass_nibble(k, u) : u) * 2 + (t & 1)) << 20 | (t < 10 && j >= 8 && j < 56) << 25;
    }
    bar_sync<6, 64>();
    wait_ns(t0 + kb_ns(60));
    if (elect_one()) bulk_load(ST_WD, p.wd + cta * 15360, 15360, bar_at(B_W));
    TRACE(235);
#pragma unroll 1
    for (int i = 0; i < 5; i++) {
        wait_ns(t0 + kb_ns(75) + i * kb_ns(6));
        if (elect_one()) { l2_prefetch(p.wg + (128 * i + cta) * 3072, 3072); l2_prefetch(p.wu + (128 * i + cta) * 3072, 3072); }
    }
#pragma unroll 1
    for (int i = 0; i < 6; i++) {
        wait_ns(t0 + kb_ns(105) + min(i, 4) * kb_ns(10));
        if (elect_one()) l2_prefetch(p.wo + (size_t)((cta >> 2) * DH + 32 * i + 8 * (cta & 3)) * 1280, 10240);
    }
    t0 += batch_ns(0);
    int jp = 0, shift = 0;
    uint32_t earliest = t0;
    auto requested = [&](uint32_t now) {
        shift = max(shift, (int)(now - t0) - (jp < 12 ? CFG(LMAX0) : CFG(LMAX)));
        TRACE(128 + jp);
        t0 += tick_ns(++jp);
    };
    const int grp0 = kv_group(0, 0);
    auto group = [&](int j) { return grp0 + (j >> 4) * (NHEAD * SK / 8) + (j & 7) * 16; };
#pragma unroll 1
    for (int j = 0; j < 16 * NB; j++) {
        const uint32_t pl = __shfl_sync(0xffffffffu, j & 32 ? plan[1] : plan[0], j);
        const int jmax = min(j + CFG(PMAX), 16 * NB);
        jitter();
        uint32_t now;
        SPIN_DECL;
        while (true) {
            const bool ok = mbar_test2(SM_BAR + (pl & 511), (pl >> 9) & 1, SM_BAR + ((pl >> 10) & 511), (pl >> 19) & 1);
            now = now_ns();
            const int late = now - t0 - shift;
            if (ok && (jp > j ? (int)(now - earliest) : late) >= 0) break;
            if (late >= (jp > j ? 0 : CFG(PGRACE)) && jp < jmax) {
                if (elect_one())
                    asm volatile("cp.async.bulk.prefetch.tensor.4d.L2.global [%0, {%1, %1, %1, %2}];" ::"l"(tmKV + ((jp >> 3) & 1)), "r"(0), "r"(group(jp)) : "memory");
                requested(now);
            }
            SPIN_CHECK(j);
        }
        if (elect_one()) {
            mbar_expect_tx(bar_at(B_F1 + (j & 15)), TILE);
            tma_tile(SB + ((pl >> 20) & 31) * TILE, tmKV + ((j >> 3) & 1), group(j), bar_at(B_F1 + (j & 15)), pl >> 25 ? POL_NORMAL : POL_FIRST);
        }
        TRACE(256 + j);
        if ((j & 15) == 15) TRACES(88 + (j >> 4));
        earliest = now + CFG(VSTEP);
        if (jp == j) requested(now);
        const int jl = j - 3;
        if (jl >= 8 && !mbar_test2(bar_at(B_F1 + (jl & 15)), (jl >> 4) & 1, bar_at(B_F1 + (jl & 15)), (jl >> 4) & 1)) shift += CFG(UP);
    }
}

__device__ __forceinline__ void reload_role(const Params& p, const Maps* tm, uint32_t t0) {
    const CUtensorMap* const tmK = &tm->k;
    const CUtensorMap* const tmV = &tm->v;
    const int cta = cta_id();
    t0 += CFG(TICK0) + CFG(WLAG) + phase_ns();
#pragma unroll 1
    for (int i = 0; i < 5; i++) {
        wait_ns(t0 + i * CFG(TICK0));
        if (elect_one()) tma2d(ST_WQ + i * 12288, &tm->q, 48 * cta, 128 * i, bar_at(B_W));
        TRACE(240 + i);
        if (i == 1) bar_sync<5, 480>();
    }
#pragma unroll 1
    for (int i = 0, o = 0; i < 10;) {
        const uint32_t now = now_ns() - t0;
        if (o < 6 && (int)now >= kb_ns(105) + o * kb_ns(10)) {
            if (elect_one()) tma2d(ST_WO + o * 10240, &tm->o, 160 * (cta & 3), (cta >> 2) * DH + 32 * o, bar_at(B_W + 1));
            o++;
        } else if ((int)now >= kb_ns(77) + i * CFG(GSTEP) && (i < 9 || o == 6)) {
            if (elect_one()) tma2d(ST_WG + (i & 1) * 20480 + (i >> 1) * 4096, i & 1 ? &tm->u : &tm->g, (12 * cta) & ~7, 128 * (i >> 1), bar_at(B_W + 2));
            i++;
        }
    }
#pragma unroll 1
    for (int k = 0; k < NB - 1; k++) {
        mbar_wait(bar_at(B_RK), k & 1);
        if (elect_one()) {
            const uint32_t dst = SB + slot_at(slots(k), 0) * PAIR;
            mbar_expect_tx(bar_at(B_FL), PAIR);
            tma_tile(dst, tmV, kv_group(k, 0), bar_at(B_FL), POL_FIRST);
            tma_tile(dst + TILE, tmV, kv_group(k, 1), bar_at(B_FL), POL_FIRST);
        }
        mbar_wait(bar_at(k == NB - 2 ? B_RK + 3 : B_RV), k & 1);
        uint32_t due = now_ns();
        if (elect_one()) mbar_expect_tx(bar_at(B_F3), 4 * PAIR);
#pragma unroll 1
        for (int t = 0; t < 8; t++) {
            if (t == 2) mbar_wait(bar_at(B_RV), k & 1);
            wait_ns(due);
            due += k == NB - 2 ? CFG(RSTEP3) : CFG(RSTEP);
            if (elect_one())
                tma_tile(SB + slot_at(slots(k + 1), t >> 1) * PAIR + (t & 1) * TILE, tmK, kv_group(k + 1, t), bar_at(B_F3), POL_FIRST);
        }
        TRACE(121 + k);
    }
}

__device__ __forceinline__ void zero_role(const Params& p, int lane, uint32_t t0) {
    const int cta = cta_id();
    unsigned ticket = 0;
    if (lane == 0) ticket = atomicAdd(&g_epoch, 1u);
    const uint32_t epoch = __shfl_sync(0xffffffffu, ticket, 0) / NCTA + 1;
    if (lane == 0) { sts32(SM_EPOCH, epoch); mbar_arrive(bar_at(B_EP)); }
    mbar_wait(bar_at(B_EP), 0);
#pragma unroll 1
    for (int k = 0; k < NB + 2; k++) {
        lane = opaque(lane);
        const int cl = 2 * (cta & 15) + (lane & 1);
        const int col = 80 * (cta >> 4) + (cl & 2 ? 48 : 0) + (cl >> 2) + (cl & 1 ? 8 : 0);
        const char* own = p.scr + (cl >> 2) * 256 + (cl & 3) * 16;
        uint32_t v0 = 0, v1 = 0, v2 = 0;
        if (lane < 4 && k < NB) {
            const unsigned short* xp = p.x + k * DM + col;
            v0 = __ldg(xp) << 16; v1 = __ldg(xp + 16) << 16; v2 = cl & 2 ? 0 : __ldg(xp + 32) << 16;
        }
        uint4 r;
        if (k == 1) mbar_wait(bar_at(B_RK), 0);
        if (k > 1) {
            mbar_wait(bar_at(B_FIN), k & 1);
            r = lds128(SM_FIN + (lane & 1) * 16);
        }
        if (k < NB) {
            const int lg = lane >> 3, ty = (lane & 7) >> 1;
            const char* dst = own + acc_off((k - (lg >> 1)) & 3, lg != 0, cta >> 4) + ty * HALF;
            wait_ns(t0 + batch_ns(k) + CFG(ZTILE) * CFG(TICK0));
            if (lg == 0 || (lg == 1 && (ty < 2 || k == NB - 1)) || (lg == 2 && k > 0 && ty > 1)) {
                st_pkt(dst, v0, v1, v2, ~0u);
                asm volatile("atom.relaxed.gpu.global.exch.b32 %0, [%1+12], %2;" : "=r"(v0) : "l"(dst), "r"(lane < 4 ? 0x3f800000u : 0u) : "memory");
                v0 = ~v0;
            }
            if (__any_sync(0xffffffffu, v0 != 0)) __trap();
            const char* cnt = p.scr + SCR_COUNT;
            if (lane < 2) asm volatile("red.relaxed.gpu.global.add.u32 [%0], 1;" ::"l"(cnt + lane * HALF) : "memory");
            const uint32_t target = ((epoch - 1) * NB + k + 1) * NCTA;
            cnt += near_half();
            SPIN_DECL;
            uint32_t v;
            do {
                __nanosleep(100);
                asm volatile("ld.relaxed.gpu.global.u32 %0, [%1];" : "=r"(v) : "l"(cnt) : "memory");
                SPIN_CHECK(v);
            } while (__any_sync(0xffffffffu, (int)(v - target) < 0));
        }
        __syncwarp();
        if (lane == 0) mbar_arrive(bar_at(B_Z));
        if (k > 1) {
            const int b = k - 2;
            const char* src = own + acc_off(b, 1, cta >> 4) + (2 + ((lane >> 1) & 1)) * HALF;
            unsigned short* o = p.out + b * DM + col + (lane >> 2) * 16;
            const bool on = !(lane & 2) && lane < (cl & 2 ? 8 : 12);
            wait_clk(clk32() + CFG(DLY_F));
            float cnt;
            SPIN_DECL;
            do {
                const uint4 v = ld_pkt(src);
                SPIN_CHECK(k);
                cnt = F(v.w) + shx(F(v.w), 2);
                const float y0 = F(v.x) + shx(F(v.x), 2), y1 = F(v.y) + shx(F(v.y), 2), y2 = F(v.z) + shx(F(v.z), 2);
                const uint32_t x01 = badd2(r.x, badd2(r.y, bmul2(pack2(y0, y1), r.w)));
                const uint32_t x2 = badd2(r.z, badd2(r.z >> 16, bmul2(pack2(y2, 0.f), r.w)));
                if (cnt == NCTA && on) *o = lane < 4 ? x01 : lane < 8 ? x01 >> 16 : x2;
            } while (__any_sync(0xffffffffu, cnt != NCTA));
            TRACES((2 * b + 1) * 6 + 4);
        }
    }
}

__host__ __device__ constexpr uint32_t desc_lo(uint32_t addr) { return ((addr & 0x3FFFFu) >> 4) | (1u << 16); }
constexpr uint32_t DESC_HI_TILE = (3072u >> 4) | (1u << 30);
constexpr uint32_t DESC_HI_VEC = 1u;
template <int TA, int AOFF, int BOFF>
__device__ __forceinline__ void wgmma_n8(float (&d)[4], uint32_t alo, uint32_t blo, int accumulate) {
    asm volatile("{\n.reg .pred p;\n.reg .b32 a, b;\n.reg .b64 da, db;\nsetp.ne.b32 p, %6, 0;\n"
                 "add.u32 a, %4, %8;\nadd.u32 b, %5, %9;\nmov.b64 da, {a, %10};\nmov.b64 db, {b, %11};\n"
                 "wgmma.mma_async.sync.aligned.m64n8k16.f32.bf16.bf16 {%0,%1,%2,%3}, da, db, p, 1, 1, %7, 0;\n}"
                 : "+f"(d[0]), "+f"(d[1]), "+f"(d[2]), "+f"(d[3])
                 : "r"(alo), "r"(blo), "r"(accumulate), "n"(TA), "n"(AOFF >> 4), "n"(BOFF >> 4), "n"(DESC_HI_TILE), "n"(DESC_HI_VEC));
}
template <int KS, int END>
__device__ __forceinline__ void qk_steps(float (&d)[4], uint32_t alo, uint32_t blo) {
    if constexpr (KS < END) {
        wgmma_n8<0, (KS >> 2) * 1024 + (KS & 3) * 32, KS * 32>(d, alo, blo, KS > 0);
        qk_steps<KS + 1, END>(d, alo, blo);
    }
}
__device__ __forceinline__ void pv_steps(float (&e)[3][4], uint32_t alo, uint32_t blo, int acc) {
    wgmma_n8<1, 0, 0>(e[0], alo, blo, acc); wgmma_n8<1, 1024, 0>(e[1], alo, blo, acc); wgmma_n8<1, 2048, 0>(e[2], alo, blo, acc);
    wgmma_n8<1, 6144, 32>(e[0], alo, blo, 1); wgmma_n8<1, 7168, 32>(e[1], alo, blo, 1); wgmma_n8<1, 8192, 32>(e[2], alo, blo, 1);
}
__device__ __forceinline__ void wg_fence() { asm volatile("wgmma.fence.sync.aligned;" ::: "memory"); }
__device__ __forceinline__ void wg_commit() { asm volatile("wgmma.commit_group.sync.aligned;" ::: "memory"); }
template <int N> __device__ __forceinline__ void wg_wait() { asm volatile("wgmma.wait_group.sync.aligned %0;" ::"n"(N) : "memory"); }
__device__ __forceinline__ void acc_ready(float (&d)[4]) { asm volatile("" : "+f"(d[0]), "+f"(d[1]), "+f"(d[2]), "+f"(d[3]) :: "memory"); }
__device__ __forceinline__ uint32_t score_pair(float (&d)[4]) {
    acc_ready(d);
    const uint32_t r = pack2(d[0], d[2]);
    return pack2(bf_lo(r) * SCALE, bf_hi(r) * SCALE);
}

__device__ __forceinline__ void attention_role(const Params& p, int w, int lane) {
    const int cta = cta_id(), t4 = lane & 3, g = lane >> 2;
    mbar_wait(bar_at(B_EP), 0);
    const uint32_t tag0 = lds32(SM_EPOCH) * NB;
    const char* const odst = p.scr + SCR_O + head_off(cta >> 2) + (2 * w + (g >> 2)) * 256 + (cta & 3) * 64 + (g & 3) * 16;
    const uint32_t pdst = SM_P + ((t4 + 3) & 3) * PSTR + (16 * w + g) * 2;
    auto softmax = [&](uint32_t& sc, int ps) -> uint32_t {
        const float s0 = bf_lo(sc), s1 = bf_hi(sc);
        int key = __float_as_int(fmaxf(s0, s1));
        key ^= (key >> 31) & 0x7fffffff;
        key = __reduce_max_sync(0xffffffffu, key);
        sts32(SM_MAX + w * 4, key);
        bar_sync<4, 128>();
        const uint4 mx = lds128(SM_MAX);
        key = max(max((int)mx.x, (int)mx.y), max((int)mx.z, (int)mx.w));
        key ^= (key >> 31) & 0x7fffffff;
        const float mb = __int_as_float(key) * LOG2E;
        const uint32_t pp = pack2(fast_ex2(fmaf(s0, LOG2E, -mb)), fast_ex2(fmaf(s1, LOG2E, -mb)));
        sts16(pdst + ps * 4 * PSTR, pp); sts16(pdst + ps * 4 * PSTR + 16, pp >> 16);
        fence_async();
        bar_sync<4, 128>();
        sc = pp;
        return key;
    };
    auto put_sum = [&](uint32_t pp, int ps) {
        uint32_t fs;
        asm volatile("redux.sync.add.u32 %0, %1, 0xffffffff;" : "=r"(fs) : "r"(__float2uint_rn((bf_lo(pp) + bf_hi(pp)) * 8388608.f)) : "memory");
        sts32(SM_SUM + ps * 16 + w * 4, fs);
    };
    auto aux_word = [&](uint32_t mx, const uint4& u, int k) {
        const float l = __uint2float_rn((u.x + u.y) + (u.z + u.w)) * (1.f / 8388608.f);
        return (g < 4 ? mx : (__float_as_uint(l) + 0x80u) & 0xffffff00u) | ((tag0 + k) & 0x7fu) | 0x80u;
    };
    auto send = [&](float (&e)[3][4], uint32_t aux, int ps) {
        acc_ready(e[0]); acc_ready(e[1]); acc_ready(e[2]);
        const uint32_t o0 = pack2(e[0][0], e[0][2]), o1 = pack2(e[1][0], e[1][2]), o2 = pack2(e[2][0], e[2][2]);
        st_pkt2_if(t4 == 0, odst + ps * 2048, o0, o1, o2, aux);
        mbar_arrive_if(lane == 0, bar_at(ps ? B_RV : B_PS));
    };
    mbar_wait(bar_at(B_QR), 0);
    TRACES(73);
#pragma unroll 1
    for (int it = 0; it <= NB; it++) {
        uint32_t m1 = 0;
        if (it < NB) {
            const uint32_t tab = slots(it);
            const uint32_t ka = SB + (2 * w + ((lane >> 3) & 1)) * 3072 + (lane & 7) * 128 + (((lane >> 4) ^ (lane & 7)) << 4);
            const uint32_t qa = SM_Q + it * 384 + (lane >> 3) * 16;
            uint32_t sc = 0;
#pragma unroll 1
            for (int u = 0; u < 4; u++) {
                const uint32_t base = ka + slot_at(tab, pass_nibble(it, u)) * PAIR;
                mbar_wait(bar_at(B_F1 + 2 * u + (w >> 1)), it & 1);
                float d0[4] = {}, d1[4] = {};
#pragma unroll
                for (int c = 0; c < 6; c++) {
                    uint32_t a0[4], a1[4], b[4];
                    ldsm4(b, qa + c * 64);
                    ldsm4(a0, (base ^ ((c & 1) * 64)) + (c >> 1) * 1024);
                    ldsm4(a1, (base ^ ((c & 1) * 64 + 32)) + (c >> 1) * 1024);
                    mma16816(d0, a0[0], a0[1], a0[2], a0[3], b[0], b[1]);
                    mma16816(d1, a1[0], a1[1], a1[2], a1[3], b[2], b[3]);
                }
                const uint32_t r = pack2(d0[0] + d1[0], d0[2] + d1[2]);
                mbar_arrive_if(lane == 0, bar_at(B_RR + 2 * u + (w >> 1)));
                if (t4 == ((u + 1) & 3)) sc = pack2(bf_lo(r) * SCALE, bf_hi(r) * SCALE);
            }
            m1 = softmax(sc, 0);
            put_sum(sc, 0);
        }
        if (it > 0) {
            const int k = it - 1;
            const uint32_t tab = slots(k);
            const uint32_t v0 = slot_at(tab, k < NB - 1 ? 0 : 4);
            TRACES(48 + k * 6);
            if (k > 0) mbar_wait(bar_at(B_F3), it & 1);
            mbar_wait(bar_at(B_QR), it & 1);
            fence_async();
            TRACES(49 + k * 6);
            float d[4][4] = {};
            const bool busy = k < NB - 1;
#pragma unroll
            for (int u = 0; u < 4; u++) {
                const uint32_t alo = desc_lo(SB) + slot_at(tab, u) * (PAIR >> 4), blo = desc_lo(SM_Q + 4 * 384);
                wg_fence();
                qk_steps<0, 6>(d[u], alo, blo);
                wg_commit();
                if (busy) {
                    wg_wait<1>();
                    if (u > 0) mbar_arrive_if(lane == 0, bar_at(B_RK + u - 1));
                }
                wg_fence();
                qk_steps<6, 12>(d[u], alo, blo);
                wg_commit();
                if (u < 3 && busy) wg_wait<1>();
            }
            wg_wait<2>();
            uint32_t sc = shi(score_pair(d[0]), lane & 28), s = shi(score_pair(d[1]), lane & 28);
            if (t4 == 2) sc = s;
            s = shi(score_pair(d[2]), lane & 28);
            if (t4 == 3) sc = s;
            wg_wait<0>();
            s = score_pair(d[3]);
            if (t4 == 0) sc = s;
            mbar_arrive_if(lane == 0, bar_at(B_RK + 3));
            TRACES(50 + k * 6);
            const uint32_t m2 = softmax(sc, 1);
            TRACES(51 + k * 6);
            float e[3][4] = {};
#pragma unroll
            for (int t = 0; t < 8; t++) {
                const int pr = ((t >> 1) + 1) & 3;
                if (t == 6 && k < NB - 1) mbar_wait(bar_at(B_FL), k & 1);
                wg_fence();
                pv_steps(e, desc_lo(SB + (t & 1) * TILE) + (pr ? slot_at(tab, 4 + pr) : v0) * (PAIR >> 4), desc_lo(SM_P + (4 + pr) * PSTR + (t & 1) * 64), t > 0);
                wg_commit();
                if (t < 7 && busy) wg_wait<1>();
                if (t == 1) put_sum(sc, 1);
            }
            bar_sync<4, 128>();
            const uint32_t aux = opaque(aux_word(m2, lds128(SM_SUM + 16), k));
            wg_wait<0>();
            send(e, aux, 1);
            TRACES(52 + k * 6);
        }
        if (it < NB) {
            const uint32_t tab = slots(it);
            if (it == 0) st_pkt2_if(t4 == 0, odst, 0, 0, 0, 0);
            bar_sync<4, 128>();
            const uint32_t aux = opaque(aux_word(m1, lds128(SM_SUM), it));
            float e[3][4] = {};
#pragma unroll 1
            for (int u = 0; u < 4; u++) {
                const uint32_t alo = desc_lo(SB) + slot_at(tab, 4 + u) * (PAIR >> 4), blo = desc_lo(SM_P) + u * (PSTR >> 4);
                mbar_wait(bar_at(B_F1 + 8 + 2 * u), it & 1);
                wg_fence();
                pv_steps(e, alo, blo, u > 0);
                wg_commit();
                wg_wait<1>();
                if (u == 1) mbar_arrive_if(lane == 0, bar_at(B_RP));
                mbar_wait(bar_at(B_F1 + 9 + 2 * u), it & 1);
                wg_fence();
                pv_steps(e, alo + (TILE >> 4), blo + 4, 1);
                wg_commit();
                wg_wait<1>();
            }
            wg_wait<0>();
            send(e, aux, 0);
            TRACES(53 + it * 6);
        }
    }
}

__device__ __forceinline__ void ln_finish(float s, float q, float& mean_b, float& rden) {
    const float mean = s * (1.f / DM);
    const float var = fmaxf(fmaf(q, 1.f / DM, -mean * mean), 0.f);
    mean_b = bfr(mean);
    rden = fast_rcp(bfr(fast_sqrt(bfr(bfr(var) + 1e-5f))));
}
__device__ __forceinline__ uint32_t ln_apply(uint32_t w, float mean_b, float rden) {
    const uint32_t d = bsub2(w, __byte_perm(__float_as_uint(mean_b), 0, 0x3232));
    return pack2(bf_lo(d) * rden, bf_hi(d) * rden);
}
__device__ __forceinline__ void put_x(uint32_t x01, uint32_t x2, uint32_t wa, bool e2) {
    jitter();
    sts16(wa, x01); sts16(wa + 8, x01 >> 16);
    sts16_if(!e2, wa + 16, x2);
}
__device__ __forceinline__ void get_x(uint32_t (&b)[10], uint32_t ra) {
    __syncwarp();
    const uint4 u = lds128(ra), v = lds128(ra + 16);
    const uint2 z = lds64(ra + 32);
    b[0] = u.x; b[1] = u.y; b[2] = u.z; b[3] = u.w; b[4] = v.x; b[5] = v.y; b[6] = v.z; b[7] = v.w; b[8] = z.x; b[9] = z.y;
}
__device__ __forceinline__ float fold(float a, float b, bool sel, int m) { return (sel ? b : a) + shx(sel ? a : b, m); }

__device__ __forceinline__ void chain_role(const Params& p, int w, int lane) {
    const int cta = cta_id(), h = cta >> 2, s = cta & 3;
    const int g = lane >> 2, t4 = lane & 3;
    const bool e1 = t4 & 1, e2 = t4 & 2;
    uint32_t wq[5][3][4], wo[3][5][4], wg[5][4], wh[5][2], wd[4][4];
    const int col0 = 80 * w + (e2 ? 48 : 0) + g + (e1 ? 8 : 0);
    const uint32_t xw = opaque(SM_X + w * 384 + 48 * (g >> 1) + (e2 ? 24 : 0) + (e1 ? 4 : 0) + 2 * (g & 1));
    const uint32_t xr = opaque(g == 1 ? SM_ONES : SM_X + w * 384 + (g == 3 ? 192 : 0) + 48 * t4);
    TRACES(75);
    sts32_if(lane < 12, SM_ONES + lane * 4, 0x3f803f80u);
    uint32_t zero = lane >> 5;
    const int mi = lane >> 3, mr = lane & 7;
    mbar_wait(bar_at(B_W), 0);
    TRACES(74);
    sts16(xw + 192, lds16(ST_X + 5120 + col0 * 2)); sts16(xw + 200, lds16(ST_X + 5120 + col0 * 2 + 32));
    sts16_if(!e2, xw + 208, lds16(ST_X + 5120 + col0 * 2 + 64));
#pragma unroll
    for (int i = 0; i < 5; i++)
#pragma unroll
        for (int mt = 0; mt < 3; mt++) ldsm4t(wq[i][mt], ST_WQ + (80 * w + 16 * i + mr + 8 * (mi >> 1)) * 96 + 32 * mt + 16 * (mi & 1), zero);
    const bool odd = cta & 1;
    const uint32_t lo = ST_WD + (mr + (odd ? 4 : 0)) * 1280 + 160 * w + 16 * (mi & 1);
    const uint32_t hi = ST_WD + ((mr & 3) + (odd ? 0 : 8)) * 1280 + 160 * w + 16 * (mi & 1);
    ldsm4t(wd[0], lo + 96 * (mi >> 1), zero);
    ldsm4t(wd[1], lo + 96 * (mi >> 1) + 32, zero);
    ldsm4t(wd[2], (mi < 2 ? lo : hi) + 64, zero);
    ldsm4t(wd[3], hi + 32 * (mi >> 1) + 96 * (mr >> 2), zero);
    fence_async();
    __syncwarp();
    mbar_arrive_if(lane == 0, bar_at(B_WC));
    mbar_wait(bar_at(B_EP), 0);
    const uint32_t near = __shfl_sync(0xffffffffu, near_half(), 0);
    uint32_t x01 = 0, x2 = 0, nx01 = 0, nx2 = 0;
#pragma unroll 1
    for (int n = -5; n < NROUND; n++) {
        const bool last = (ORD_LAST >> (n & 15)) & 1, head = !((ORD_NO_HEAD >> (n & 15)) & 1);
        const int k = (ORD_BATCH >> (2 * (n & 15))) & 3;
        if (n > -5 && n <= 0) bar_sync<7, 288>();
        else if (!last) bar_sync<2, 256>();
        TRACES(n <= 0 ? 83 + n : 95);
        const char* const slice = p.scr + acc_off(k, last, w);
        const char* const cell = opaque(slice + g * 256 + t4 * 16);
        if (n < -1) {
            const uint32_t xa = ST_X + (n + 5) * 1280, ln = opaque(lane);
            const int col0 = 80 * w + (ln & 2 ? 48 : 0) + (ln >> 2) + (ln & 1 ? 8 : 0);
            float sm = 0.f, sq = 0.f;
#pragma unroll
            for (int i = 0; i < 5; i++) {
                const uint2 c = lds64(xa + i * 256 + ln * 8);
                sm += (bf_lo(c.x) + bf_hi(c.x)) + (bf_lo(c.y) + bf_hi(c.y));
                sq = fmaf(bf_lo(c.x), bf_lo(c.x), fmaf(bf_hi(c.x), bf_hi(c.x), fmaf(bf_lo(c.y), bf_lo(c.y), fmaf(bf_hi(c.y), bf_hi(c.y), sq))));
            }
            x01 = lds16(xa + col0 * 2) | lds16(xa + col0 * 2 + 32) << 16;
            x2 = lds16(xa + col0 * 2 + 64);
#pragma unroll
            for (int o = 16; o; o >>= 1) { sm += shx(sm, o); sq += shx(sq, o); }
            float mean_b, rden;
            ln_finish(sm, sq, mean_b, rden);
            x01 = ln_apply(x01, mean_b, rden);
            x2 = ln_apply(x2, mean_b, rden);
            put_x(x01, x2, xw, e2);
        } else {
            if (n >= 0 && head) {
                if (!last || n == NROUND - 1) mbar_wait(bar_at(B_Z), (k + last) & 1);
                const char* src = p.scr + SCR_O + head_off(h) + head_near(h, near) + last * 2048 + (w & 6) * 256 + (lane & 15) * 16;
                const uint32_t tag = (lds32(SM_EPOCH) * NB + k) | 0x80u;
                mbar_wait(bar_at(last ? B_RV : B_PS), k & 1);
                uint4 v, z;
                {
                    SPIN_DECL;
                    do {
                        v = ld_pkt(src); z = ld_pkt(src + 256);
                        SPIN_CHECK(n);
                    } while (__any_sync(0xffffffffu, (((v.w ^ tag) | (z.w ^ tag)) & 0xffu) != 0));
                }
                TRACES(tr + 0);
                float a[3][4] = {};
                const uint32_t bb[3][2] = {{v.x, v.y}, {z.x, z.y}, {v.z, z.z}};
                float sa, sb, rl;
#pragma unroll
                for (int i = 0; i < 3; i++) {
                    const uint32_t l0 = g < 4 ? bb[i][0] : 0, l1 = g < 4 ? bb[i][1] : 0, h0 = g < 4 ? 0 : bb[i][0], h1 = g < 4 ? 0 : bb[i][1];
#pragma unroll
                    for (int mt = 0; mt < 5; mt++)
                        mma16816(a[mt % 3], wo[i][mt][0], wo[i][mt][1], wo[i][mt][2], wo[i][mt][3], mt < 3 ? l0 : h0, mt < 3 ? l1 : h1);
                    if (i == 0) {
                        int key = v.w & 0xffffff00u;
                        key ^= (key >> 31) & 0x7fffffff;
                        key = __reduce_max_sync(0xffffffffu, key);
                        key ^= (key >> 31) & 0x7fffffff;
                        const float ws = fast_ex2((F(v.w & 0xffffff00u) - __int_as_float(key)) * LOG2E);
                        sa = shi(ws, e1 ? 8 : 0); sb = shi(ws, e1 ? 12 : 4);
                        rl = ws * F(z.w & 0xffffff00u);
                        rl += shx(rl, 4);
                    }
                    if (i == 1) rl += shx(rl, 8);
                }
                float y[3];
#pragma unroll
                for (int j = 2; j < 5; j++) {
                    const int mt = j % 3;
                    y[mt] = fold(fmaf(a[mt][0], sa, a[mt][1] * sb), fmaf(a[mt][2], sa, a[mt][3] * sb), e1, 1);
                }
                const uint32_t pa = SM_PO + w * 512 + lane * 16;
                if (w < 2) {
                    const char* dst = opaque(cell + s * 16384);
                    rl = fast_rcp(rl);
                    bar_sync<1, 256>();
                    const uint4 c1 = lds128(pa), c2 = lds128(pa + 1024), c3 = lds128(pa + 2048);
                    red_cell2_if(true, dst, ((y[0] + F(c1.x)) + (F(c2.x) + F(c3.x))) * rl, ((y[1] + F(c1.y)) + (F(c2.y) + F(c3.y))) * rl,
                                 ((y[2] + F(c1.z)) + (F(c2.z) + F(c3.z))) * rl);
                } else {
                    stsf4(pa - 1024, y[0], y[1], y[2], 0.f);
                    bar_sync<1, 256>();
                }
                TRACES(tr + 1);
                if ((ORD_NO_TAIL >> n) & 1) continue;
                const uint32_t tsend = clk32();
                if (n == 0) {
                    st_pkt2_if(lane < 4, p.scr + SCR_O + head_off(h) + 2048 + w * 256 + s * 64 + lane * 16, 0, 0, 0, 0);
                    __syncwarp();
                } else if (!last) {
                    const char* nsrc = p.scr + acc_off(k - 1, 1, w) + near + g * 256 + t4 * 16;
                    SPIN_DECL;
                    do {
                        v = ld_pkt(nsrc);
                        SPIN_CHECK(n);
                        nx01 = pack2(F(v.x), F(v.y)); nx2 = pack2(F(v.z), 0.f);
                    } while (__any_sync(0xffffffffu, v.w != FULL_A));
                }
                wait_clk(tsend + (w < 2 ? 0 : 60) + (n < QUIET ? CFG(DLY_AL) : CFG(DLY_A)));
                {
                    SPIN_DECL;
                    do {
                        v = ld_pkt(cell + near);
                        SPIN_CHECK(n);
                        x01 = pack2(F(v.x), F(v.y));
                        x2 = pack2(F(v.z), 0.f);
                        put_x(x01, x2, xw, e2);
                    } while (__any_sync(0xffffffffu, v.w != FULL_A));
                }
                TRACES(tr + 2);
            } else if (n >= 0) {
                x01 = nx01; x2 = nx2;
                put_x(x01, x2, xw, e2);
            } else {
                mbar_wait(bar_at(B_W + 1), 0);
                const uint32_t ln = opaque(lane);
                const int mi = ln >> 3, mr = ln & 7;
                uint32_t zero = ln >> 5;
                TRACES(76);
#pragma unroll
                for (int i = 0; i < 3; i++) {
                    const int d = 16 * (w >> 1) + (mr >> 1) + 8 * (mr & 1) + (i < 2 ? 64 * (mi >> 1) + 4 * i : 128 + 4 * (mi >> 1));
#pragma unroll
                    for (int mt = 0; mt < 5; mt++) ldsm4t(wo[i][mt], ST_WO + d * 320 + 160 * (w & 1) + 32 * mt + 16 * (mi & 1), zero);
                }
                fence_async();
                __syncwarp();
                mbar_arrive_if(lane == 0, bar_at(B_WC + 1));
                mbar_wait(bar_at(B_W + 2), 0);
                TRACES(77);
#pragma unroll
                for (int i = 0; i < 5; i++) {
                    const uint32_t ga = ST_WG + (mi & 1) * 20480 + (80 * w + 16 * i + mr + 8 * (mi >> 1)) * 32;
                    uint32_t r[4];
                    ldsm4t(wg[i], ga + (odd ? 16 : 0), zero);
                    ldsm4t(r, ga + (odd ? 0 : 16), zero);
#pragma unroll
                    for (int kh = 0; kh < 2; kh++) {
                        const uint32_t moved = __shfl_xor_sync(0xffffffffu, odd ? r[2 * kh] : r[2 * kh + 1], 16);
                        wh[i][kh] = (g < 4) == odd ? moved : odd ? r[2 * kh + 1] : r[2 * kh];
                    }
                }
                fence_async();
                __syncwarp();
                mbar_arrive_if(lane == 0, bar_at(B_WC + 2));
                TRACES(72);
                x01 = 0x3f803f80u; x2 = 0x3f80u;
                put_x(x01, x2, xw, e2);
            }
            uint32_t b[10];
            get_x(b, xr);
            float a[2][4] = {};
#pragma unroll
            for (int i = 0; i < 5; i++) {
                mma16816(a[0], wg[i][0], wg[i][1], wg[i][2], wg[i][3], b[2 * i], b[2 * i + 1]);
                mma16816(a[1], wh[i][0], b[2 * i], wh[i][1], b[2 * i + 1], b[2 * i], b[2 * i + 1]);
            }
            stsf(SM_PG + (w >> 2) * 512 + (g + 8 * t4) * 16 + (w & 3) * 4, e2 ? (e1 ? a[1][2] : a[1][0]) : (e1 ? a[0][2] : a[0][0]));
            const uint2 cs = lds64(SM_CSG + lane * 48);
            const char* dst = opaque(cell + 3 * HALF - near);
            bar_sync<2, 256>();
            const float S = sum8(lds128(SM_PG + lane * 16), lds128(SM_PG + 512 + lane * 16));
            const float sx = shi(S, 25), sq = shi(S, 24), Su = shi(S, lane + (lane < 16 ? 8 : 4));
            if (n < 0) {
                if (w == 0) stsf2(SM_CSG + lane * 48, S, Su);
            } else {
                float mean_b, rden;
                ln_fast(sx, sq, mean_b, rden);
                const float gv = bfr(fmaf(-mean_b, F(cs.x), S) * rden), uv = bfr(fmaf(-mean_b, F(cs.y), Su) * rden);
                const float sg = fast_rcp(1.f + fast_ex2(-LOG2E * gv));
                const uint32_t hb = pack2(bfr(gv * sg) * uv, 0.f);
                const uint32_t b0 = __byte_perm(shi(hb, 2 * t4), shi(hb, 2 * t4 + 1), 0x5410);
                const uint32_t b1 = __byte_perm(shi(hb, e1 ? 18 : 16), shi(hb, e1 ? 19 : 17), 0x5410);
                const bool up = g >= 4;
                const uint32_t l0 = up ? 0 : b0, h0 = up ? b0 : 0;
                const uint32_t m1 = up == e2 ? b1 : 0;
                float d[3][4] = {};
                mma16816(d[0], wd[0][0], wd[0][1], wd[0][2], wd[0][3], l0, h0);
                mma16816(d[1], wd[1][0], wd[1][1], wd[1][2], wd[1][3], l0, h0);
                mma16816(d[2], wd[2][0], wd[2][1], wd[2][2], wd[2][3], l0, up ? 0 : m1);
                mma1688(d[0], wd[3][0], wd[3][1], m1);
                mma1688(d[1], wd[3][2], wd[3][3], m1);
                red_cell(dst, e1 ? d[0][2] : d[0][0], e1 ? d[1][2] : d[1][0], e1 ? d[2][2] : d[2][0]);
                const uint32_t tsend = clk32();
                TRACES(tr + 3);
                if (last && w != cta >> 4) continue;
                const float sgr = shi(sg, 27);
                const uint32_t sg2 = pack2(sgr, sgr);
                ln_finish(sx, sq, mean_b, rden);
                const uint32_t n01 = opaque(ln_apply(x01, mean_b, rden)), n2 = opaque(ln_apply(x2, mean_b, rden));
                if (last) {
                    sts128_if(lane >> 1 == (cta & 15), SM_FIN + (lane & 1) * 16, x01, n01, __byte_perm(x2, n2, 0x5410), sg2);
                    mbar_arrive_if(lane >> 1 == (cta & 15), bar_at(B_FIN));
                    __syncwarp();
                    continue;
                }
                wait_clk(tsend + (n < QUIET ? CFG(DLY_BL) : CFG(DLY_B)));
                const uint32_t r01 = x01, r2 = x2;
                float cnt;
                SPIN_DECL;
                do {
                    const uint4 v = ld_pkt(cell + 2 * HALF), z = ld_pkt(cell + 3 * HALF);
                    SPIN_CHECK(n);
                    cnt = F(v.w) + F(z.w);
                    x01 = badd2(r01, badd2(n01, bmul2(pack2(F(v.x) + F(z.x), F(v.y) + F(z.y)), sg2)));
                    x2 = badd2(r2, badd2(n2, bmul2(pack2(F(v.z) + F(z.z), 0.f), sg2)));
                    put_x(x01, x2, xw, e2);
                } while (__any_sync(0xffffffffu, cnt != NCTA));
                TRACES(tr + 4);
            }
        }
        {
            uint32_t b[10];
            get_x(b, xr);
            float a[3][4] = {};
            const float f0 = bf_lo(x01), f1 = bf_hi(x01), f2 = e2 ? 0.f : bf_lo(x2);
            float st;
#pragma unroll
            for (int i = 0; i < 5; i++) {
#pragma unroll
                for (int mt = 0; mt < 3; mt++) {
                    mma16816(a[mt], wq[i][mt][0], wq[i][mt][1], wq[i][mt][2], wq[i][mt][3], b[2 * i], b[2 * i + 1]);
                    if (i == 0 && mt == 0) st = fold(fmaf(f0, f0, fmaf(f1, f1, f2 * f2)), (f0 + f1) + f2, g & 1, 4);
                }
                if (i < 4) st += shx(st, i < 2 ? 1 << i : 2 << i);
            }
            const uint32_t pa = SM_PQ + (w >> 2) * 1024 + (g & 1) * 512 + ((e2 ? 16 : 0) + (e1 ? 4 : 0) + (g >> 1)) * 16 + (w & 3) * 4;
            stsf(pa + 128, e2 ? st : e1 ? a[1][2] : a[1][0]);
            stsf(pa, e2 ? (e1 ? a[2][2] : a[2][0]) : (e1 ? a[0][2] : a[0][0]));
            bar_sync<3, 288>();
            if (n >= 0 && w == cta >> 4) {
                red_cell2_if(lane >> 1 == (cta & 15), cell + (acc_off(k, 1, 0) - acc_off(k, 0, 0)), f0, f1, f2);
                __syncwarp();
            }
        }
    }
}

__host__ __device__ constexpr int bar_count(int i) {
    return i < 16 ? 1 : i < B_RR ? 0 : i < B_RK ? 2 : i <= B_RV ? 4 : i == B_Z ? 1 : i == B_EP ? 9 : i < B_WC ? 0 : i < B_FIN ? 8 :
           i == B_FIN ? 2 : i == B_PS || i == B_RP ? 4 : i == B_QR ? 32 : 1;
}
template <int I, int END> __device__ __forceinline__ void init_bars() {
    if constexpr (I < END) {
        if (bar_count(I)) mbar_init(bar_at(I), bar_count(I));
        init_bars<I + 1, END>();
    }
}
template <int ID> __device__ __forceinline__ void role_exit() { asm volatile("exit; // %0" ::"n"(ID)); }
constexpr int NTHREADS = 512;
#define STR2(x) #x
#define STR(x) STR2(x)
__global__ void __launch_bounds__(NTHREADS, 1)
decode_kernel(const Params p, const __grid_constant__ Maps tm) {
    extern __shared__ __align__(1024) unsigned char smem[];
    if (threadIdx.x == 0) l2_prefetch(p.wq + (size_t)blockIdx.x * 12288, 12288);
    const uint32_t t0 = now_ns() - CFG(LEAD);
    const int lane = threadIdx.x & 31;
    const int warp = __reduce_max_sync(0xffffffffu, threadIdx.x >> 5);
    if (warp < 8) {
        asm volatile("setmaxnreg.inc.sync.aligned.u32 " STR(CFG_REG_CHAIN) ";");
        bar_arrive<5, 480>();
        const uint32_t vote = probe_near(p, warp, lane);
        bar_sync<2, 256 + 32>();
        sts32(SM_NEAR + warp * 4, vote);
        mbar_arrive_if(lane == 0, bar_at(B_EP));
        chain_role(p, warp, __shfl_sync(0xffffffffu, lane, lane));
        role_exit<3>();
    } else if (warp < 12) {
        asm volatile("setmaxnreg.dec.sync.aligned.u32 " STR(CFG_REG_ATT) ";");
        if (elect_one()) {
            if (warp == 8) init_bars<0, 12>();
            else if (warp == 9) init_bars<12, 30>();
            else if (warp == 10) init_bars<30, 42>();
            else init_bars<42, NBAR>();
            asm volatile("fence.mbarrier_init.release.cluster;" ::: "memory");
            fence_async();
        }
        if (warp == 8) TRACE(236);
        bar_sync<5, 480>();
        if (warp == 8) TRACE(237);
        attention_role(p, warp - 8, lane);
        role_exit<2>();
    } else {
        asm volatile("setmaxnreg.dec.sync.aligned.u32 " STR(CFG_REG_HELP) ";");
        if (warp == 12) {
            load_role(p, &tm.k, lane, t0);
            role_exit<0>();
        } else {
            if (warp == 14) {
                if (smem_u32(smem) != SB) __trap();
                if (elect_one()) {
                    asm volatile("prefetch.tensormap [%0];" ::"l"(&tm.q) : "memory");
                    mbar_init(bar_at(B_W), 1); mbar_init(bar_at(B_W + 1), 1); mbar_init(bar_at(B_W + 2), 1);
                    asm volatile("fence.mbarrier_init.release.cluster;" ::: "memory");
                    fence_async();
                    mbar_expect_tx(bar_at(B_W), 61440 + 15360 + 6400); mbar_expect_tx(bar_at(B_W + 1), 61440); mbar_expect_tx(bar_at(B_W + 2), 40960);
                    bulk_load(ST_X, p.x, 5120, bar_at(B_W));
                    bulk_load(ST_X + 5120, p.wr, 1280, bar_at(B_W));
                }
                TRACE(238);
                reload_role(p, &tm, t0);
            } else {
                if (warp == 13 && elect_one()) {
                    asm volatile("prefetch.tensormap [%0];" ::"l"(&tm.g) : "memory");
                    asm volatile("prefetch.tensormap [%0];" ::"l"(&tm.u) : "memory");
                    asm volatile("prefetch.tensormap [%0];" ::"l"(&tm.o) : "memory");
                    asm volatile("prefetch.tensormap [%0];" ::"l"(&tm.k) : "memory");
                    asm volatile("prefetch.tensormap [%0];" ::"l"(&tm.v) : "memory");
                }
                TRACE(233 + warp);
                bar_sync<5, 480>();
                if (warp == 13) { bar_arrive<6, 64>(); q_role(p, lane); }
                else { bar_arrive<2, 256 + 32>(); zero_role(p, lane, t0); }
            }
            role_exit<1>();
        }
    }
}

typedef CUresult (*EncodeFn)(CUtensorMap*, CUtensorMapDataType, cuuint32_t, void*, const cuuint64_t*, const cuuint64_t*,
                             const cuuint32_t*, const cuuint32_t*, CUtensorMapInterleave, CUtensorMapSwizzle,
                             CUtensorMapL2promotion, CUtensorMapFloatOOBfill);

bool make_map(EncodeFn fn, CUtensorMap* m, const void* ptr, uint64_t cols, uint64_t rows, uint32_t bc, uint32_t br) {
    cuuint64_t dims[2] = {cols, rows};
    cuuint64_t strides[1] = {cols * 2};
    cuuint32_t box[2] = {bc, br};
    cuuint32_t es[2] = {1, 1};
    return fn(m, CU_TENSOR_MAP_DATA_TYPE_BFLOAT16, 2, const_cast<void*>(ptr), dims, strides, box, es, CU_TENSOR_MAP_INTERLEAVE_NONE,
              CU_TENSOR_MAP_SWIZZLE_NONE, CU_TENSOR_MAP_L2_PROMOTION_L2_128B, CU_TENSOR_MAP_FLOAT_OOB_FILL_NONE) == CUDA_SUCCESS;
}

bool make_kv_map(EncodeFn fn, CUtensorMap* m, const void* ptr) {
    cuuint64_t dims[4] = {64, 8, 3, (cuuint64_t)NB * NHEAD * SK / 8};
    cuuint64_t strides[3] = {DH * 2, 128, 8 * DH * 2};
    cuuint32_t box[4] = {64, 8, 3, 4};
    cuuint32_t es[4] = {1, 1, 1, 1};
    return fn(m, CU_TENSOR_MAP_DATA_TYPE_BFLOAT16, 4, const_cast<void*>(ptr), dims, strides, box, es, CU_TENSOR_MAP_INTERLEAVE_NONE,
              CU_TENSOR_MAP_SWIZZLE_128B, CU_TENSOR_MAP_L2_PROMOTION_L2_128B, CU_TENSOR_MAP_FLOAT_OOB_FILL_NONE) == CUDA_SUCCESS;
}

}

extern "C" void kernel_launch(void* const* d_in, const int* in_sizes, int n_in, void* d_out, int out_size) {
    (void)in_sizes; (void)n_in; (void)out_size;
    static EncodeFn fn = nullptr;
    static const char* scr = nullptr;
    if (!fn) {
        void* f = nullptr;
        cudaDriverEntryPointQueryResult qr;
        if (cudaGetDriverEntryPoint("cuTensorMapEncodeTiled", &f, cudaEnableDefault, &qr) != cudaSuccess || !f) return;
        void* sp = nullptr;
        if (cudaGetSymbolAddress(&sp, g_scratch) != cudaSuccess) return;
        scr = (const char*)(((uintptr_t)sp + (2 << 20) - 1) & ~(uintptr_t)((2 << 20) - 1));
        fn = (EncodeFn)f;
        cudaFuncSetAttribute(decode_kernel, cudaFuncAttributeMaxDynamicSharedMemorySize, SMEM_BYTES);
    }
    Maps tm;
    if (!make_kv_map(fn, &tm.k, d_in[1]) || !make_kv_map(fn, &tm.v, d_in[2])) return;
    if (!make_map(fn, &tm.q, d_in[3], NHEAD * DH, DM, 48, 128) || !make_map(fn, &tm.o, d_in[4], DM, NHEAD * DH, 160, 32)) return;
    if (!make_map(fn, &tm.g, d_in[7], FF, DM, 16, 128) || !make_map(fn, &tm.u, d_in[8], FF, DM, 16, 128)) return;
    Params p;
    p.x = (const unsigned short*)d_in[0];
    p.wq = (const char*)d_in[3];
    p.wo = (const char*)d_in[4];
    p.wr = (const unsigned short*)d_in[6];
    p.wg = (const char*)d_in[7];
    p.wu = (const char*)d_in[8];
    p.wd = (const char*)d_in[9];
    p.out = (unsigned short*)d_out;
    p.scr = scr;
    decode_kernel<<<NCTA, NTHREADS, SMEM_BYTES>>>(p, tm);
}
```

```cpp
#include <cuda_runtime.h>
#include <cuda_bf16.h>
#include <cuda.h>
#include <stdint.h>

namespace {

constexpr int NB = 4, DM = 640, NHEAD = 32, DH = 192, SK = 4096, WIN = 1024, FF = 1536;
constexpr int NCTA = 128;
constexpr int TILE = 12288, PAIR = 2 * TILE;

#define CFG_LIST(X) \
    X(TICK0, 479)        \
    X(TICK, 492)        \
    X(LEAD, 600)        \
    X(STAG, 430)        \
    X(WLAG, 350)        \
    X(GSTEP, 750)        \
    X(WIN, 5)        \
    X(PMAX, 2)        \
    X(PGRACE, 50)        \
    X(LMAX0, 150)        \
    X(LMAX, 160) \
    X(UP, 50)        \
    X(VSTEP, 150)        \
    X(RSTEP, 670)        \
    X(RSTEP3, 450) \
    X(ZTILE, 11)        \
    X(DLY_A, 410)        \
    X(DLY_AL, 100) \
    X(DLY_B, 535) \
    X(DLY_BL, 950) \
    X(DLY_F, 290) \
    X(FLIP, 0) \

#define X(n, v) constexpr int CFG_##n = v;
CFG_LIST(X)
#undef X
#define CFG(n) CFG_##n
constexpr int QUIET = 8;
#define CFG_REG_CHAIN 216
#define CFG_REG_ATT 48
#define CFG_REG_HELP 32
__device__ __forceinline__ int cta_id() { return (blockIdx.x & 1) << 6 | blockIdx.x >> 1; }
constexpr int KB_KV0 = 165;
__device__ __forceinline__ int kb_ns(int kb) { return kb * CFG(TICK0) / 12; }
__device__ __forceinline__ int tick_ns(int j) { return j <= 16 ? CFG(TICK0) : CFG(TICK); }
__device__ __forceinline__ int batch_ns(int k) { return kb_ns(KB_KV0) + (k ? 16 * (CFG(TICK0) + (k - 1) * CFG(TICK)) : 0); }

__device__ __forceinline__ uint32_t slots(int k) { return k & 2 ? (k & 1 ? 0x21304765u : 0x76835214u) : (k & 1 ? 0x21480765u : 0x76543210u); }
__device__ __forceinline__ int pass_nibble(int k, int u) { return k > 0 ? 4 + (u & 1) : u; }
__device__ __forceinline__ uint32_t slot_at(uint32_t tab, int u) { return (tab >> (4 * u)) & 15; }

constexpr int NROUND = 11;
constexpr uint32_t ORD_BATCH = 0x3b9910, ORD_LAST = 0x6da, ORD_NO_HEAD = 0x248, ORD_NO_TAIL = 0x092;

constexpr uint32_t SB = 1024;
constexpr uint32_t SM_BAR = SB + 9 * PAIR;
constexpr int B_F1 = 0;
constexpr int B_RR = 24;
constexpr int B_RK = 32;
constexpr int B_RV = 36;
constexpr int B_Z = 37;
constexpr int B_EP = 38;
constexpr int B_W = 39;
constexpr int B_WC = 42;
constexpr int B_FIN = 45;
constexpr int B_F3 = 46;
constexpr int B_PS = 48;
constexpr int B_RP = 49;
constexpr int B_FL = 50;
constexpr int B_QR = 51;
constexpr int NBAR = 52;
__host__ __device__ constexpr uint32_t bar_at(int i) { return SM_BAR + 8 * i; }
constexpr uint32_t SM_EPOCH = SM_BAR + 416;
constexpr uint32_t SM_MAX = SM_EPOCH + 16;
constexpr uint32_t SM_SUM = SM_MAX + 16;
constexpr uint32_t SM_NEAR = SM_SUM + 32;
constexpr uint32_t SM_FIN = SM_NEAR + 32;
constexpr uint32_t SM_Q = SM_FIN + 32;
constexpr uint32_t PSTR = 144;
constexpr uint32_t SM_P = SM_Q + 5 * 384;
constexpr uint32_t SM_X = SM_P + 8 * PSTR;
constexpr uint32_t SM_CSG = SM_X + 40;
constexpr uint32_t SM_ONES = SM_X + 8 * 384;
constexpr uint32_t SM_PG = SM_ONES + 48;
constexpr uint32_t SM_PO = SM_PG + 1024;
constexpr uint32_t SM_PQ = SM_PO;
constexpr int SMEM_BYTES = SM_PO + 3072 - SB;
static_assert(SMEM_BYTES <= 232448 && SM_Q % 16 == 0 && SM_P % 16 == 0 && SM_X % 16 == 0 && SM_PO % 16 == 0, "smem");
constexpr uint32_t ST_WQ = SB, ST_WD = SB + 3 * PAIR, ST_WO = SB + 4 * PAIR, ST_WG = SB + 7 * PAIR, ST_X = ST_WG + 40960;

__device__ unsigned g_epoch;
__device__ unsigned char g_scratch[4 << 20];
constexpr uint32_t HALF = 4096, SCR_O = 1 << 16, SCR_Q = 1 << 17, SCR_COUNT = 3 << 16;
__device__ __forceinline__ uint32_t acc_off(int k, int layer, int w) {
    return (k & 1) << 6 | layer << 7 | (w & 1) << 11 | (w >> 1) << 14 | (k + layer == NB) << 18;
}
__device__ __forceinline__ uint32_t head_off(int h) { return (h & 3) << 14 | (h & 4) << 16 | (h & 8) << 17 | (h & 16) << 9; }
__device__ __forceinline__ uint32_t head_near(int h, uint32_t near) { return near ^ HALF ^ (h & 16) << 8; }
constexpr uint32_t FULL_A = 0x42040000u;

struct Params {
    const char* wq;
    const unsigned short* x;
    const char* wo;
    const unsigned short* wr;
    const char* wg;
    const char* wu;
    const char* wd;
    unsigned short* out;
    const char* scr;
};

__device__ __forceinline__ uint32_t smem_u32(const void* p) { return (uint32_t)__cvta_generic_to_shared(p); }
__device__ __forceinline__ void mbar_init(uint32_t a, uint32_t c) { asm volatile("mbarrier.init.shared::cta.b64 [%0], %1;" ::"r"(a), "r"(c) : "memory"); }
__device__ __forceinline__ void mbar_expect_tx(uint32_t a, uint32_t b) {
    asm volatile("mbarrier.arrive.expect_tx.shared::cta.b64 _, [%0], %1;" ::"r"(a), "r"(b) : "memory");
}
__device__ __forceinline__ void mbar_arrive(uint32_t a) { asm volatile("mbarrier.arrive.shared::cta.b64 _, [%0];" ::"r"(a) : "memory"); }
constexpr uint32_t SPIN_LIMIT = 1u << 22;
#define SPIN_DECL uint32_t spins = 0
#define SPIN_CHECK(info) { if (++spins > SPIN_LIMIT) __trap(); }
__device__ __forceinline__ void jitter() {}
__device__ __forceinline__ void mbar_wait(uint32_t a, uint32_t parity) {
    jitter();
    uint32_t ok;
    SPIN_DECL;
    while (true) {
        asm volatile("{\n.reg .pred p;\nmbarrier.try_wait.parity.shared::cta.b64 p, [%1], %2;\nselp.u32 %0, 1, 0, p;\n}"
                     : "=r"(ok) : "r"(a), "r"(parity) : "memory");
        if (ok) break;
        SPIN_CHECK((a - SM_BAR) / 8 * 10 + parity);
    }
    jitter();
}
__device__ __forceinline__ bool mbar_test2(uint32_t a, uint32_t pa, uint32_t b, uint32_t pb) {
    uint32_t ok;
    asm volatile("{\n.reg .pred p, q;\nmbarrier.test_wait.parity.shared::cta.b64 p, [%1], %2;\n"
                 "mbarrier.test_wait.parity.shared::cta.b64 q, [%3], %4;\nand.pred p, p, q;\nvote.sync.all.pred p, p, 0xffffffff;\nselp.u32 %0, 1, 0, p;\n}"
                 : "=r"(ok) : "r"(a), "r"(pa), "r"(b), "r"(pb) : "memory");
    return ok;
}
__device__ __forceinline__ uint32_t now_ns() { uint32_t t; asm volatile("mov.u32 %0, %%globaltimer_lo;" : "=r"(t) :: "memory"); return t; }
__device__ __forceinline__ uint32_t clk32() { uint32_t c; asm volatile("mov.u32 %0, %%clock;" : "=r"(c) :: "memory"); return c; }
__device__ __forceinline__ void wait_ns(uint32_t t) { jitter(); while ((int)(now_ns() - t) < 0) {} }
__device__ __forceinline__ void wait_clk(uint32_t t) { jitter(); while ((int)(clk32() - t) < 0) {} }
__device__ __forceinline__ bool elect_one() {
    uint32_t e;
    asm volatile("{\n.reg .pred p;\nelect.sync _|p, 0xffffffff;\nselp.u32 %0, 1, 0, p;\n}" : "=r"(e));
    return e;
}
constexpr uint64_t POL_FIRST = 0x12F0000000000000ull, POL_NORMAL = 0x1000000000000000ull;
__device__ __forceinline__ void tma_tile(uint32_t dst, const CUtensorMap* tm, int group, uint32_t bar, uint64_t pol) {
    asm volatile("cp.async.bulk.tensor.4d.shared::cluster.global.mbarrier::complete_tx::bytes.L2::cache_hint"
                 " [%0], [%1, {%3, %3, %3, %4}], [%2], %5;"
                 ::"r"(dst), "l"(tm), "r"(bar), "r"(0), "r"(group), "l"(pol) : "memory");
}
__device__ __forceinline__ void tma2d(uint32_t dst, const CUtensorMap* tm, int x, int y, uint32_t bar) {
    asm volatile("cp.async.bulk.tensor.2d.shared::cluster.global.mbarrier::complete_tx::bytes [%0], [%1, {%3, %4}], [%2];"
                 ::"r"(dst), "l"(tm), "r"(bar), "r"(x), "r"(y) : "memory");
}
__device__ __forceinline__ void bulk_load(uint32_t dst, const void* src, uint32_t bytes, uint32_t bar) {
    asm volatile("cp.async.bulk.shared::cluster.global.mbarrier::complete_tx::bytes [%0], [%1], %2, [%3];"
                 ::"r"(dst), "l"(src), "r"(bytes), "r"(bar) : "memory");
}
__device__ __forceinline__ void l2_prefetch(const void* p, uint32_t bytes) {
    asm volatile("cp.async.bulk.prefetch.L2.global [%0], %1;" ::"l"(p), "r"(bytes) : "memory");
}
__device__ __forceinline__ void mma16816(float (&c)[4], uint32_t a0, uint32_t a1, uint32_t a2, uint32_t a3, uint32_t b0, uint32_t b1) {
    asm volatile("mma.sync.aligned.m16n8k16.row.col.f32.bf16.bf16.f32 {%0,%1,%2,%3}, {%4,%5,%6,%7}, {%8,%9}, {%0,%1,%2,%3};"
                 : "+f"(c[0]), "+f"(c[1]), "+f"(c[2]), "+f"(c[3]) : "r"(a0), "r"(a1), "r"(a2), "r"(a3), "r"(b0), "r"(b1));
}
__device__ __forceinline__ void mma1688(float (&c)[4], uint32_t a0, uint32_t a1, uint32_t b0) {
    asm volatile("mma.sync.aligned.m16n8k8.row.col.f32.bf16.bf16.f32 {%0,%1,%2,%3}, {%4,%5}, {%6}, {%0,%1,%2,%3};"
                 : "+f"(c[0]), "+f"(c[1]), "+f"(c[2]), "+f"(c[3]) : "r"(a0), "r"(a1), "r"(b0));
}
__device__ __forceinline__ void ldsm4(uint32_t (&r)[4], uint32_t a) {
    asm volatile("ldmatrix.sync.aligned.m8n8.x4.shared.b16 {%0,%1,%2,%3}, [%4];"
                 : "=r"(r[0]), "=r"(r[1]), "=r"(r[2]), "=r"(r[3]) : "r"(a) : "memory");
}
__device__ __forceinline__ void ldsm4t(uint32_t (&r)[4], uint32_t a, uint32_t& zero) {
    asm volatile("ldmatrix.sync.aligned.m8n8.x4.trans.shared.b16 {%0,%1,%2,%3}, [%4];"
                 : "=r"(r[0]), "=r"(r[1]), "=r"(r[2]), "=r"(r[3]) : "r"(a + zero) : "memory");
    zero &= r[3];
}
__device__ __forceinline__ uint4 ld_pkt(const void* p) {
    uint4 v;
    asm volatile("{\n.reg .b128 t;\nld.relaxed.gpu.global.b128 t, [%4];\nmov.b128 {%0,%1,%2,%3}, t;\n}"
                 : "=r"(v.x), "=r"(v.y), "=r"(v.z), "=r"(v.w) : "l"(p) : "memory");
    return v;
}
__device__ __forceinline__ void st_pkt(const void* p, uint32_t a, uint32_t b, uint32_t c, uint32_t d) {
    asm volatile("{\n.reg .b128 t;\nmov.b128 t, {%1,%2,%3,%4};\nst.relaxed.gpu.global.b128 [%0], t;\n}"
                 ::"l"(p), "r"(a), "r"(b), "r"(c), "r"(d) : "memory");
}
__device__ __forceinline__ uint2 ld_pkt8(const void* p) {
    uint2 v;
    asm volatile("{\n.reg .b64 t;\nld.relaxed.gpu.global.b64 t, [%2];\nmov.b64 {%0,%1}, t;\n}" : "=r"(v.x), "=r"(v.y) : "l"(p) : "memory");
    return v;
}
__device__ __forceinline__ void red_cell(const char* p, float a, float b, float c) {
    jitter();
    asm volatile("red.relaxed.gpu.global.add.v4.f32 [%0], {%1,%2,%3,%4};" ::"l"(p), "f"(a), "f"(b), "f"(c), "f"(1.0f) : "memory");
}
#define PRED(n) "{\n.reg .pred p;\nsetp.ne.u32 p, %" #n ", 0;\n"
__device__ __forceinline__ void red_cell2_if(bool on, const char* p, float a, float b, float c) {
    jitter();
    asm volatile(PRED(5) "@p red.relaxed.gpu.global.add.v4.f32 [%0], {%1,%2,%3,%4};\n@p red.relaxed.gpu.global.add.v4.f32 [%0+4096], {%1,%2,%3,%4};\n}"
                 ::"l"(p), "f"(a), "f"(b), "f"(c), "f"(1.0f), "r"((uint32_t)on) : "memory");
}
__device__ __forceinline__ void st_pkt8_if(bool on, const void* p, uint32_t a, uint32_t b) {
    jitter();
    asm volatile(PRED(3) ".reg .b64 t;\nmov.b64 t, {%1,%2};\n@p st.relaxed.gpu.global.b64 [%0], t;\n}" ::"l"(p), "r"(a), "r"(b), "r"((uint32_t)on) : "memory");
}
__device__ __forceinline__ void st_pkt82_if(bool on, const void* p, uint32_t a, uint32_t b) {
    asm volatile(PRED(3) ".reg .b64 t;\nmov.b64 t, {%1,%2};\n@p st.relaxed.gpu.global.b64 [%0], t;\n@p st.relaxed.gpu.global.b64 [%0+4096], t;\n}"
                 ::"l"(p), "r"(a), "r"(b), "r"((uint32_t)on) : "memory");
}
__device__ __forceinline__ void st_pkt2_if(bool on, const void* p, uint32_t a, uint32_t b, uint32_t c, uint32_t d) {
    jitter();
    asm volatile(PRED(5) ".reg .b128 t;\nmov.b128 t, {%1,%2,%3,%4};\n@p st.relaxed.gpu.global.b128 [%0], t;\n@p st.relaxed.gpu.global.b128 [%0+4096], t;\n}"
                 ::"l"(p), "r"(a), "r"(b), "r"(c), "r"(d), "r"((uint32_t)on) : "memory");
}
__device__ __forceinline__ void mbar_arrive_if(bool on, uint32_t a) {
    jitter();
    asm volatile(PRED(1) "@p mbarrier.arrive.shared::cta.b64 _, [%0];\n}" ::"r"(a), "r"((uint32_t)on) : "memory");
}
__device__ __forceinline__ void sts16_if(bool on, uint32_t a, uint32_t v) {
    asm volatile(PRED(2) "@p st.shared.u16 [%0], %1;\n}" ::"r"(a), "h"((unsigned short)v), "r"((uint32_t)on) : "memory");
}
__device__ __forceinline__ void sts32_if(bool on, uint32_t a, uint32_t v) {
    asm volatile(PRED(2) "@p st.shared.u32 [%0], %1;\n}" ::"r"(a), "r"(v), "r"((uint32_t)on) : "memory");
}
__device__ __forceinline__ void sts128_if(bool on, uint32_t a, uint32_t x, uint32_t y, uint32_t z, uint32_t w) {
    jitter();
    asm volatile(PRED(5) "@p st.shared.v4.u32 [%0], {%1,%2,%3,%4};\n}" ::"r"(a), "r"(x), "r"(y), "r"(z), "r"(w), "r"((uint32_t)on) : "memory");
}
__device__ __forceinline__ float fast_rcp(float x) { float r; asm("rcp.approx.ftz.f32 %0, %1;" : "=f"(r) : "f"(x)); return r; }
__device__ __forceinline__ float fast_sqrt(float x) { float r; asm("sqrt.approx.ftz.f32 %0, %1;" : "=f"(r) : "f"(x)); return r; }
__device__ __forceinline__ float fast_ex2(float x) { float r; asm("ex2.approx.ftz.f32 %0, %1;" : "=f"(r) : "f"(x)); return r; }
__device__ __forceinline__ uint32_t pack2(float lo, float hi) {
    uint32_t r;
    asm("cvt.rn.bf16x2.f32 %0, %1, %2;" : "=r"(r) : "f"(hi), "f"(lo));
    return r;
}
__device__ __forceinline__ float bfr(float x) { return __uint_as_float(pack2(0.f, x)); }
__device__ __forceinline__ uint32_t badd2(uint32_t a, uint32_t b) { uint32_t r; asm("add.rn.bf16x2 %0, %1, %2;" : "=r"(r) : "r"(a), "r"(b)); return r; }
__device__ __forceinline__ uint32_t bsub2(uint32_t a, uint32_t b) { uint32_t r; asm("sub.rn.bf16x2 %0, %1, %2;" : "=r"(r) : "r"(a), "r"(b)); return r; }
__device__ __forceinline__ uint32_t bmul2(uint32_t a, uint32_t b) { uint32_t r; asm("mul.rn.bf16x2 %0, %1, %2;" : "=r"(r) : "r"(a), "r"(b)); return r; }
__device__ __forceinline__ float bf_lo(uint32_t w) { return __uint_as_float(w << 16); }
__device__ __forceinline__ float bf_hi(uint32_t w) { return __uint_as_float(w & 0xffff0000u); }
__device__ __forceinline__ float F(uint32_t t) { return __uint_as_float(t); }
__device__ __forceinline__ uint32_t lds16(uint32_t a) { unsigned short h; asm volatile("ld.shared.u16 %0, [%1];" : "=h"(h) : "r"(a) : "memory"); return h; }
__device__ __forceinline__ uint32_t lds32(uint32_t a) { uint32_t v; asm volatile("ld.shared.u32 %0, [%1];" : "=r"(v) : "r"(a) : "memory"); return v; }
__device__ __forceinline__ uint2 lds64(uint32_t a) {
    uint2 v; asm volatile("ld.shared.v2.u32 {%0,%1}, [%2];" : "=r"(v.x), "=r"(v.y) : "r"(a) : "memory"); return v;
}
__device__ __forceinline__ uint4 lds128(uint32_t a) {
    uint4 v; asm volatile("ld.shared.v4.u32 {%0,%1,%2,%3}, [%4];" : "=r"(v.x), "=r"(v.y), "=r"(v.z), "=r"(v.w) : "r"(a) : "memory"); return v;
}
__device__ __forceinline__ float sum8(const uint4& u, const uint4& v) {
    return ((F(u.x) + F(u.y)) + (F(u.z) + F(u.w))) + ((F(v.x) + F(v.y)) + (F(v.z) + F(v.w)));
}
__device__ __forceinline__ void sts16(uint32_t a, uint32_t v) { asm volatile("st.shared.u16 [%0], %1;" ::"r"(a), "h"((unsigned short)v) : "memory"); }
__device__ __forceinline__ void sts32(uint32_t a, uint32_t v) { asm volatile("st.shared.u32 [%0], %1;" ::"r"(a), "r"(v) : "memory"); }
__device__ __forceinline__ void stsf(uint32_t a, float v) { asm volatile("st.shared.f32 [%0], %1;" ::"r"(a), "f"(v) : "memory"); }
__device__ __forceinline__ void stsf2(uint32_t a, float x, float y) { asm volatile("st.shared.v2.f32 [%0], {%1,%2};" ::"r"(a), "f"(x), "f"(y) : "memory"); }
__device__ __forceinline__ void stsf4(uint32_t a, float x, float y, float z, float w) {
    asm volatile("st.shared.v4.f32 [%0], {%1,%2,%3,%4};" ::"r"(a), "f"(x), "f"(y), "f"(z), "f"(w) : "memory");
}
template <int ID, int N> __device__ __forceinline__ void bar_sync() { jitter(); asm volatile("bar.sync %0, %1;" ::"n"(ID), "n"(N) : "memory"); jitter(); }
template <int ID, int N> __device__ __forceinline__ void bar_arrive() { jitter(); asm volatile("bar.arrive %0, %1;" ::"n"(ID), "n"(N) : "memory"); jitter(); }
__device__ __forceinline__ void fence_async() { asm volatile("fence.proxy.async.shared::cta;" ::: "memory"); }
__device__ __forceinline__ float shx(float v, int m) { return __shfl_xor_sync(0xffffffffu, v, m); }
__device__ __forceinline__ float shi(float v, int l) { return __shfl_sync(0xffffffffu, v, l); }
__device__ __forceinline__ uint32_t shi(uint32_t v, int l) { return __shfl_sync(0xffffffffu, v, l); }
__device__ __forceinline__ uint32_t opaque(uint32_t x) { asm volatile("mov.u32 %0, %0;" : "+r"(x)); return x; }
__device__ __forceinline__ const char* opaque(const char* x) { asm volatile("mov.u64 %0, %0;" : "+l"(x)); return x; }
constexpr float LOG2E = 1.4426950408889634f, SCALE = 0.07216878364870322f;

#define TRACE(idx) do {} while (0)
#define TRACES(slot) do {} while (0)

__device__ __forceinline__ uint32_t probe_near(const Params& p, int w, int lane) {
    const int cta = cta_id();
    const char* pr = p.scr + SCR_O + head_off(cta >> 2) + 2048 + w * 256 + (cta & 3) * 64;
    st_pkt2_if(lane < 4, pr + lane * 16, 0, 0, 0, 0);
    uint32_t best0 = ~0u, best1 = ~0u;
#pragma unroll 1
    for (int i = w & 1; i < 6 + (w & 1); i++) {
        uint32_t c = clk32(), v = 0;
        if (lane == 0) asm volatile("atom.relaxed.gpu.global.add.u32 %0, [%1], 1;" : "=r"(v) : "l"(pr + (i & 1) * HALF) : "memory");
        c += __shfl_sync(0xffffffffu, v, 0) >> 16;
        c = clk32() - c;
        if (i & 1) best1 = min(best1, c); else best0 = min(best0, c);
    }
    return min(best0, 0xffffu) | min(best1, 0xffffu) << 16;
}
__device__ __forceinline__ uint32_t near_half() {
    const uint4 a = lds128(SM_NEAR), b = lds128(SM_NEAR + 16);
    const uint32_t m = __vminu2(__vminu2(__vminu2(a.x, a.y), __vminu2(a.z, a.w)), __vminu2(__vminu2(b.x, b.y), __vminu2(b.z, b.w)));
    return head_near(cta_id() >> 2, ((m & 0xffffu) > m >> 16) != (CFG(FLIP) != 0) ? HALF : 0);
}

__device__ __forceinline__ int kv_group(int k, int t) {
    const int cta = cta_id();
    return ((k * NHEAD + (cta >> 2)) * SK + (SK - WIN) + (cta & 3) * 32 + t * 128) / 8;
}
__device__ __forceinline__ uint32_t phase_ns() { return (((cta_id() >> 2) * 13) & 31) * CFG(STAG) / 32; }

__device__ __forceinline__ void ln_fast(float s, float q, float& mean, float& rstd) {
    mean = s * (1.f / DM);
    asm("rsqrt.approx.ftz.f32 %0, %1;" : "=f"(rstd) : "f"(fmaxf(fmaf(-mean, mean, fmaf(q, 1.f / DM, 1e-5f)), 1e-5f)));
}
__device__ __forceinline__ void q_role(const Params& p, int lane) {
    const int cta = cta_id();
    mbar_wait(bar_at(B_EP), 0);
    const uint32_t epoch = lds32(SM_EPOCH), near = head_near(cta >> 2, near_half());
    auto sums = [&](float& S0, float& S1) {
        bar_sync<3, 288>();
        const uint32_t ra = SM_PQ + lane * 16;
        S0 = sum8(lds128(ra), lds128(ra + 1024)); S1 = sum8(lds128(ra + 512), lds128(ra + 1536));
    };
    float cs0, cs1;
    {
        uint32_t q0 = 0, q1 = 0, q2 = 0, q3 = 0;
#pragma unroll 1
        for (int r = 0; r < NB; r++) {
            sums(cs0, cs1);
            bar_arrive<7, 288>();
            q0 = q1; q1 = q2; q2 = q3; q3 = pack2(cs0, cs1);
        }
        const uint32_t t0 = shi(q3, 3 * lane - 72), t1 = shi(q3, 3 * lane - 71), t2 = shi(q3, 3 * lane - 70), tag = epoch << 8 | 0x40;
        const char* box = p.scr + SCR_O + head_off(cta >> 2) + 2048 + (lane >> 2) * 256 + (lane & 3) * 16;
        st_pkt2_if(true, box + (cta & 3) * 64, lane < 24 ? q0 : t0, lane < 24 ? q1 : t1, lane < 24 ? q2 : t2, tag);
        const uint32_t qd = SM_Q + (lane < 24 ? lane * 4 : 3 * 384 + (lane - 24) * 12), step = lane < 24 ? 384 : 4;
#pragma unroll 1
        for (int j = 0; j < 4; j++) {
            uint4 v;
            SPIN_DECL;
            do {
                __nanosleep(200);
                v = ld_pkt(box + near + j * 64);
                SPIN_CHECK(j);
            } while (__any_sync(0xffffffffu, v.w != tag));
            sts32(qd + j * 96, v.x); sts32(qd + j * 96 + step, v.y); sts32(qd + j * 96 + 2 * step, v.z);
        }
        mbar_arrive(bar_at(B_QR));
    }
    sums(cs0, cs1);
    bar_arrive<7, 288>();
    const char* const src = p.scr + SCR_Q + head_off(cta >> 2) + lane * 8 + near;
    const char* const dst = src + (cta & 3) * 192;
    const uint32_t qd = SM_Q + NB * 384 + lane * 4;
    st_pkt82_if(lane < 24, dst - near, 0, 0);
#pragma unroll 1
    for (int k = 0; k < NB; k++) {
        float S0, S1, mean, rstd;
        sums(S0, S1);
        ln_fast(shi(S1, 24), shi(S0, 24), mean, rstd);
        const uint32_t qq = pack2(fmaf(-mean, cs0, S0) * rstd, fmaf(-mean, cs1, S1) * rstd), tag = epoch * NB + k;
        st_pkt8_if(lane < 24, dst + ((int)HALF - 2 * (int)near), qq, tag);
        st_pkt8_if(lane < 24, dst, qq, tag);
        TRACES(k * 12 + 5);
        uint2 a, b, c;
        SPIN_DECL;
        do {
            a = ld_pkt8(src); b = ld_pkt8(src + 256); c = ld_pkt8(src + 512);
            SPIN_CHECK(k);
            sts32(qd, a.x); sts32(qd + 128, b.x); sts32(qd + 256, c.x);
        } while (__any_sync(0xffffffffu, a.y != tag || b.y != tag || c.y != tag));
        mbar_arrive(bar_at(B_QR));
    }
}

struct Maps { CUtensorMap k, v, q, o, g, u; };
__device__ __forceinline__ void load_role(const Params& p, const CUtensorMap* tmKV, int lane, uint32_t t0) {
    const int cta = cta_id();
    t0 += phase_ns();
#pragma unroll 1
    for (int i = 1; i < 5; i++) {
        wait_ns(t0 + i * CFG(TICK0));
        if (elect_one()) l2_prefetch(p.wq + (size_t)(128 * i + cta) * 12288, 12288);
        TRACE(230 + i);
    }
    uint32_t plan[2];
#pragma unroll
    for (int i = 0; i < 2; i++) {
        const int j = lane + 32 * i, k = j >> 4, t = j & 15, u = t >> 1, jw = j - CFG(WIN);
        const int sb = k == 0 ? B_WC + (t >= 8) + (t >= 14) : t >= 12 ? B_RK + u - 5 : t >= 4 ? B_RR + t - 4 : t >= 2 ? B_RP : k > 1 ? B_RK + 3 : B_RR + t;
        const uint32_t sw = sb * 8 | (j < 18 ? 0 : (t >= 12 || u == 1 ? k - 1 : k) & 1) << 9;
        plan[i] = sw | (jw < 0 ? sw : (B_F1 + (jw & 15)) * 8 | ((jw >> 4) & 1) << 9) << 10 |
                  (slot_at(slots(k), t < 8 ? pass_nibble(k, u) : u) * 2 + (t & 1)) << 20 | (t < 10 && j >= 8 && j < 56) << 25;
    }
    bar_sync<6, 64>();
    wait_ns(t0 + kb_ns(60));
    if (elect_one()) bulk_load(ST_WD, p.wd + cta * 15360, 15360, bar_at(B_W));
    TRACE(235);
#pragma unroll 1
    for (int i = 0; i < 5; i++) {
        wait_ns(t0 + kb_ns(75) + i * kb_ns(6));
        if (elect_one()) { l2_prefetch(p.wg + (128 * i + cta) * 3072, 3072); l2_prefetch(p.wu + (128 * i + cta) * 3072, 3072); }
    }
#pragma unroll 1
    for (int i = 0; i < 6; i++) {
        wait_ns(t0 + kb_ns(105) + min(i, 4) * kb_ns(10));
        if (elect_one()) l2_prefetch(p.wo + (size_t)((cta >> 2) * DH + 32 * i + 8 * (cta & 3)) * 1280, 10240);
    }
    t0 += batch_ns(0);
    int jp = 0, shift = 0;
    uint32_t earliest = t0;
    auto requested = [&](uint32_t now) {
        shift = max(shift, (int)(now - t0) - (jp < 12 ? CFG(LMAX0) : CFG(LMAX)));
        TRACE(128 + jp);
        t0 += tick_ns(++jp);
    };
    const int grp0 = kv_group(0, 0);
    auto group = [&](int j) { return grp0 + (j >> 4) * (NHEAD * SK / 8) + (j & 7) * 16; };
#pragma unroll 1
    for (int j = 0; j < 16 * NB; j++) {
        const uint32_t pl = __shfl_sync(0xffffffffu, j & 32 ? plan[1] : plan[0], j);
        const int jmax = min(j + CFG(PMAX), 16 * NB);
        jitter();
        uint32_t now;
        SPIN_DECL;
        while (true) {
            const bool ok = mbar_test2(SM_BAR + (pl & 511), (pl >> 9) & 1, SM_BAR + ((pl >> 10) & 511), (pl >> 19) & 1);
            now = now_ns();
            const int late = now - t0 - shift;
            if (ok && (jp > j ? (int)(now - earliest) : late) >= 0) break;
            if (late >= (jp > j ? 0 : CFG(PGRACE)) && jp < jmax) {
                if (elect_one())
                    asm volatile("cp.async.bulk.prefetch.tensor.4d.L2.global [%0, {%1, %1, %1, %2}];" ::"l"(tmKV + ((jp >> 3) & 1)), "r"(0), "r"(group(jp)) : "memory");
                requested(now);
            }
            SPIN_CHECK(j);
        }
        if (elect_one()) {
            mbar_expect_tx(bar_at(B_F1 + (j & 15)), TILE);
            tma_tile(SB + ((pl >> 20) & 31) * TILE, tmKV + ((j >> 3) & 1), group(j), bar_at(B_F1 + (j & 15)), pl >> 25 ? POL_NORMAL : POL_FIRST);
        }
        TRACE(256 + j);
        if ((j & 15) == 15) TRACES(88 + (j >> 4));
        earliest = now + CFG(VSTEP);
        if (jp == j) requested(now);
        const int jl = j - 3;
        if (jl >= 8 && !mbar_test2(bar_at(B_F1 + (jl & 15)), (jl >> 4) & 1, bar_at(B_F1 + (jl & 15)), (jl >> 4) & 1)) shift += CFG(UP);
    }
}

__device__ __forceinline__ void reload_role(const Params& p, const Maps* tm, uint32_t t0) {
    const CUtensorMap* const tmK = &tm->k;
    const CUtensorMap* const tmV = &tm->v;
    const int cta = cta_id();
    t0 += CFG(TICK0) + CFG(WLAG) + phase_ns();
#pragma unroll 1
    for (int i = 0; i < 5; i++) {
        wait_ns(t0 + i * CFG(TICK0));
        if (elect_one()) tma2d(ST_WQ + i * 12288, &tm->q, 48 * cta, 128 * i, bar_at(B_W));
        TRACE(240 + i);
        if (i == 1) bar_sync<5, 480>();
    }
#pragma unroll 1
    for (int i = 0, o = 0; i < 10;) {
        const uint32_t now = now_ns() - t0;
        if (o < 6 && (int)now >= kb_ns(105) + o * kb_ns(10)) {
            if (elect_one()) tma2d(ST_WO + o * 10240, &tm->o, 160 * (cta & 3), (cta >> 2) * DH + 32 * o, bar_at(B_W + 1));
            o++;
        } else if ((int)now >= kb_ns(77) + i * CFG(GSTEP) && (i < 9 || o == 6)) {
            if (elect_one()) tma2d(ST_WG + (i & 1) * 20480 + (i >> 1) * 4096, i & 1 ? &tm->u : &tm->g, (12 * cta) & ~7, 128 * (i >> 1), bar_at(B_W + 2));
            i++;
        }
    }
#pragma unroll 1
    for (int k = 0; k < NB - 1; k++) {
        mbar_wait(bar_at(B_RK), k & 1);
        if (elect_one()) {
            const uint32_t dst = SB + slot_at(slots(k), 0) * PAIR;
            mbar_expect_tx(bar_at(B_FL), PAIR);
            tma_tile(dst, tmV, kv_group(k, 0), bar_at(B_FL), POL_FIRST);
            tma_tile(dst + TILE, tmV, kv_group(k, 1), bar_at(B_FL), POL_FIRST);
        }
        mbar_wait(bar_at(k == NB - 2 ? B_RK + 3 : B_RV), k & 1);
        uint32_t due = now_ns();
        if (elect_one()) mbar_expect_tx(bar_at(B_F3), 4 * PAIR);
#pragma unroll 1
        for (int t = 0; t < 8; t++) {
            if (t == 2) mbar_wait(bar_at(B_RV), k & 1);
            wait_ns(due);
            due += k == NB - 2 ? CFG(RSTEP3) : CFG(RSTEP);
            if (elect_one())
                tma_tile(SB + slot_at(slots(k + 1), t >> 1) * PAIR + (t & 1) * TILE, tmK, kv_group(k + 1, t), bar_at(B_F3), POL_FIRST);
        }
        TRACE(121 + k);
    }
}

__device__ __forceinline__ void zero_role(const Params& p, int lane, uint32_t t0) {
    const int cta = cta_id();
    unsigned ticket = 0;
    if (lane == 0) ticket = atomicAdd(&g_epoch, 1u);
    const uint32_t epoch = __shfl_sync(0xffffffffu, ticket, 0) / NCTA + 1;
    if (lane == 0) { sts32(SM_EPOCH, epoch); mbar_arrive(bar_at(B_EP)); }
    mbar_wait(bar_at(B_EP), 0);
#pragma unroll 1
    for (int k = 0; k < NB + 2; k++) {
        lane = opaque(lane);
        const int cl = 2 * (cta & 15) + (lane & 1);
        const int col = 80 * (cta >> 4) + (cl & 2 ? 48 : 0) + (cl >> 2) + (cl & 1 ? 8 : 0);
        const char* own = p.scr + (cl >> 2) * 256 + (cl & 3) * 16;
        uint32_t v0 = 0, v1 = 0, v2 = 0;
        if (lane < 4 && k < NB) {
            const unsigned short* xp = p.x + k * DM + col;
            v0 = __ldg(xp) << 16; v1 = __ldg(xp + 16) << 16; v2 = cl & 2 ? 0 : __ldg(xp + 32) << 16;
        }
        uint4 r;
        if (k == 1) mbar_wait(bar_at(B_RK), 0);
        if (k > 1) {
            mbar_wait(bar_at(B_FIN), k & 1);
            r = lds128(SM_FIN + (lane & 1) * 16);
        }
        if (k < NB) {
            const int lg = lane >> 3, ty = (lane & 7) >> 1;
            const char* dst = own + acc_off((k - (lg >> 1)) & 3, lg != 0, cta >> 4) + ty * HALF;
            wait_ns(t0 + batch_ns(k) + CFG(ZTILE) * CFG(TICK0));
            if (lg == 0 || (lg == 1 && (ty < 2 || k == NB - 1)) || (lg == 2 && k > 0 && ty > 1)) {
                st_pkt(dst, v0, v1, v2, ~0u);
                asm volatile("atom.relaxed.gpu.global.exch.b32 %0, [%1+12], %2;" : "=r"(v0) : "l"(dst), "r"(lane < 4 ? 0x3f800000u : 0u) : "memory");
                v0 = ~v0;
            }
            if (__any_sync(0xffffffffu, v0 != 0)) __trap();
            const char* cnt = p.scr + SCR_COUNT;
            if (lane < 2) asm volatile("red.relaxed.gpu.global.add.u32 [%0], 1;" ::"l"(cnt + lane * HALF) : "memory");
            const uint32_t target = ((epoch - 1) * NB + k + 1) * NCTA;
            cnt += near_half();
            SPIN_DECL;
            uint32_t v;
            do {
                __nanosleep(100);
                asm volatile("ld.relaxed.gpu.global.u32 %0, [%1];" : "=r"(v) : "l"(cnt) : "memory");
                SPIN_CHECK(v);
            } while (__any_sync(0xffffffffu, (int)(v - target) < 0));
        }
        __syncwarp();
        if (lane == 0) mbar_arrive(bar_at(B_Z));
        if (k > 1) {
            const int b = k - 2;
            const char* src = own + acc_off(b, 1, cta >> 4) + (2 + ((lane >> 1) & 1)) * HALF;
            unsigned short* o = p.out + b * DM + col + (lane >> 2) * 16;
            const bool on = !(lane & 2) && lane < (cl & 2 ? 8 : 12);
            wait_clk(clk32() + CFG(DLY_F));
            float cnt;
            SPIN_DECL;
            do {
                const uint4 v = ld_pkt(src);
                SPIN_CHECK(k);
                cnt = F(v.w) + shx(F(v.w), 2);
                const float y0 = F(v.x) + shx(F(v.x), 2), y1 = F(v.y) + shx(F(v.y), 2), y2 = F(v.z) + shx(F(v.z), 2);
                const uint32_t x01 = badd2(r.x, badd2(r.y, bmul2(pack2(y0, y1), r.w)));
                const uint32_t x2 = badd2(r.z, badd2(r.z >> 16, bmul2(pack2(y2, 0.f), r.w)));
                if (cnt == NCTA && on) *o = lane < 4 ? x01 : lane < 8 ? x01 >> 16 : x2;
            } while (__any_sync(0xffffffffu, cnt != NCTA));
            TRACES((2 * b + 1) * 6 + 4);
        }
    }
}

__host__ __device__ constexpr uint32_t desc_lo(uint32_t addr) { return ((addr & 0x3FFFFu) >> 4) | (1u << 16); }
constexpr uint32_t DESC_HI_TILE = (3072u >> 4) | (1u << 30);
constexpr uint32_t DESC_HI_VEC = 1u;
template <int TA, int AOFF, int BOFF>
__device__ __forceinline__ void wgmma_n8(float (&d)[4], uint32_t alo, uint32_t blo, int accumulate) {
    asm volatile("{\n.reg .pred p;\n.reg .b32 a, b;\n.reg .b64 da, db;\nsetp.ne.b32 p, %6, 0;\n"
                 "add.u32 a, %4, %8;\nadd.u32 b, %5, %9;\nmov.b64 da, {a, %10};\nmov.b64 db, {b, %11};\n"
                 "wgmma.mma_async.sync.aligned.m64n8k16.f32.bf16.bf16 {%0,%1,%2,%3}, da, db, p, 1, 1, %7, 0;\n}"
                 : "+f"(d[0]), "+f"(d[1]), "+f"(d[2]), "+f"(d[3])
                 : "r"(alo), "r"(blo), "r"(accumulate), "n"(TA), "n"(AOFF >> 4), "n"(BOFF >> 4), "n"(DESC_HI_TILE), "n"(DESC_HI_VEC));
}
template <int KS, int END>
__device__ __forceinline__ void qk_steps(float (&d)[4], uint32_t alo, uint32_t blo) {
    if constexpr (KS < END) {
        wgmma_n8<0, (KS >> 2) * 1024 + (KS & 3) * 32, KS * 32>(d, alo, blo, KS > 0);
        qk_steps<KS + 1, END>(d, alo, blo);
    }
}
__device__ __forceinline__ void pv_steps(float (&e)[3][4], uint32_t alo, uint32_t blo, int acc) {
    wgmma_n8<1, 0, 0>(e[0], alo, blo, acc); wgmma_n8<1, 1024, 0>(e[1], alo, blo, acc); wgmma_n8<1, 2048, 0>(e[2], alo, blo, acc);
    wgmma_n8<1, 6144, 32>(e[0], alo, blo, 1); wgmma_n8<1, 7168, 32>(e[1], alo, blo, 1); wgmma_n8<1, 8192, 32>(e[2], alo, blo, 1);
}
__device__ __forceinline__ void wg_fence() { asm volatile("wgmma.fence.sync.aligned;" ::: "memory"); }
__device__ __forceinline__ void wg_commit() { asm volatile("wgmma.commit_group.sync.aligned;" ::: "memory"); }
template <int N> __device__ __forceinline__ void wg_wait() { asm volatile("wgmma.wait_group.sync.aligned %0;" ::"n"(N) : "memory"); }
__device__ __forceinline__ void acc_ready(float (&d)[4]) { asm volatile("" : "+f"(d[0]), "+f"(d[1]), "+f"(d[2]), "+f"(d[3]) :: "memory"); }
__device__ __forceinline__ uint32_t score_pair(float (&d)[4]) {
    acc_ready(d);
    const uint32_t r = pack2(d[0], d[2]);
    return pack2(bf_lo(r) * SCALE, bf_hi(r) * SCALE);
}

__device__ __forceinline__ void attention_role(const Params& p, int w, int lane) {
    const int cta = cta_id(), t4 = lane & 3, g = lane >> 2;
    mbar_wait(bar_at(B_EP), 0);
    const uint32_t tag0 = lds32(SM_EPOCH) * NB;
    const char* const odst = p.scr + SCR_O + head_off(cta >> 2) + (2 * w + (g >> 2)) * 256 + (cta & 3) * 64 + (g & 3) * 16;
    const uint32_t pdst = SM_P + ((t4 + 3) & 3) * PSTR + (16 * w + g) * 2;
    auto softmax = [&](uint32_t& sc, int ps) -> uint32_t {
        const float s0 = bf_lo(sc), s1 = bf_hi(sc);
        int key = __float_as_int(fmaxf(s0, s1));
        key ^= (key >> 31) & 0x7fffffff;
        key = __reduce_max_sync(0xffffffffu, key);
        sts32(SM_MAX + w * 4, key);
        bar_sync<4, 128>();
        const uint4 mx = lds128(SM_MAX);
        key = max(max((int)mx.x, (int)mx.y), max((int)mx.z, (int)mx.w));
        key ^= (key >> 31) & 0x7fffffff;
        const float mb = __int_as_float(key) * LOG2E;
        const uint32_t pp = pack2(fast_ex2(fmaf(s0, LOG2E, -mb)), fast_ex2(fmaf(s1, LOG2E, -mb)));
        sts16(pdst + ps * 4 * PSTR, pp); sts16(pdst + ps * 4 * PSTR + 16, pp >> 16);
        fence_async();
        bar_sync<4, 128>();
        sc = pp;
        return key;
    };
    auto put_sum = [&](uint32_t pp, int ps) {
        uint32_t fs;
        asm volatile("redux.sync.add.u32 %0, %1, 0xffffffff;" : "=r"(fs) : "r"(__float2uint_rn((bf_lo(pp) + bf_hi(pp)) * 8388608.f)) : "memory");
        sts32(SM_SUM + ps * 16 + w * 4, fs);
    };
    auto aux_word = [&](uint32_t mx, const uint4& u, int k) {
        const float l = __uint2float_rn((u.x + u.y) + (u.z + u.w)) * (1.f / 8388608.f);
        return (g < 4 ? mx : (__float_as_uint(l) + 0x80u) & 0xffffff00u) | ((tag0 + k) & 0x7fu) | 0x80u;
    };
    auto send = [&](float (&e)[3][4], uint32_t aux, int ps) {
        acc_ready(e[0]); acc_ready(e[1]); acc_ready(e[2]);
        const uint32_t o0 = pack2(e[0][0], e[0][2]), o1 = pack2(e[1][0], e[1][2]), o2 = pack2(e[2][0], e[2][2]);
        st_pkt2_if(t4 == 0, odst + ps * 2048, o0, o1, o2, aux);
        mbar_arrive_if(lane == 0, bar_at(ps ? B_RV : B_PS));
    };
    mbar_wait(bar_at(B_QR), 0);
    TRACES(73);
#pragma unroll 1
    for (int it = 0; it <= NB; it++) {
        uint32_t m1 = 0;
        if (it < NB) {
            const uint32_t tab = slots(it);
            const uint32_t ka = SB + (2 * w + ((lane >> 3) & 1)) * 3072 + (lane & 7) * 128 + (((lane >> 4) ^ (lane & 7)) << 4);
            const uint32_t qa = SM_Q + it * 384 + (lane >> 3) * 16;
            uint32_t sc = 0;
#pragma unroll 1
            for (int u = 0; u < 4; u++) {
                const uint32_t base = ka + slot_at(tab, pass_nibble(it, u)) * PAIR;
                mbar_wait(bar_at(B_F1 + 2 * u + (w >> 1)), it & 1);
                float d0[4] = {}, d1[4] = {};
#pragma unroll
                for (int c = 0; c < 6; c++) {
                    uint32_t a0[4], a1[4], b[4];
                    ldsm4(b, qa + c * 64);
                    ldsm4(a0, (base ^ ((c & 1) * 64)) + (c >> 1) * 1024);
                    ldsm4(a1, (base ^ ((c & 1) * 64 + 32)) + (c >> 1) * 1024);
                    mma16816(d0, a0[0], a0[1], a0[2], a0[3], b[0], b[1]);
                    mma16816(d1, a1[0], a1[1], a1[2], a1[3], b[2], b[3]);
                }
                const uint32_t r = pack2(d0[0] + d1[0], d0[2] + d1[2]);
                mbar_arrive_if(lane == 0, bar_at(B_RR + 2 * u + (w >> 1)));
                if (t4 == ((u + 1) & 3)) sc = pack2(bf_lo(r) * SCALE, bf_hi(r) * SCALE);
            }
            m1 = softmax(sc, 0);
            put_sum(sc, 0);
        }
        if (it > 0) {
            const int k = it - 1;
            const uint32_t tab = slots(k);
            const uint32_t v0 = slot_at(tab, k < NB - 1 ? 0 : 4);
            TRACES(48 + k * 6);
            if (k > 0) mbar_wait(bar_at(B_F3), it & 1);
            mbar_wait(bar_at(B_QR), it & 1);
            fence_async();
            TRACES(49 + k * 6);
            float d[4][4] = {};
            const bool busy = k < NB - 1;
#pragma unroll
            for (int u = 0; u < 4; u++) {
                const uint32_t alo = desc_lo(SB) + slot_at(tab, u) * (PAIR >> 4), blo = desc_lo(SM_Q + 4 * 384);
                wg_fence();
                qk_steps<0, 6>(d[u], alo, blo);
                wg_commit();
                if (busy) {
                    wg_wait<1>();
                    if (u > 0) mbar_arrive_if(lane == 0, bar_at(B_RK + u - 1));
                }
                wg_fence();
                qk_steps<6, 12>(d[u], alo, blo);
                wg_commit();
                if (u < 3 && busy) wg_wait<1>();
            }
            wg_wait<2>();
            uint32_t sc = shi(score_pair(d[0]), lane & 28), s = shi(score_pair(d[1]), lane & 28);
            if (t4 == 2) sc = s;
            s = shi(score_pair(d[2]), lane & 28);
            if (t4 == 3) sc = s;
            wg_wait<0>();
            s = score_pair(d[3]);
            if (t4 == 0) sc = s;
            mbar_arrive_if(lane == 0, bar_at(B_RK + 3));
            TRACES(50 + k * 6);
            const uint32_t m2 = softmax(sc, 1);
            TRACES(51 + k * 6);
            float e[3][4] = {};
#pragma unroll
            for (int t = 0; t < 8; t++) {
                const int pr = ((t >> 1) + 1) & 3;
                if (t == 6 && k < NB - 1) mbar_wait(bar_at(B_FL), k & 1);
                wg_fence();
                pv_steps(e, desc_lo(SB + (t & 1) * TILE) + (pr ? slot_at(tab, 4 + pr) : v0) * (PAIR >> 4), desc_lo(SM_P + (4 + pr) * PSTR + (t & 1) * 64), t > 0);
                wg_commit();
                if (t < 7 && busy) wg_wait<1>();
                if (t == 1) put_sum(sc, 1);
            }
            bar_sync<4, 128>();
            const uint32_t aux = opaque(aux_word(m2, lds128(SM_SUM + 16), k));
            wg_wait<0>();
            send(e, aux, 1);
            TRACES(52 + k * 6);
        }
        if (it < NB) {
            const uint32_t tab = slots(it);
            if (it == 0) st_pkt2_if(t4 == 0, odst, 0, 0, 0, 0);
            bar_sync<4, 128>();
            const uint32_t aux = opaque(aux_word(m1, lds128(SM_SUM), it));
            float e[3][4] = {};
#pragma unroll 1
            for (int u = 0; u < 4; u++) {
                const uint32_t alo = desc_lo(SB) + slot_at(tab, 4 + u) * (PAIR >> 4), blo = desc_lo(SM_P) + u * (PSTR >> 4);
                mbar_wait(bar_at(B_F1 + 8 + 2 * u), it & 1);
                wg_fence();
                pv_steps(e, alo, blo, u > 0);
                wg_commit();
                wg_wait<1>();
                if (u == 1) mbar_arrive_if(lane == 0, bar_at(B_RP));
                mbar_wait(bar_at(B_F1 + 9 + 2 * u), it & 1);
                wg_fence();
                pv_steps(e, alo + (TILE >> 4), blo + 4, 1);
                wg_commit();
                wg_wait<1>();
            }
            wg_wait<0>();
            send(e, aux, 0);
            TRACES(53 + it * 6);
        }
    }
}

__device__ __forceinline__ void ln_finish(float s, float q, float& mean_b, float& rden) {
    const float mean = s * (1.f / DM);
    const float var = fmaxf(fmaf(q, 1.f / DM, -mean * mean), 0.f);
    mean_b = bfr(mean);
    rden = fast_rcp(bfr(fast_sqrt(bfr(bfr(var) + 1e-5f))));
}
__device__ __forceinline__ uint32_t ln_apply(uint32_t w, float mean_b, float rden) {
    const uint32_t d = bsub2(w, __byte_perm(__float_as_uint(mean_b), 0, 0x3232));
    return pack2(bf_lo(d) * rden, bf_hi(d) * rden);
}
__device__ __forceinline__ void put_x(uint32_t x01, uint32_t x2, uint32_t wa, bool e2) {
    jitter();
    sts16(wa, x01); sts16(wa + 8, x01 >> 16);
    sts16_if(!e2, wa + 16, x2);
}
__device__ __forceinline__ void get_x(uint32_t (&b)[10], uint32_t ra) {
    __syncwarp();
    const uint4 u = lds128(ra), v = lds128(ra + 16);
    const uint2 z = lds64(ra + 32);
    b[0] = u.x; b[1] = u.y; b[2] = u.z; b[3] = u.w; b[4] = v.x; b[5] = v.y; b[6] = v.z; b[7] = v.w; b[8] = z.x; b[9] = z.y;
}
__device__ __forceinline__ float fold(float a, float b, bool sel, int m) { return (sel ? b : a) + shx(sel ? a : b, m); }

__device__ __forceinline__ void chain_role(const Params& p, int w, int lane) {
    const int cta = cta_id(), h = cta >> 2, s = cta & 3;
    const int g = lane >> 2, t4 = lane & 3;
    const bool e1 = t4 & 1, e2 = t4 & 2;
    uint32_t wq[5][3][4], wo[3][5][4], wg[5][4], wh[5][2], wd[4][4];
    const int col0 = 80 * w + (e2 ? 48 : 0) + g + (e1 ? 8 : 0);
    const uint32_t xw = opaque(SM_X + w * 384 + 48 * (g >> 1) + (e2 ? 24 : 0) + (e1 ? 4 : 0) + 2 * (g & 1));
    const uint32_t xr = opaque(g == 1 ? SM_ONES : SM_X + w * 384 + (g == 3 ? 192 : 0) + 48 * t4);
    TRACES(75);
    sts32_if(lane < 12, SM_ONES + lane * 4, 0x3f803f80u);
    uint32_t zero = lane >> 5;
    const int mi = lane >> 3, mr = lane & 7;
    mbar_wait(bar_at(B_W), 0);
    TRACES(74);
    sts16(xw + 192, lds16(ST_X + 5120 + col0 * 2)); sts16(xw + 200, lds16(ST_X + 5120 + col0 * 2 + 32));
    sts16_if(!e2, xw + 208, lds16(ST_X + 5120 + col0 * 2 + 64));
#pragma unroll
    for (int i = 0; i < 5; i++)
#pragma unroll
        for (int mt = 0; mt < 3; mt++) ldsm4t(wq[i][mt], ST_WQ + (80 * w + 16 * i + mr + 8 * (mi >> 1)) * 96 + 32 * mt + 16 * (mi & 1), zero);
    const bool odd = cta & 1;
    const uint32_t lo = ST_WD + (mr + (odd ? 4 : 0)) * 1280 + 160 * w + 16 * (mi & 1);
    const uint32_t hi = ST_WD + ((mr & 3) + (odd ? 0 : 8)) * 1280 + 160 * w + 16 * (mi & 1);
    ldsm4t(wd[0], lo + 96 * (mi >> 1), zero);
    ldsm4t(wd[1], lo + 96 * (mi >> 1) + 32, zero);
    ldsm4t(wd[2], (mi < 2 ? lo : hi) + 64, zero);
    ldsm4t(wd[3], hi + 32 * (mi >> 1) + 96 * (mr >> 2), zero);
    fence_async();
    __syncwarp();
    mbar_arrive_if(lane == 0, bar_at(B_WC));
    mbar_wait(bar_at(B_EP), 0);
    const uint32_t near = __shfl_sync(0xffffffffu, near_half(), 0);
    uint32_t x01 = 0, x2 = 0, nx01 = 0, nx2 = 0;
#pragma unroll 1
    for (int n = -5; n < NROUND; n++) {
        const bool last = (ORD_LAST >> (n & 15)) & 1, head = !((ORD_NO_HEAD >> (n & 15)) & 1);
        const int k = (ORD_BATCH >> (2 * (n & 15))) & 3;
        if (n > -5 && n <= 0) bar_sync<7, 288>();
        else if (!last) bar_sync<2, 256>();
        TRACES(n <= 0 ? 83 + n : 95);
        const char* const slice = p.scr + acc_off(k, last, w);
        const char* const cell = opaque(slice + g * 256 + t4 * 16);
        if (n < -1) {
            const uint32_t xa = ST_X + (n + 5) * 1280, ln = opaque(lane);
            const int col0 = 80 * w + (ln & 2 ? 48 : 0) + (ln >> 2) + (ln & 1 ? 8 : 0);
            float sm = 0.f, sq = 0.f;
#pragma unroll
            for (int i = 0; i < 5; i++) {
                const uint2 c = lds64(xa + i * 256 + ln * 8);
                sm += (bf_lo(c.x) + bf_hi(c.x)) + (bf_lo(c.y) + bf_hi(c.y));
                sq = fmaf(bf_lo(c.x), bf_lo(c.x), fmaf(bf_hi(c.x), bf_hi(c.x), fmaf(bf_lo(c.y), bf_lo(c.y), fmaf(bf_hi(c.y), bf_hi(c.y), sq))));
            }
            x01 = lds16(xa + col0 * 2) | lds16(xa + col0 * 2 + 32) << 16;
            x2 = lds16(xa + col0 * 2 + 64);
#pragma unroll
            for (int o = 16; o; o >>= 1) { sm += shx(sm, o); sq += shx(sq, o); }
            float mean_b, rden;
            ln_finish(sm, sq, mean_b, rden);
            x01 = ln_apply(x01, mean_b, rden);
            x2 = ln_apply(x2, mean_b, rden);
            put_x(x01, x2, xw, e2);
        } else {
            if (n >= 0 && head) {
                if (!last || n == NROUND - 1) mbar_wait(bar_at(B_Z), (k + last) & 1);
                const char* src = p.scr + SCR_O + head_off(h) + head_near(h, near) + last * 2048 + (w & 6) * 256 + (lane & 15) * 16;
                const uint32_t tag = (lds32(SM_EPOCH) * NB + k) | 0x80u;
                mbar_wait(bar_at(last ? B_RV : B_PS), k & 1);
                uint4 v, z;
                {
                    SPIN_DECL;
                    do {
                        v = ld_pkt(src); z = ld_pkt(src + 256);
                        SPIN_CHECK(n);
                    } while (__any_sync(0xffffffffu, (((v.w ^ tag) | (z.w ^ tag)) & 0xffu) != 0));
                }
                TRACES(tr + 0);
                float a[3][4] = {};
                const uint32_t bb[3][2] = {{v.x, v.y}, {z.x, z.y}, {v.z, z.z}};
                float sa, sb, rl;
#pragma unroll
                for (int i = 0; i < 3; i++) {
                    const uint32_t l0 = g < 4 ? bb[i][0] : 0, l1 = g < 4 ? bb[i][1] : 0, h0 = g < 4 ? 0 : bb[i][0], h1 = g < 4 ? 0 : bb[i][1];
#pragma unroll
                    for (int mt = 0; mt < 5; mt++)
                        mma16816(a[mt % 3], wo[i][mt][0], wo[i][mt][1], wo[i][mt][2], wo[i][mt][3], mt < 3 ? l0 : h0, mt < 3 ? l1 : h1);
                    if (i == 0) {
                        int key = v.w & 0xffffff00u;
                        key ^= (key >> 31) & 0x7fffffff;
                        key = __reduce_max_sync(0xffffffffu, key);
                        key ^= (key >> 31) & 0x7fffffff;
                        const float ws = fast_ex2((F(v.w & 0xffffff00u) - __int_as_float(key)) * LOG2E);
                        sa = shi(ws, e1 ? 8 : 0); sb = shi(ws, e1 ? 12 : 4);
                        rl = ws * F(z.w & 0xffffff00u);
                        rl += shx(rl, 4);
                    }
                    if (i == 1) rl += shx(rl, 8);
                }
                float y[3];
#pragma unroll
                for (int j = 2; j < 5; j++) {
                    const int mt = j % 3;
                    y[mt] = fold(fmaf(a[mt][0], sa, a[mt][1] * sb), fmaf(a[mt][2], sa, a[mt][3] * sb), e1, 1);
                }
                const uint32_t pa = SM_PO + w * 512 + lane * 16;
                if (w < 2) {
                    const char* dst = opaque(cell + s * 16384);
                    rl = fast_rcp(rl);
                    bar_sync<1, 256>();
                    const uint4 c1 = lds128(pa), c2 = lds128(pa + 1024), c3 = lds128(pa + 2048);
                    const float z0 = ((y[0] + F(c1.x)) + (F(c2.x) + F(c3.x))) * rl, z1 = ((y[1] + F(c1.y)) + (F(c2.y) + F(c3.y))) * rl;
                    const float z2 = ((y[2] + F(c1.z)) + (F(c2.z) + F(c3.z))) * rl;
                    red_cell(dst + (near ^ HALF), z0, z1, z2);
                    red_cell(dst + near, z0, z1, z2);
                } else {
                    stsf4(pa - 1024, y[0], y[1], y[2], 0.f);
                    bar_sync<1, 256>();
                }
                TRACES(tr + 1);
                if ((ORD_NO_TAIL >> n) & 1) continue;
                const uint32_t tsend = clk32();
                if (n == 0) {
                    st_pkt2_if(lane < 4, p.scr + SCR_O + head_off(h) + 2048 + w * 256 + s * 64 + lane * 16, 0, 0, 0, 0);
                    __syncwarp();
                } else if (!last) {
                    const char* nsrc = p.scr + acc_off(k - 1, 1, w) + near + g * 256 + t4 * 16;
                    SPIN_DECL;
                    do {
                        v = ld_pkt(nsrc);
                        SPIN_CHECK(n);
                        nx01 = pack2(F(v.x), F(v.y)); nx2 = pack2(F(v.z), 0.f);
                    } while (__any_sync(0xffffffffu, v.w != FULL_A));
                }
                wait_clk(tsend + (w < 2 ? 0 : 60) + (n < QUIET ? CFG(DLY_AL) : CFG(DLY_A)));
                {
                    SPIN_DECL;
                    do {
                        v = ld_pkt(cell + near);
                        SPIN_CHECK(n);
                        x01 = pack2(F(v.x), F(v.y));
                        x2 = pack2(F(v.z), 0.f);
                        put_x(x01, x2, xw, e2);
                    } while (__any_sync(0xffffffffu, v.w != FULL_A));
                }
                TRACES(tr + 2);
            } else if (n >= 0) {
                x01 = nx01; x2 = nx2;
                put_x(x01, x2, xw, e2);
            } else {
                mbar_wait(bar_at(B_W + 1), 0);
                const uint32_t ln = opaque(lane);
                const int mi = ln >> 3, mr = ln & 7;
                uint32_t zero = ln >> 5;
                TRACES(76);
#pragma unroll
                for (int i = 0; i < 3; i++) {
                    const int d = 16 * (w >> 1) + (mr >> 1) + 8 * (mr & 1) + (i < 2 ? 64 * (mi >> 1) + 4 * i : 128 + 4 * (mi >> 1));
#pragma unroll
                    for (int mt = 0; mt < 5; mt++) ldsm4t(wo[i][mt], ST_WO + d * 320 + 160 * (w & 1) + 32 * mt + 16 * (mi & 1), zero);
                }
                fence_async();
                __syncwarp();
                mbar_arrive_if(lane == 0, bar_at(B_WC + 1));
                mbar_wait(bar_at(B_W + 2), 0);
                TRACES(77);
#pragma unroll
                for (int i = 0; i < 5; i++) {
                    const uint32_t ga = ST_WG + (mi & 1) * 20480 + (80 * w + 16 * i + mr + 8 * (mi >> 1)) * 32;
                    uint32_t r[4];
                    ldsm4t(wg[i], ga + (odd ? 16 : 0), zero);
                    ldsm4t(r, ga + (odd ? 0 : 16), zero);
#pragma unroll
                    for (int kh = 0; kh < 2; kh++) {
                        const uint32_t moved = __shfl_xor_sync(0xffffffffu, odd ? r[2 * kh] : r[2 * kh + 1], 16);
                        wh[i][kh] = (g < 4) == odd ? moved : odd ? r[2 * kh + 1] : r[2 * kh];
                    }
                }
                fence_async();
                __syncwarp();
                mbar_arrive_if(lane == 0, bar_at(B_WC + 2));
                TRACES(72);
                x01 = 0x3f803f80u; x2 = 0x3f80u;
                put_x(x01, x2, xw, e2);
            }
            uint32_t b[10];
            get_x(b, xr);
            float a[2][4] = {};
#pragma unroll
            for (int i = 0; i < 5; i++) {
                mma16816(a[0], wg[i][0], wg[i][1], wg[i][2], wg[i][3], b[2 * i], b[2 * i + 1]);
                mma16816(a[1], wh[i][0], b[2 * i], wh[i][1], b[2 * i + 1], b[2 * i], b[2 * i + 1]);
            }
            stsf(SM_PG + (w >> 2) * 512 + (g + 8 * t4) * 16 + (w & 3) * 4, e2 ? (e1 ? a[1][2] : a[1][0]) : (e1 ? a[0][2] : a[0][0]));
            const uint2 cs = lds64(SM_CSG + lane * 48);
            const char* dst = opaque(cell + 3 * HALF - near);
            bar_sync<2, 256>();
            const float S = sum8(lds128(SM_PG + lane * 16), lds128(SM_PG + 512 + lane * 16));
            const float sx = shi(S, 25), sq = shi(S, 24), Su = shi(S, lane + (lane < 16 ? 8 : 4));
            if (n < 0) {
                if (w == 0) stsf2(SM_CSG + lane * 48, S, Su);
            } else {
                float mean_b, rden;
                ln_fast(sx, sq, mean_b, rden);
                const float gv = bfr(fmaf(-mean_b, F(cs.x), S) * rden), uv = bfr(fmaf(-mean_b, F(cs.y), Su) * rden);
                const float sg = fast_rcp(1.f + fast_ex2(-LOG2E * gv));
                const uint32_t hb = pack2(bfr(gv * sg) * uv, 0.f);
                const uint32_t b0 = __byte_perm(shi(hb, 2 * t4), shi(hb, 2 * t4 + 1), 0x5410);
                const uint32_t b1 = __byte_perm(shi(hb, e1 ? 18 : 16), shi(hb, e1 ? 19 : 17), 0x5410);
                const bool up = g >= 4;
                const uint32_t l0 = up ? 0 : b0, h0 = up ? b0 : 0;
                const uint32_t m1 = up == e2 ? b1 : 0;
                float d[3][4] = {};
                mma16816(d[0], wd[0][0], wd[0][1], wd[0][2], wd[0][3], l0, h0);
                mma16816(d[1], wd[1][0], wd[1][1], wd[1][2], wd[1][3], l0, h0);
                mma16816(d[2], wd[2][0], wd[2][1], wd[2][2], wd[2][3], l0, up ? 0 : m1);
                mma1688(d[0], wd[3][0], wd[3][1], m1);
                mma1688(d[1], wd[3][2], wd[3][3], m1);
                red_cell(dst, e1 ? d[0][2] : d[0][0], e1 ? d[1][2] : d[1][0], e1 ? d[2][2] : d[2][0]);
                const uint32_t tsend = clk32();
                TRACES(tr + 3);
                if (last && w != cta >> 4) continue;
                const float sgr = shi(sg, 27);
                const uint32_t sg2 = pack2(sgr, sgr);
                ln_finish(sx, sq, mean_b, rden);
                const uint32_t n01 = opaque(ln_apply(x01, mean_b, rden)), n2 = opaque(ln_apply(x2, mean_b, rden));
                if (last) {
                    sts128_if(lane >> 1 == (cta & 15), SM_FIN + (lane & 1) * 16, x01, n01, __byte_perm(x2, n2, 0x5410), sg2);
                    mbar_arrive_if(lane >> 1 == (cta & 15), bar_at(B_FIN));
                    __syncwarp();
                    continue;
                }
                wait_clk(tsend + (n < QUIET ? CFG(DLY_BL) : CFG(DLY_B)));
                const uint32_t r01 = x01, r2 = x2;
                float cnt;
                SPIN_DECL;
                do {
                    const uint4 v = ld_pkt(cell + 2 * HALF + near), z = ld_pkt(dst);
                    SPIN_CHECK(n);
                    cnt = F(v.w) + F(z.w);
                    x01 = badd2(r01, badd2(n01, bmul2(pack2(F(v.x) + F(z.x), F(v.y) + F(z.y)), sg2)));
                    x2 = badd2(r2, badd2(n2, bmul2(pack2(F(v.z) + F(z.z), 0.f), sg2)));
                    put_x(x01, x2, xw, e2);
                } while (__any_sync(0xffffffffu, cnt != NCTA));
                TRACES(tr + 4);
            }
        }
        {
            uint32_t b[10];
            get_x(b, xr);
            float a[3][4] = {};
            const float f0 = bf_lo(x01), f1 = bf_hi(x01), f2 = e2 ? 0.f : bf_lo(x2);
            float st;
#pragma unroll
            for (int i = 0; i < 5; i++) {
#pragma unroll
                for (int mt = 0; mt < 3; mt++) {
                    mma16816(a[mt], wq[i][mt][0], wq[i][mt][1], wq[i][mt][2], wq[i][mt][3], b[2 * i], b[2 * i + 1]);
                    if (i == 0 && mt == 0) st = fold(fmaf(f0, f0, fmaf(f1, f1, f2 * f2)), (f0 + f1) + f2, g & 1, 4);
                }
                if (i < 4) st += shx(st, i < 2 ? 1 << i : 2 << i);
            }
            const uint32_t pa = SM_PQ + (w >> 2) * 1024 + (g & 1) * 512 + ((e2 ? 16 : 0) + (e1 ? 4 : 0) + (g >> 1)) * 16 + (w & 3) * 4;
            stsf(pa + 128, e2 ? st : e1 ? a[1][2] : a[1][0]);
            stsf(pa, e2 ? (e1 ? a[2][2] : a[2][0]) : (e1 ? a[0][2] : a[0][0]));
            bar_sync<3, 288>();
            if (n >= 0 && w == cta >> 4) {
                red_cell2_if(lane >> 1 == (cta & 15), cell + (acc_off(k, 1, 0) - acc_off(k, 0, 0)), f0, f1, f2);
                __syncwarp();
            }
        }
    }
}

__host__ __device__ constexpr int bar_count(int i) {
    return i < 16 ? 1 : i < B_RR ? 0 : i < B_RK ? 2 : i <= B_RV ? 4 : i == B_Z ? 1 : i == B_EP ? 9 : i < B_WC ? 0 : i < B_FIN ? 8 :
           i == B_FIN ? 2 : i == B_PS || i == B_RP ? 4 : i == B_QR ? 32 : 1;
}
template <int I, int END> __device__ __forceinline__ void init_bars() {
    if constexpr (I < END) {
        if (bar_count(I)) mbar_init(bar_at(I), bar_count(I));
        init_bars<I + 1, END>();
    }
}
template <int ID> __device__ __forceinline__ void role_exit() { asm volatile("exit; // %0" ::"n"(ID)); }
constexpr int NTHREADS = 512;
#define STR2(x) #x
#define STR(x) STR2(x)
__global__ void __launch_bounds__(NTHREADS, 1)
decode_kernel(const Params p, const __grid_constant__ Maps tm) {
    extern __shared__ __align__(1024) unsigned char smem[];
    if (threadIdx.x == 0) l2_prefetch(p.wq + (size_t)blockIdx.x * 12288, 12288);
    const uint32_t t0 = now_ns() - CFG(LEAD);
    const int lane = threadIdx.x & 31;
    const int warp = __reduce_max_sync(0xffffffffu, threadIdx.x >> 5);
    if (warp < 8) {
        asm volatile("setmaxnreg.inc.sync.aligned.u32 " STR(CFG_REG_CHAIN) ";");
        bar_arrive<5, 480>();
        const uint32_t vote = probe_near(p, warp, lane);
        bar_sync<2, 256 + 32>();
        sts32(SM_NEAR + warp * 4, vote);
        mbar_arrive_if(lane == 0, bar_at(B_EP));
        chain_role(p, warp, __shfl_sync(0xffffffffu, lane, lane));
        role_exit<3>();
    } else if (warp < 12) {
        asm volatile("setmaxnreg.dec.sync.aligned.u32 " STR(CFG_REG_ATT) ";");
        if (elect_one()) {
            if (warp == 8) init_bars<0, 12>();
            else if (warp == 9) init_bars<12, 30>();
            else if (warp == 10) init_bars<30, 42>();
            else init_bars<42, NBAR>();
            asm volatile("fence.mbarrier_init.release.cluster;" ::: "memory");
            fence_async();
        }
        if (warp == 8) TRACE(236);
        bar_sync<5, 480>();
        if (warp == 8) TRACE(237);
        attention_role(p, warp - 8, lane);
        role_exit<2>();
    } else {
        asm volatile("setmaxnreg.dec.sync.aligned.u32 " STR(CFG_REG_HELP) ";");
        if (warp == 12) {
            load_role(p, &tm.k, lane, t0);
            role_exit<0>();
        } else {
            if (warp == 14) {
                if (smem_u32(smem) != SB) __trap();
                if (elect_one()) {
                    asm volatile("prefetch.tensormap [%0];" ::"l"(&tm.q) : "memory");
                    mbar_init(bar_at(B_W), 1); mbar_init(bar_at(B_W + 1), 1); mbar_init(bar_at(B_W + 2), 1);
                    asm volatile("fence.mbarrier_init.release.cluster;" ::: "memory");
                    fence_async();
                    mbar_expect_tx(bar_at(B_W), 61440 + 15360 + 6400); mbar_expect_tx(bar_at(B_W + 1), 61440); mbar_expect_tx(bar_at(B_W + 2), 40960);
                    bulk_load(ST_X, p.x, 5120, bar_at(B_W));
                    bulk_load(ST_X + 5120, p.wr, 1280, bar_at(B_W));
                }
                TRACE(238);
                reload_role(p, &tm, t0);
            } else {
                if (warp == 13 && elect_one()) {
                    asm volatile("prefetch.tensormap [%0];" ::"l"(&tm.g) : "memory");
                    asm volatile("prefetch.tensormap [%0];" ::"l"(&tm.u) : "memory");
                    asm volatile("prefetch.tensormap [%0];" ::"l"(&tm.o) : "memory");
                    asm volatile("prefetch.tensormap [%0];" ::"l"(&tm.k) : "memory");
                    asm volatile("prefetch.tensormap [%0];" ::"l"(&tm.v) : "memory");
                }
                TRACE(233 + warp);
                bar_sync<5, 480>();
                if (warp == 13) { bar_arrive<6, 64>(); q_role(p, lane); }
                else { bar_arrive<2, 256 + 32>(); zero_role(p, lane, t0); }
            }
            role_exit<1>();
        }
    }
}

typedef CUresult (*EncodeFn)(CUtensorMap*, CUtensorMapDataType, cuuint32_t, void*, const cuuint64_t*, const cuuint64_t*,
                             const cuuint32_t*, const cuuint32_t*, CUtensorMapInterleave, CUtensorMapSwizzle,
                             CUtensorMapL2promotion, CUtensorMapFloatOOBfill);

bool make_map(EncodeFn fn, CUtensorMap* m, const void* ptr, uint64_t cols, uint64_t rows, uint32_t bc, uint32_t br) {
    cuuint64_t dims[2] = {cols, rows};
    cuuint64_t strides[1] = {cols * 2};
    cuuint32_t box[2] = {bc, br};
    cuuint32_t es[2] = {1, 1};
    return fn(m, CU_TENSOR_MAP_DATA_TYPE_BFLOAT16, 2, const_cast<void*>(ptr), dims, strides, box, es, CU_TENSOR_MAP_INTERLEAVE_NONE,
              CU_TENSOR_MAP_SWIZZLE_NONE, CU_TENSOR_MAP_L2_PROMOTION_L2_128B, CU_TENSOR_MAP_FLOAT_OOB_FILL_NONE) == CUDA_SUCCESS;
}

bool make_kv_map(EncodeFn fn, CUtensorMap* m, const void* ptr) {
    cuuint64_t dims[4] = {64, 8, 3, (cuuint64_t)NB * NHEAD * SK / 8};
    cuuint64_t strides[3] = {DH * 2, 128, 8 * DH * 2};
    cuuint32_t box[4] = {64, 8, 3, 4};
    cuuint32_t es[4] = {1, 1, 1, 1};
    return fn(m, CU_TENSOR_MAP_DATA_TYPE_BFLOAT16, 4, const_cast<void*>(ptr), dims, strides, box, es, CU_TENSOR_MAP_INTERLEAVE_NONE,
              CU_TENSOR_MAP_SWIZZLE_128B, CU_TENSOR_MAP_L2_PROMOTION_L2_128B, CU_TENSOR_MAP_FLOAT_OOB_FILL_NONE) == CUDA_SUCCESS;
}

}

extern "C" void kernel_launch(void* const* d_in, const int* in_sizes, int n_in, void* d_out, int out_size) {
    (void)in_sizes; (void)n_in; (void)out_size;
    static EncodeFn fn = nullptr;
    static const char* scr = nullptr;
    if (!fn) {
        void* f = nullptr;
        cudaDriverEntryPointQueryResult qr;
        if (cudaGetDriverEntryPoint("cuTensorMapEncodeTiled", &f, cudaEnableDefault, &qr) != cudaSuccess || !f) return;
        void* sp = nullptr;
        if (cudaGetSymbolAddress(&sp, g_scratch) != cudaSuccess) return;
        scr = (const char*)(((uintptr_t)sp + (2 << 20) - 1) & ~(uintptr_t)((2 << 20) - 1));
        fn = (EncodeFn)f;
        cudaFuncSetAttribute(decode_kernel, cudaFuncAttributeMaxDynamicSharedMemorySize, SMEM_BYTES);
    }
    Maps tm;
    if (!make_kv_map(fn, &tm.k, d_in[1]) || !make_kv_map(fn, &tm.v, d_in[2])) return;
    if (!make_map(fn, &tm.q, d_in[3], NHEAD * DH, DM, 48, 128) || !make_map(fn, &tm.o, d_in[4], DM, NHEAD * DH, 160, 32)) return;
    if (!make_map(fn, &tm.g, d_in[7], FF, DM, 16, 128) || !make_map(fn, &tm.u, d_in[8], FF, DM, 16, 128)) return;
    Params p;
    p.x = (const unsigned short*)d_in[0];
    p.wq = (const char*)d_in[3];
    p.wo = (const char*)d_in[4];
    p.wr = (const unsigned short*)d_in[6];
    p.wg = (const char*)d_in[7];
    p.wu = (const char*)d_in[8];
    p.wd = (const char*)d_in[9];
    p.out = (unsigned short*)d_out;
    p.scr = scr;
    decode_kernel<<<NCTA, NTHREADS, SMEM_BYTES>>>(p, tm);
}
```
